```python
import torch

def _softmax(x, axis=-1):
    return torch.softmax(x, dim=axis)

def _gelu(x):
    return torch.nn.functional.gelu(x, approximate='tanh')

def _silu(x):
    return torch.nn.functional.silu(x)

def _sigmoid(x):
    return torch.sigmoid(x)

def _layernorm(x, axis=-1, eps=1e-05):
    m = x.mean(dim=axis, keepdim=True)
    v = x.var(dim=axis, keepdim=True, unbiased=False)
    return (x - m) / torch.sqrt(v + eps)

def _scatter_add(tgt, idx, src, axis=0):
    return tgt.clone().index_add_(axis, idx, src)

def _segment_sum(src, seg, n):
    out = torch.zeros((n,) + src.shape[1:], dtype=src.dtype)
    return out.index_add_(0, seg, src)

def _pad(x, pw):
    flat = tuple((v for pair in reversed(pw) for v in pair))
    return torch.nn.functional.pad(x, flat)
kernel_name = 'adaLN_cond__compressed_kv_cla__dense_activation_relu__decode'

def setup_inputs():

    _w = lambda a: (lambda t: t.to(torch.bfloat16) if t.is_floating_point() else t)(torch.as_tensor(a))

    def _A_setup():
        B, H, Sq, Sk, D, M = (8, 32, 1, 4096, 128, 512)
        Dc = 4 * D
        return {'x': _w((lambda *s: torch.randn(*s, dtype=torch.bfloat16) * 0.05)(B, Sq, M)), 'c_kv': _w((lambda *s: torch.randn(*s, dtype=torch.bfloat16) * 1.6)(B, Sk, Dc)), 'w_q': _w((lambda *s: torch.randn(*s, dtype=torch.bfloat16) * 1.6)(M, H, D) * M ** (-0.5)), 'w_uk': _w((lambda *s: torch.randn(*s, dtype=torch.bfloat16) * 1.6)(Dc, H, D) * Dc ** (-0.5)), 'w_uv': _w((lambda *s: torch.randn(*s, dtype=torch.bfloat16) * 1.6)(Dc, H, D) * Dc ** (-0.5)), 'w_o': _w((lambda *s: torch.randn(*s, dtype=torch.bfloat16) * 1.6)(H, D, M) * (H * D) ** (-0.5))}
    _A_in = _A_setup()

    def _B_setup():
        B, S, D, Dff = (8, 1, 512, 1792)
        return {'x': _w((lambda *s: torch.randn(*s, dtype=torch.bfloat16) * 0.05)(B, S, D)), 'w1': _w((lambda *s: torch.randn(*s, dtype=torch.bfloat16) * 0.05)(D, Dff)), 'w2': _w((lambda *s: torch.randn(*s, dtype=torch.bfloat16) * 0.05)(Dff, D))}
    _B_in = _B_setup()
    return {'A_x': _A_in['x'], 'A_c_kv': _A_in['c_kv'], 'A_w_q': _A_in['w_q'], 'A_w_uk': _A_in['w_uk'], 'A_w_uv': _A_in['w_uv'], 'A_w_o': _A_in['w_o'], 'B_x': _B_in['x'], 'B_w1': _B_in['w1'], 'B_w2': _B_in['w2'], 'c': _w((lambda *s: torch.randn(*s, dtype=torch.bfloat16) * 0.2)(8, 512) * 8.0), 'w_mod': _w((lambda *s: torch.randn(*s, dtype=torch.bfloat16) * 0.2)(512, 6 * 512) * 512 ** (-0.5) * 8.0)}

def reference(A_x, A_c_kv, A_w_q, A_w_uk, A_w_uv, A_w_o, B_x, B_w1, B_w2, c, w_mod):

    def _A_ref(x, c_kv, w_q, w_uk, w_uv, w_o):
        B, Sq, M = (x.shape[0], x.shape[1], x.shape[2])
        Sk = c_kv.shape[1]
        H, D = (w_q.shape[1], w_q.shape[2])
        q = torch.einsum('bqm,mhd->bhqd', x, w_q)
        k = torch.einsum('bkc,chd->bhkd', c_kv, w_uk)
        v = torch.einsum('bkc,chd->bhkd', c_kv, w_uv)
        scores = torch.einsum('bhqd,bhkd->bhqk', q, k) * D ** (-0.5)
        off = Sk - Sq
        qi = torch.arange(Sq)[:, None]
        kj = torch.arange(Sk)[None, :]
        cmask = kj <= qi + off
        scores = torch.where(cmask[None, None], scores, -1000000000.0)
        p = _softmax(scores, axis=-1)
        ctx = torch.einsum('bhqk,bhkd->bhqd', p, v)
        return torch.einsum('bhqd,hdm->bqm', ctx, w_o)

    def _B_ref(x, w1, w2):
        h = torch.einsum('bsd,df->bsf', x, w1)
        zero = torch.zeros_like(h)
        h = torch.maximum(h, zero)
        return torch.einsum('bsf,fd->bsd', h, w2)
    x = A_x
    mod = (_silu(c) @ w_mod).reshape(c.shape[0], 6, 1, -1)
    sa, ca, ga, sb, cb, gb = (mod[:, 0].clone(), mod[:, 1].clone(), mod[:, 2].clone(), mod[:, 3].clone(), mod[:, 4].clone(), mod[:, 5].clone())
    h = _layernorm(x, axis=-1) * (1 + ca) + sa
    x = x + ga * _A_ref(h, A_c_kv, A_w_q, A_w_uk, A_w_uv, A_w_o)
    h = _layernorm(x, axis=-1) * (1 + cb) + sb
    x = x + gb * _B_ref(h, B_w1, B_w2)
    return x
```

```cpp
#include <cuda_runtime.h>
#include <cuda.h>
#include <cuda_bf16.h>
#include <stdint.h>

namespace {

constexpr int NCTA = 128;
constexpr int NTHREADS = 384;
constexpr int FCH = 16;
constexpr int NFF = 1792 / FCH;
constexpr int NREP = 4;

constexpr uint32_t SB = 1024;
constexpr uint32_t OFF_BUFA = SB;
constexpr uint32_t OFF_BUFB = SB + 65536;
constexpr uint32_t OFF_R0 = SB + 131072;
constexpr uint32_t OFF_R1 = SB + 163840;
constexpr uint32_t OFF_R2 = SB + 196608;
constexpr uint32_t OFF_MISC = SB + 229376;
constexpr uint32_t OFF_BARS = OFF_MISC;
constexpr uint32_t OFF_EPOCH = OFF_MISC + 768;
constexpr uint32_t OFF_TL = OFF_MISC + 784;
constexpr uint32_t OFF_BS = OFF_MISC + 1024;
constexpr uint32_t SMEM_BYTES = 229376 + 3072;
constexpr uint32_t OFF_P0S = OFF_R0 + 24576;
constexpr uint32_t OFF_BS2 = OFF_R0 + 30720;
constexpr uint32_t OFF_PT = OFF_R1;
constexpr uint32_t OFF_RED = OFF_BS;
constexpr uint32_t OFF_ALPHA = OFF_BS + 512;
constexpr uint32_t OFF_MREF = OFF_BS + 640;
constexpr uint32_t OFF_ONES = OFF_BS + 768;
__host__ __device__ constexpr uint32_t box_off(int n) {
  return n < 16 ? SB + n * 8192 : n < 23 ? OFF_R1 + (n - 15) * 8192 : n < 39 ? SB + (n - 23) * 8192 : OFF_R1 + 8192;
}
constexpr uint32_t OFF_WUV = OFF_R2;
constexpr uint32_t OFF_XE = OFF_R1 + 16384;
constexpr uint32_t OFF_WO = OFF_BUFA;
constexpr uint32_t OFF_W1 = OFF_BUFA + 32768;
constexpr uint32_t OFF_W2 = OFF_BUFA + 49152;
constexpr uint32_t OFF_BS4 = OFF_BUFB;
constexpr uint32_t OFF_BS5 = OFF_BUFB + 4096;
constexpr uint32_t OFF_MLS = OFF_BUFB + 4096;
constexpr uint32_t OFF_REDG = OFF_R0;
constexpr uint32_t OFF_REDS = OFF_R0 + 4096;
constexpr uint32_t OFF_REDU = OFF_R0 + 8192;
constexpr uint32_t OFF_REDV = OFF_R0 + 12288;
constexpr uint32_t OFF_H1 = OFF_R0 + 16384;

constexpr int BAR_FULL = 10;
constexpr int U_WQ = -10, U_WUK = -6, U_WMOD = -2, U_WUV = 40, U_WO = 44, U_W1 = 48, U_W2 = 50, NUNITS = 52;
constexpr int BAR_EMPTY = 62;
constexpr int BAR_GO = 66, BAR_CLR = 67, BAR_EPOCH = 68;
constexpr int BAR_P1D = 69, BAR_P2D = 70;
constexpr int BAR_P2E = 71, BAR_P5D = 72, BAR_P7D = 73;
constexpr int BAR_XE = 74;
constexpr int BAR_QXG = 75;
constexpr int NBARS = 83;
__host__ __device__ constexpr uint32_t BAR(int i) { return OFF_BARS + 8 * i; }
#define WIN_0 1
#define PACE_T0 1000
#define PACE_DT 330
#define PACE_DTM 330
#define PACE_NM 8
#define PACE_DTE 330
#define PACE_GAP 400
#define PACE_DT2 400
#define WIN_PRE 8
#define WIN_MID 8
#define WIN_END 8
#define WIN_TAIL 4
#define PACE_NS 200
#define CLR_CLK 300
#define CLR_AT 2
#define CLR_D0 0
#define D_MOD 400
#define D_QP 400
#define D_QX 900
#define CNT_AT 33
#define XE_AT 36
#define X1_D0 500
#define D_X2 300
#define D_X3A 300
#define D_X3B 0
#define D_FIN 600

struct Scratch {
  uint32_t X1[128 * 64 * 64];
  uint32_t X2[128 * 256 * 2];
  uint32_t X3A[128 * 512];
  uint32_t X3B[NREP * 128 * 16];
  uint32_t X4[128 * NFF * 16];
  uint32_t MLL[32 * 64 * 8];
  uint32_t MODA[1024 * 4];
  uint32_t QP[128 * 256 * 2];
  uint32_t MODB[2][2048 * 4];
  uint32_t QX[2][8 * 32 * 256];
  uint32_t XE[128 * 64 * 64];
  uint32_t MLE[32 * 128 * 8];
  uint32_t epoch;
  uint32_t pad[31];
  uint32_t cnt;
};
__device__ __align__(4096) Scratch g_s;

#define TL(idx) do {} while (0)
#define TLW(idx) do {} while (0)
#define PROBE_UNITS(a, b) do {} while (0)

struct Params {
  CUtensorMap wq, wuk, wmod, ckv, wuv, wo, w1, w2;
};

__device__ __forceinline__ void mbar_init(uint32_t bar, int cnt) { asm volatile("mbarrier.init.shared::cta.b64 [%0], %1;" ::"r"(bar), "r"(cnt)); }
__device__ __forceinline__ void mbar_expect(uint32_t bar, uint32_t bytes) { asm volatile("mbarrier.arrive.expect_tx.shared::cta.b64 _, [%0], %1;" ::"r"(bar), "r"(bytes) : "memory"); }
__device__ __forceinline__ void mbar_arrive(uint32_t bar) { asm volatile("mbarrier.arrive.shared::cta.b64 _, [%0];" ::"r"(bar) : "memory"); }
__device__ __forceinline__ void mbar_arrive_cluster(uint32_t bar) { asm volatile("mbarrier.arrive.shared::cluster.b64 _, [%0];" ::"r"(bar) : "memory"); }
__device__ __forceinline__ bool mbar_test(uint32_t bar) {
  uint32_t ok;
  asm volatile("{\n.reg .pred p;\nmbarrier.test_wait.parity.shared::cta.b64 p, [%1], 0;\nselp.u32 %0,1,0,p;\n}" : "=r"(ok) : "r"(bar) : "memory");
  return ok;
}
__device__ __forceinline__ uint32_t gtime32() { uint32_t c; asm volatile("mov.u32 %0, %%globaltimer_lo;" : "=r"(c) :: "memory"); return c; }
__device__ __forceinline__ uint32_t clk32() { uint32_t c; asm volatile("{\n.reg .u64 t;\nmov.u64 t, %%clock64;\ncvt.u32.u64 %0, t;\n}" : "=r"(c) :: "memory"); return c; }
__device__ __forceinline__ void wait_until(uint32_t c0, int clocks) { if (clocks > 0) while ((int)(clk32() - c0) < clocks) {} }
__device__ __forceinline__ void backoff(int clocks) { if (clocks > 0) wait_until(clk32(), clocks); }
template <typename T> __device__ __forceinline__ T* pin(T* p) { asm volatile("" : "+l"(p)); return p; }
__device__ __forceinline__ uint32_t pin32(uint32_t p) { asm volatile("" : "+r"(p)); return p; }
constexpr int SPIN_LIMIT = 1 << 22;
__device__ __forceinline__ void mbar_wait(uint32_t bar) {
  asm volatile("{\n.reg .pred p;\nMW_LOOP:\nmbarrier.try_wait.parity.shared::cta.b64 p, [%0], 0;\n@!p bra MW_LOOP;\n}" ::"r"(bar) : "memory");
}
__device__ __forceinline__ void mbar_wait_b(uint32_t bar) {
  asm volatile("{\n.reg .pred p;\n.reg .u32 c;\nmov.u32 c, 0;\n"
               "MW_LOOP:\nmbarrier.try_wait.parity.shared::cta.b64 p, [%0], 0;\n@p bra MW_DONE;\n"
               "add.u32 c, c, 1;\nsetp.lt.u32 p, c, 1048576;\n@p bra MW_LOOP;\ntrap;\nMW_DONE:\n}"
               ::"r"(bar) : "memory");
}
__device__ __forceinline__ void tma2d(uint32_t dst, const CUtensorMap* m, int c0, int c1, uint32_t bar, uint64_t pol) {
  asm volatile("cp.async.bulk.tensor.2d.shared::cluster.global.mbarrier::complete_tx::bytes.L2::cache_hint [%0], [%1, {%3,%4}], [%2], %5;"
               ::"r"(dst), "l"(m), "r"(bar), "r"(c0), "r"(c1), "l"(pol) : "memory");
}
__device__ __forceinline__ void tma2d_both(uint32_t dst, const CUtensorMap* m, int c0, int c1, uint32_t bar, uint64_t pol) {
  asm volatile("cp.async.bulk.tensor.2d.shared::cluster.global.mbarrier::complete_tx::bytes.multicast::cluster.L2::cache_hint [%0], [%1, {%3,%4}], [%2], %6, %5;"
               ::"r"(dst), "l"(m), "r"(bar), "r"(c0), "r"(c1), "l"(pol), "h"((uint16_t)3) : "memory");
}
__device__ __forceinline__ void tma3d(uint32_t dst, const CUtensorMap* m, int c0, int c1, int c2, uint32_t bar, uint64_t pol) {
  asm volatile("cp.async.bulk.tensor.3d.shared::cluster.global.mbarrier::complete_tx::bytes.L2::cache_hint [%0], [%1, {%3,%4,%5}], [%2], %6;"
               ::"r"(dst), "l"(m), "r"(bar), "r"(c0), "r"(c1), "r"(c2), "l"(pol) : "memory");
}
__device__ __forceinline__ void tma2d_nohint(uint32_t dst, const CUtensorMap* m, int c0, int c1, uint32_t bar) {
  asm volatile("cp.async.bulk.tensor.2d.shared::cluster.global.mbarrier::complete_tx::bytes [%0], [%1, {%3,%4}], [%2];"
               ::"r"(dst), "l"(m), "r"(bar), "r"(c0), "r"(c1) : "memory");
}
__device__ __forceinline__ void bulk_load(uint32_t dst, const void* src, uint32_t bytes, uint32_t bar) {
  asm volatile("cp.async.bulk.shared::cluster.global.mbarrier::complete_tx::bytes [%0], [%1], %2, [%3];" ::"r"(dst), "l"(src), "r"(bytes), "r"(bar) : "memory");
}
__device__ __forceinline__ void cbar() { asm volatile("bar.sync 1, 256;" ::: "memory"); }
__device__ __forceinline__ void wg0bar() { asm volatile("bar.sync 2, 128;" ::: "memory"); }
__device__ __forceinline__ bool cbar_or(bool p) {
  uint32_t r;
  asm volatile("{\n.reg .pred p, q;\nsetp.ne.u32 p, %1, 0;\nbarrier.cta.red.or.aligned.pred q, 1, 256, p;\nselp.u32 %0, 1, 0, q;\n}" : "=r"(r) : "r"((uint32_t)p) : "memory");
  return r;
}

__device__ __forceinline__ uint32_t ldg_rlx1(const void* p) { uint32_t v; asm volatile("ld.relaxed.gpu.global.u32 %0, [%1];" : "=r"(v) : "l"(p) : "memory"); return v; }
__device__ __forceinline__ void stg4(void* p, uint4 v) { asm volatile("st.relaxed.gpu.global.v4.u32 [%0], {%1,%2,%3,%4};" ::"l"(p), "r"(v.x), "r"(v.y), "r"(v.z), "r"(v.w) : "memory"); }
__device__ __forceinline__ void stg1(void* p, uint32_t a) { asm volatile("st.relaxed.gpu.global.u32 [%0], %1;" ::"l"(p), "r"(a) : "memory"); }
__device__ __forceinline__ uint32_t nz(uint32_t w) { return max(w, 1u); }
__device__ __forceinline__ uint32_t min3(uint32_t a, uint32_t b, uint32_t c) { return min(min(a, b), c); }

__device__ __forceinline__ uint32_t pack_bf16(float lo, float hi) { uint32_t r; asm("cvt.rn.bf16x2.f32 %0, %1, %2;" : "=r"(r) : "f"(hi), "f"(lo)); return r; }
__device__ __forceinline__ float bf_lo(uint32_t w) { return __uint_as_float(w << 16); }
__device__ __forceinline__ float bf_hi(uint32_t w) { return __uint_as_float(w & 0xffff0000u); }
__device__ __forceinline__ float ex2(float x) { float r; asm("ex2.approx.ftz.f32 %0, %1;" : "=f"(r) : "f"(x)); return r; }
__device__ __forceinline__ uint32_t shl_clamp(uint32_t x, int s) { uint32_t r; asm("shl.b32 %0, %1, %2;" : "=r"(r) : "r"(x), "r"(s)); return r; }

__device__ __forceinline__ void ldsm4(uint32_t (&r)[4], uint32_t a) { asm volatile("ldmatrix.sync.aligned.m8n8.x4.shared.b16 {%0,%1,%2,%3}, [%4];" : "=r"(r[0]), "=r"(r[1]), "=r"(r[2]), "=r"(r[3]) : "r"(a) : "memory"); }
__device__ __forceinline__ void ldsm4t(uint32_t (&r)[4], uint32_t a) { asm volatile("ldmatrix.sync.aligned.m8n8.x4.trans.shared.b16 {%0,%1,%2,%3}, [%4];" : "=r"(r[0]), "=r"(r[1]), "=r"(r[2]), "=r"(r[3]) : "r"(a) : "memory"); }
__device__ __forceinline__ void ldsm2t(uint32_t& r0, uint32_t& r1, uint32_t a) { asm volatile("ldmatrix.sync.aligned.m8n8.x2.trans.shared.b16 {%0,%1}, [%2];" : "=r"(r0), "=r"(r1) : "r"(a) : "memory"); }
__device__ __forceinline__ void stsm4t(uint32_t a, uint32_t r0, uint32_t r1, uint32_t r2, uint32_t r3) { asm volatile("stmatrix.sync.aligned.m8n8.x4.trans.shared.b16 [%0], {%1,%2,%3,%4};" ::"r"(a), "r"(r0), "r"(r1), "r"(r2), "r"(r3) : "memory"); }
__device__ __forceinline__ void stsm2t(uint32_t a, uint32_t r0, uint32_t r1) { asm volatile("stmatrix.sync.aligned.m8n8.x2.trans.shared.b16 [%0], {%1,%2};" ::"r"(a), "r"(r0), "r"(r1) : "memory"); }
__device__ __forceinline__ void mma16816(float (&d)[4], const uint32_t (&a)[4], uint32_t b0, uint32_t b1) {
  asm volatile("mma.sync.aligned.m16n8k16.row.col.f32.bf16.bf16.f32 {%0,%1,%2,%3}, {%4,%5,%6,%7}, {%8,%9}, {%0,%1,%2,%3};"
               : "+f"(d[0]), "+f"(d[1]), "+f"(d[2]), "+f"(d[3]) : "r"(a[0]), "r"(a[1]), "r"(a[2]), "r"(a[3]), "r"(b0), "r"(b1));
}
__device__ __forceinline__ void mma_v(float (&d)[4], const uint4& a, uint32_t b0, uint32_t b1) {
  asm volatile("mma.sync.aligned.m16n8k16.row.col.f32.bf16.bf16.f32 {%0,%1,%2,%3}, {%4,%5,%6,%7}, {%8,%9}, {%0,%1,%2,%3};"
               : "+f"(d[0]), "+f"(d[1]), "+f"(d[2]), "+f"(d[3]) : "r"(a.x), "r"(a.y), "r"(a.z), "r"(a.w), "r"(b0), "r"(b1));
}
__device__ __forceinline__ void sts1(uint32_t a, uint32_t v) { asm volatile("st.shared.u32 [%0], %1;" ::"r"(a), "r"(v) : "memory"); }
__device__ __forceinline__ void sts2(uint32_t a, uint32_t x, uint32_t y) { asm volatile("st.shared.v2.u32 [%0], {%1,%2};" ::"r"(a), "r"(x), "r"(y) : "memory"); }
__device__ __forceinline__ void sts4(uint32_t a, uint4 v) { asm volatile("st.shared.v4.u32 [%0], {%1,%2,%3,%4};" ::"r"(a), "r"(v.x), "r"(v.y), "r"(v.z), "r"(v.w) : "memory"); }
__device__ __forceinline__ void sts4f(uint32_t a, float x, float y, float z, float w) { asm volatile("st.shared.v4.f32 [%0], {%1,%2,%3,%4};" ::"r"(a), "f"(x), "f"(y), "f"(z), "f"(w) : "memory"); }
__device__ __forceinline__ void sts2f(uint32_t a, float x, float y) { asm volatile("st.shared.v2.f32 [%0], {%1,%2};" ::"r"(a), "f"(x), "f"(y) : "memory"); }
__device__ __forceinline__ void stsf(uint32_t a, float v) { asm volatile("st.shared.f32 [%0], %1;" ::"r"(a), "f"(v) : "memory"); }
__device__ __forceinline__ uint32_t lds1(uint32_t a) { uint32_t v; asm volatile("ld.shared.u32 %0, [%1];" : "=r"(v) : "r"(a) : "memory"); return v; }
__device__ __forceinline__ uint2 lds2(uint32_t a) { uint2 v; asm volatile("ld.shared.v2.u32 {%0,%1}, [%2];" : "=r"(v.x), "=r"(v.y) : "r"(a) : "memory"); return v; }
__device__ __forceinline__ float ldsf(uint32_t a) { float v; asm volatile("ld.shared.f32 %0, [%1];" : "=f"(v) : "r"(a) : "memory"); return v; }
__device__ __forceinline__ float2 ldsf2(uint32_t a) { float2 v; asm volatile("ld.shared.v2.f32 {%0,%1}, [%2];" : "=f"(v.x), "=f"(v.y) : "r"(a) : "memory"); return v; }
__device__ __forceinline__ float4 ldsf4(uint32_t a) { float4 v; asm volatile("ld.shared.v4.f32 {%0,%1,%2,%3}, [%4];" : "=f"(v.x), "=f"(v.y), "=f"(v.z), "=f"(v.w) : "r"(a) : "memory"); return v; }
__device__ __forceinline__ uint4 lds4(uint32_t a) { uint4 v; asm volatile("ld.shared.v4.u32 {%0,%1,%2,%3}, [%4];" : "=r"(v.x), "=r"(v.y), "=r"(v.z), "=r"(v.w) : "r"(a) : "memory"); return v; }

__device__ __forceinline__ void wg_fence() { asm volatile("wgmma.fence.sync.aligned;" ::: "memory"); }
__device__ __forceinline__ void wg_commit() { asm volatile("wgmma.commit_group.sync.aligned;" ::: "memory"); }
template <int N> __device__ __forceinline__ void wg_wait() { asm volatile("wgmma.wait_group.sync.aligned %0;" ::"n"(N) : "memory"); }
__host__ __device__ constexpr uint32_t dlo(uint32_t addr) { return (addr >> 4) | 0x10000u; }
constexpr uint32_t ONE2 = 0x3f803f80u;
template <int TA, int ACC> __device__ __forceinline__ void wgmma_ss(float (&d)[16], uint32_t da, uint32_t db) {
  asm volatile("{\n.reg .b64 da, db;\nmov.b64 da, {%16, 0x40000040};\nmov.b64 db, {%17, 0x40000040};\n"
               "wgmma.mma_async.sync.aligned.m64n32k16.f32.bf16.bf16 {%0,%1,%2,%3,%4,%5,%6,%7,%8,%9,%10,%11,%12,%13,%14,%15}, da, db, %18, 1, 1, %19, 0;\n}"
               : "+f"(d[0]), "+f"(d[1]), "+f"(d[2]), "+f"(d[3]), "+f"(d[4]), "+f"(d[5]), "+f"(d[6]), "+f"(d[7]),
                 "+f"(d[8]), "+f"(d[9]), "+f"(d[10]), "+f"(d[11]), "+f"(d[12]), "+f"(d[13]), "+f"(d[14]), "+f"(d[15])
               : "r"(da), "r"(db), "n"(ACC), "n"(TA));
}
template <int TA, int ACC> __device__ __forceinline__ void wgmma_ss(float (&d)[8], uint32_t da, uint32_t db) {
  asm volatile("{\n.reg .b64 da, db;\nmov.b64 da, {%8, 0x40000040};\nmov.b64 db, {%9, 0x40000040};\n"
               "wgmma.mma_async.sync.aligned.m64n16k16.f32.bf16.bf16 {%0,%1,%2,%3,%4,%5,%6,%7}, da, db, %10, 1, 1, %11, 0;\n}"
               : "+f"(d[0]), "+f"(d[1]), "+f"(d[2]), "+f"(d[3]), "+f"(d[4]), "+f"(d[5]), "+f"(d[6]), "+f"(d[7])
               : "r"(da), "r"(db), "n"(ACC), "n"(TA));
}
__device__ __forceinline__ void wgmma_ones(float (&d)[16], const uint32_t (&one)[4], uint32_t db) {
  asm volatile("{\n.reg .b64 db;\nmov.b64 db, {%20, 0x40000040};\n"
               "wgmma.mma_async.sync.aligned.m64n32k16.f32.bf16.bf16 {%0,%1,%2,%3,%4,%5,%6,%7,%8,%9,%10,%11,%12,%13,%14,%15}, {%16,%17,%18,%19}, db, 1, 1, 1, 0;\n}"
               : "+f"(d[0]), "+f"(d[1]), "+f"(d[2]), "+f"(d[3]), "+f"(d[4]), "+f"(d[5]), "+f"(d[6]), "+f"(d[7]),
                 "+f"(d[8]), "+f"(d[9]), "+f"(d[10]), "+f"(d[11]), "+f"(d[12]), "+f"(d[13]), "+f"(d[14]), "+f"(d[15])
               : "r"(one[0]), "r"(one[1]), "r"(one[2]), "r"(one[3]), "r"(db));
}
__device__ __forceinline__ void wgmma_ones(float (&d)[8], const uint32_t (&one)[4], uint32_t db) {
  asm volatile("{\n.reg .b64 db;\nmov.b64 db, {%12, 0x40000040};\n"
               "wgmma.mma_async.sync.aligned.m64n16k16.f32.bf16.bf16 {%0,%1,%2,%3,%4,%5,%6,%7}, {%8,%9,%10,%11}, db, 1, 1, 1, 0;\n}"
               : "+f"(d[0]), "+f"(d[1]), "+f"(d[2]), "+f"(d[3]), "+f"(d[4]), "+f"(d[5]), "+f"(d[6]), "+f"(d[7])
               : "r"(one[0]), "r"(one[1]), "r"(one[2]), "r"(one[3]), "r"(db));
}
template <int K> __device__ __forceinline__ void tie(float (&d)[K]) {
#pragma unroll
  for (int i = 0; i < K; i += 8)
    asm volatile("" : "+f"(d[i]), "+f"(d[i + 1]), "+f"(d[i + 2]), "+f"(d[i + 3]), "+f"(d[i + 4]), "+f"(d[i + 5]), "+f"(d[i + 6]), "+f"(d[i + 7]) :: "memory");
}
template <bool C, typename A, typename B> __device__ __forceinline__ auto& pick(A& a, B& b) { if constexpr (C) return a; else return b; }
template <int I> struct IC { static constexpr int value = I; };
template <int B, int E, typename F> __device__ __forceinline__ void sfor(F&& f) { if constexpr (B < E) { f(IC<B>{}); sfor<B + 1, E>(f); } }

__device__ __forceinline__ uint2 ldg_u64(const void* p) {
  uint2 v; asm volatile("{\n.reg .b64 a;\nld.relaxed.gpu.global.b64 a, [%2];\nmov.b64 {%0,%1}, a;\n}" : "=r"(v.x), "=r"(v.y) : "l"(p) : "memory"); return v;
}
__device__ __forceinline__ uint4 ldg_2u64(const void* p) {
  uint4 v; asm volatile("{\n.reg .b64 a, b;\nld.relaxed.gpu.global.v2.b64 {a, b}, [%4];\nmov.b64 {%0,%1}, a;\nmov.b64 {%2,%3}, b;\n}" : "=r"(v.x), "=r"(v.y), "=r"(v.z), "=r"(v.w) : "l"(p) : "memory"); return v;
}
__device__ __forceinline__ uint4 ldg_u128(const void* p) {
  uint4 v; asm volatile("{\n.reg .b64 a, b;\n.reg .b128 q;\nld.relaxed.gpu.global.b128 q, [%4];\nmov.b128 {a, b}, q;\nmov.b64 {%0,%1}, a;\nmov.b64 {%2,%3}, b;\n}" : "=r"(v.x), "=r"(v.y), "=r"(v.z), "=r"(v.w) : "l"(p) : "memory"); return v;
}
__device__ __forceinline__ void stg_u64(void* p, uint32_t x, uint32_t y) {
  asm volatile("{\n.reg .b64 a;\nmov.b64 a, {%1,%2};\nst.relaxed.gpu.global.b64 [%0], a;\n}" ::"l"(p), "r"(x), "r"(max(y, 1u)) : "memory");
}
__device__ __forceinline__ void stg_raw64(void* p, uint32_t x, uint32_t y) {
  asm volatile("{\n.reg .b64 a;\nmov.b64 a, {%1,%2};\nst.relaxed.gpu.global.b64 [%0], a;\n}" ::"l"(p), "r"(x), "r"(y) : "memory");
}
__device__ __forceinline__ void stg4_b128(void* p, uint4 v) {
  asm volatile("{\n.reg .b64 a, b;\n.reg .b128 q;\nmov.b64 a, {%1,%2};\nmov.b64 b, {%3,%4};\nmov.b128 q, {a, b};\nst.relaxed.gpu.global.b128 [%0], q;\n}" ::"l"(p), "r"(v.x), "r"(v.y), "r"(v.z), "r"(v.w) : "memory");
}
__device__ __forceinline__ void stg_u128(void* p, uint4 v) {
  asm volatile("{\n.reg .b64 a, b;\n.reg .b128 q;\nmov.b64 a, {%1,%2};\nmov.b64 b, {%3,%4};\nmov.b128 q, {a, b};\nst.relaxed.gpu.global.b128 [%0], q;\n}" ::"l"(p), "r"(v.x), "r"(v.y), "r"(v.z), "r"(max(v.w, 1u)) : "memory");
}
__device__ __forceinline__ uint32_t hmul2(uint32_t a, uint32_t b) { uint32_t r; asm("mul.rn.bf16x2 %0, %1, %2;" : "=r"(r) : "r"(a), "r"(b)); return r; }
__device__ __forceinline__ uint32_t hadd2(uint32_t a, uint32_t b) { uint32_t r; asm("add.rn.bf16x2 %0, %1, %2;" : "=r"(r) : "r"(a), "r"(b)); return r; }
__device__ __forceinline__ uint32_t hfma2(uint32_t a, uint32_t b, uint32_t c) { uint32_t r; asm("fma.rn.bf16x2 %0, %1, %2, %3;" : "=r"(r) : "r"(a), "r"(b), "r"(c)); return r; }
__device__ __forceinline__ uint32_t movm(uint32_t a) { uint32_t d; asm volatile("movmatrix.sync.aligned.m8n8.trans.b16 %0, %1;" : "=r"(d) : "r"(a)); return d; }
__device__ __forceinline__ uint2 ldg_rlx2(const void* p) { uint2 v; asm volatile("ld.relaxed.gpu.global.v2.u32 {%0,%1}, [%2];" : "=r"(v.x), "=r"(v.y) : "l"(p) : "memory"); return v; }
__device__ __forceinline__ uint4 ldg_in4(const void* p) { uint4 v; asm volatile("ld.global.nc.v4.u32 {%0,%1,%2,%3}, [%4];" : "=r"(v.x), "=r"(v.y), "=r"(v.z), "=r"(v.w) : "l"(p)); return v; }
__device__ __forceinline__ uint32_t ldg_in1(const void* p) { uint32_t v; asm volatile("ld.global.nc.u32 %0, [%1];" : "=r"(v) : "l"(p)); return v; }
__device__ __forceinline__ uint32_t ldg_inh(const void* p) { uint16_t v; asm volatile("ld.global.nc.u16 %0, [%1];" : "=h"(v) : "l"(p)); return v; }

__device__ __forceinline__ void sum4_to_smem(uint2 (&v)[4], const uint32_t* x, uint32_t dst) {
  while (min(min(v[0].y, v[1].y), min(v[2].y, v[3].y)) == 0) {
#pragma unroll
    for (int i = 0; i < 4; i++) v[i] = ldg_u64(x + i * 512);
  }
  const float c0 = (bf_lo(v[0].x) + bf_lo(v[1].x)) + (bf_lo(v[2].x) + bf_lo(v[3].x));
  const float c1 = (bf_hi(v[0].x) + bf_hi(v[1].x)) + (bf_hi(v[2].x) + bf_hi(v[3].x));
  const float c2 = (bf_lo(v[0].y) + bf_lo(v[1].y)) + (bf_lo(v[2].y) + bf_lo(v[3].y));
  const float c3 = (bf_hi(v[0].y) + bf_hi(v[1].y)) + (bf_hi(v[2].y) + bf_hi(v[3].y));
  sts1(dst, pack_bf16(c0, c1));
  sts1(dst + 128, pack_bf16(c2, c3));
}
__device__ __forceinline__ void load_a_t(uint32_t (&a)[8][4], uint32_t box, int wq, int lane) {
  const int mi = lane >> 3, r = lane & 7;
  const uint32_t base = box + (8 * (mi >> 1) + r) * 128 + (((2 * wq + (mi & 1)) ^ r) << 4);
#pragma unroll
  for (int ks = 0; ks < 8; ks++) ldsm4t(a[ks], base + ks * 2048);
}
__device__ __forceinline__ void mma128(float (&d)[4], const uint32_t (&a)[8][4], uint32_t bs) {
  float e[4][4] = {{0.f, 0.f, 0.f, 0.f}, {0.f, 0.f, 0.f, 0.f}, {0.f, 0.f, 0.f, 0.f}, {0.f, 0.f, 0.f, 0.f}};
  uint32_t b[4][4];
#pragma unroll
  for (int kk = 0; kk < 4; kk++) ldsm4t(b[kk], bs + 32 * kk * 16);
#pragma unroll
  for (int kk = 0; kk < 4; kk++) { mma16816(e[(2 * kk) & 3], a[2 * kk], b[kk][0], b[kk][1]); mma16816(e[(2 * kk + 1) & 3], a[2 * kk + 1], b[kk][2], b[kk][3]); }
#pragma unroll
  for (int i = 0; i < 4; i++) d[i] = (e[0][i] + e[1][i]) + (e[2][i] + e[3][i]);
}
template <int NL> __device__ __forceinline__ void poll_vectors(uint4 (&v)[NL], const uint32_t* p) {
  int it = 0;
  while (true) {
#pragma unroll
    for (int i = 0; i < NL; i++) v[i] = ldg_2u64(p + i * 128);
    uint32_t m0 = min(v[0].y, v[0].w), m1 = min(v[1].y, v[1].w);
#pragma unroll
    for (int i = 2; i < NL; i += 2) { m0 = min3(m0, v[i].y, v[i].w); m1 = min3(m1, v[i + 1].y, v[i + 1].w); }
    if (__all_sync(~0u, min(m0, m1) != 0)) break;
    if (++it > SPIN_LIMIT) __trap();
  }
}

__global__ void __cluster_dims__(2, 1, 1) __launch_bounds__(NTHREADS, 1)
fused_decode_kernel(__nv_bfloat16* __restrict__ gout, Scratch* __restrict__ gs, const uint8_t* __restrict__ gwmod,
                    const uint8_t* __restrict__ gx, const uint8_t* __restrict__ gc,
                    const __grid_constant__ Params P) {
  extern __shared__ __align__(1024) uint8_t smem_raw[];
  const uint32_t hi = pin32((uint32_t)__cvta_generic_to_shared(smem_raw) - SB);
  const int tid = threadIdx.x, lane = tid & 31;
  const int w = __shfl_sync(0xffffffffu, tid >> 5, 0);
  const int cta = blockIdx.x;
  const int g = lane >> 2, t = lane & 3;
  const int hI = cta >> 2, jI = cta & 3;
  const int bI = cta >> 4, pI = (cta >> 1) & 7, rI = cta & 1;

  uint32_t epoch0 = 0;
  uint32_t tnext = 0;
  if (tid == 320) epoch0 = ldg_rlx1(&gs->epoch);
  uint4 cw0, cw1, xr0, xr1;
  uint32_t xc[4];
  uint2 sa, ca, qp[4];
  const uint32_t* const modi = gs->MODA + 512 * jI + tid * 2;
  const uint32_t* const qpi = gs->QP + (hI * 4 * 256 + tid) * 2;
  if (w < 8) {
    const uint8_t* wm = gwmod + 16 * cta + (size_t)(64 * w + lane) * 6144;
    const uint32_t dst = hi + OFF_R0 + w * 1024 + (((lane >> 1) & 7) * 8 + 2 * (lane >> 4) + (lane & 1)) * 16;
    asm volatile("cp.async.cg.shared.global.L2::128B [%0], [%1], 16;" ::"r"(dst), "l"(wm) : "memory");
    asm volatile("cp.async.cg.shared.global.L2::128B [%0], [%1], 16;" ::"r"(dst + 64), "l"(wm + 32 * 6144) : "memory");
    asm volatile("cp.async.commit_group;" ::: "memory");
    cw0 = ldg_in4(gc + g * 1024 + w * 128 + t * 32); cw1 = ldg_in4(gc + g * 1024 + w * 128 + t * 32 + 16);
    xr0 = ldg_in4(gx + w * 1024 + lane * 16); xr1 = ldg_in4(gx + w * 1024 + 512 + lane * 16);
#pragma unroll
    for (int i = 0; i < 4; i++) xc[i] = ldg_inh(gx + w * 1024 + jI * 256 + i * 64 + lane * 2);
    sa = ca = qp[0] = qp[1] = qp[2] = qp[3] = make_uint2(0, 0);
    if (hI == 0) { sa = ldg_rlx2(modi); ca = ldg_rlx2(modi + 2048); }
    if (jI == 0) {
#pragma unroll
      for (int i = 0; i < 4; i++) qp[i] = ldg_u64(qpi + i * 512);
    }
  }
  auto front_unit = [&](int k, uint64_t pol) {
    const uint32_t bar = hi + BAR(k);
    if (k < 8) tma2d(hi + OFF_R1 + k * 8192, k < 4 ? &P.wq : &P.wuk, 128 * hI + 64 * ((k >> 1) & 1), 128 * jI + 64 * (k & 1), bar, pol);
    else tma2d_nohint(hi + OFF_R0 + (k - 7) * 8192, &P.wmod, 1024 + 16 * cta, 256 * (k - 8), bar);
  };
  if (tid == 256) {
    if (hi & 0xffffff) __trap();
#pragma unroll
    for (int i = 0; i < WIN_0; i++) mbar_init(hi + BAR(i), 1);
    asm volatile("fence.mbarrier_init.release.cluster;" ::: "memory");
    uint64_t pol; asm volatile("createpolicy.fractional.L2::evict_first.b64 %0, 1.0;" : "=l"(pol));
#pragma unroll
    for (int i = 0; i < WIN_0; i++) front_unit(i, pol);
    tnext = gtime32() + (PACE_T0 - 500);
    TLW(42);
  } else if (tid == 288) {
#pragma unroll
    for (int i = WIN_0; i < NBARS; i++)
      mbar_init(hi + BAR(i), (i >= BAR_EMPTY && i < BAR_EMPTY + 3) ? 16 : (i == BAR_EMPTY + 3 || (i >= BAR_P1D && i <= BAR_P7D)) ? 8 : i == BAR_XE ? 2 : 1);
    asm volatile("fence.mbarrier_init.release.cluster;" ::: "memory");
  }
  __syncthreads();
  TL(0);

  if (w == 8) {
    mbar_expect(hi + BAR(0) + 8 * lane, 8192);
    if (lane < BAR_EMPTY - 32) mbar_expect(hi + BAR(32) + 8 * lane, 8192);
    __syncwarp();
    const int h = hI, j = jI;
    if (lane == 0) {
      uint64_t pol; asm volatile("createpolicy.fractional.L2::evict_first.b64 %0, 1.0;" : "=l"(pol));
      auto pace = [&](int dt) { if (PACE_DT > 0) { while ((int)(gtime32() - tnext) < 0) {} tnext += dt; } };
      asm volatile("prefetch.tensormap [%0];" ::"l"(&P.wuk) : "memory");
      asm volatile("prefetch.tensormap [%0];" ::"l"(&P.wmod) : "memory");
      asm volatile("prefetch.tensormap [%0];" ::"l"(&P.ckv) : "memory");
#pragma unroll 1
      for (int k = WIN_0; k < 10; k++) { if (k >= WIN_PRE) mbar_wait(hi + BAR(0) + 8 * (k - WIN_PRE)); pace(PACE_DT); front_unit(k, pol); }
      bool go = false;
      const int row0 = bI * 4096 + (cta & 15) * 64;
#pragma unroll 1
      for (int n = 0; n < 24; n++) {
        if (!go) go = mbar_test(hi + BAR(BAR_GO));
        const int win = go ? WIN_MID : WIN_PRE;
        const uint32_t dst = hi + box_off(n);
        mbar_wait(hi + BAR(BAR_FULL) + 8 * (n - win));
        if (n == 16) mbar_wait(hi + BAR(BAR_P1D));
        if (n == 19) mbar_wait(hi + BAR(BAR_P2D));
        if (n == 23) mbar_wait(hi + BAR(BAR_EMPTY));
        pace(n >= PACE_NM ? PACE_DTM : PACE_DT);
        tma2d(dst, &P.ckv, (n & 7) * 64, row0 + (n >> 3) * 1024, hi + BAR(BAR_FULL) + 8 * n, pol);
      }
      asm volatile("prefetch.tensormap [%0];" ::"l"(&P.wuv) : "memory");
      asm volatile("prefetch.tensormap [%0];" ::"l"(&P.wo) : "memory");
      asm volatile("prefetch.tensormap [%0];" ::"l"(&P.w1) : "memory");
      asm volatile("prefetch.tensormap [%0];" ::"l"(&P.w2) : "memory");
      const int row1 = bI * 4096 + (48 + pI) * 64;
      tnext += rI * (PACE_DT / 2) - PACE_DT / 4;
#pragma unroll 1
      for (int n = 24 + rI; n < 40; n += 2) {
        const int c = n - 23;
        const int m = c >= 2 * WIN_END ? n - 2 * WIN_END : 23 - (2 * WIN_END - c) / 2;
        const uint32_t dst = hi + box_off(n);
        mbar_wait(hi + BAR(BAR_FULL) + 8 * m);
        if (n == 31 || n == 32) mbar_wait(hi + BAR(BAR_EMPTY + 1));
        if (n == 39) mbar_wait(hi + BAR(BAR_EMPTY + 2));
        pace(PACE_DTE);
        tma2d_both(dst, &P.ckv, (n & 7) * 64, row1 + (n >> 5) * 512, hi + BAR(BAR_FULL) + 8 * n, pol);
      }
      mbar_wait(hi + BAR(BAR_EMPTY + 2));
      tnext += PACE_GAP;
      sfor<U_WUV, NUNITS>([&](auto nc) {
        constexpr int n = decltype(nc)::value, c = n - 39;
        constexpr int m = c >= WIN_TAIL ? n - WIN_TAIL : 39 - 2 * (WIN_TAIL - c);
        if (n >= U_W1 && cta >= NFF) return;
        mbar_wait(hi + BAR(BAR_FULL + m));
        if (n == U_WO) mbar_wait(hi + BAR(BAR_EMPTY + 3));
        pace(PACE_DT2);
        const uint32_t bar = hi + BAR(BAR_FULL + n);
        constexpr int u = n & 3;
        if constexpr (n < U_WO) tma2d(hi + OFF_WUV + u * 8192, &P.wuv, 128 * h + 64 * (u >> 1), 128 * j + 64 * (u & 1), bar, pol);
        else if constexpr (n < U_W1) tma2d(hi + OFF_WO + u * 8192, &P.wo, 128 * j + 64 * (u >> 1), 128 * h + 64 * (u & 1), bar, pol);
        else if constexpr (n < U_W2) tma2d_nohint(hi + OFF_W1 + (u & 1) * 8192, &P.w1, FCH * cta, 256 * (u & 1), bar);
        else tma3d(hi + OFF_W2 + (u & 1) * 8192, &P.w2, 0, FCH * cta, 4 * (u & 1), bar, pol);
      });
    }
    return;
  }

  if (w == 11) {
    const uint4 z = make_uint4(0, 0, 0, 0);
    float d[4] = {0.f, 0.f, 0.f, 0.f};
    const uint32_t a[4] = {0u, 0u, 0u, 0u};
    auto pace = [&] {
      mma16816(d, a, 0u, 0u);
    };
    auto pace_until = [&](int bar) { do { pace(); __nanosleep(PACE_NS); } while (!mbar_test(hi + BAR(bar))); };
    if (CLR_AT == 2) pace_until(BAR_GO);
    if (CLR_AT == 3) pace_until(BAR_P2E);
    backoff(CLR_D0);
    uint32_t* x1 = gs->X1 + ((64 * rI + (lane >> 4)) * 64 + bI * 8 + pI) * 64 + (lane & 15) * 4;
    uint32_t* x4 = gs->X4 + (g * NFF + min(cta, NFF - 1)) * 16 + t * 4;
#pragma unroll 1
    for (int i = 0; i < 16; i++) {
      const uint32_t c0 = clk32();
      stg4(x1 + 2 * i * 8192, z);
      stg4(x1 + (2 * i + 1) * 8192, z);
      if (cta < NFF) stg4(x4 + i * 8 * NFF * 16, z);
      if (i < 4) stg4(gs->X3A + (32 * jI + 8 * i) * 512 + (lane >> 1) * 256 + hI * 8 + (lane & 1) * 4, z);
      else if (i < 8) stg4(gs->X2 + cta * 512 + ((i - 4) * 32 + lane) * 4, z);
      else if (i == 8 && lane < 4 * NREP) stg4(gs->X3B + g * 2048 + cta * 16 + t * 4, z);
      else if (i == 9) stg4(gs->MLL + ((16 * rI + (lane >> 1)) * 64 + (cta >> 1)) * 8 + (lane & 1) * 4, z);
      wait_until(c0, CLR_CLK);
    }
    TLW(35);
    asm volatile("fence.acq_rel.gpu;" ::: "memory");
    __syncwarp();
    if (lane == 0) {
      mbar_arrive(hi + BAR(BAR_CLR));
      asm volatile("red.relaxed.gpu.global.add.u32 [%0], 1;" ::"l"(&gs->cnt) : "memory");
    }
    TLW(36);
    mbar_wait(hi + BAR(BAR_GO));
    const uint32_t epoch = lds1(hi + OFF_EPOCH);
    const int par = epoch & 1;
#pragma unroll
    for (int i = 0; i < 4; i++) stg4(gs->QP + cta * 512 + (i * 32 + lane) * 4, z);
#pragma unroll
    for (int i = 0; i < 4; i++) stg4(gs->QX[par ^ 1] + cta * 512 + (i * 32 + lane) * 4, z);
    if (lane < 8) stg4(gs->MODA + cta * 32 + lane * 4, z);
    if (lane < 16) stg4(gs->MODB[par ^ 1] + cta * 64 + lane * 4, z);
    mbar_wait(hi + BAR(BAR_FULL + CNT_AT));
    while ((int)(ldg_rlx1(&gs->cnt) - (epoch + 1) * NCTA) < 0) __nanosleep(100);
    if (lane == 0) mbar_arrive(hi + BAR(BAR_XE));
    TLW(54);
    mbar_wait(hi + BAR(BAR_FULL + 39));
    pace_until(BAR_P5D);
    if (cta < NFF) pace_until(BAR_P7D);
    if (d[0] != 0.f) __trap();
    return;
  }
  if (w == 10) {
    const int m0 = 16 * hI + 2 * jI;
    const int bo = lane & 7;
    const uint32_t epoch = __shfl_sync(~0u, epoch0, 0);
    if (lane == 0) { sts1(hi + OFF_EPOCH, epoch); mbar_arrive(hi + BAR(BAR_EPOCH)); }
    const int par = epoch & 1;
    const uint32_t* MOD = gs->MODB[par];
    const uint32_t xw0 = ldg_in1(gx + bo * 1024 + m0 * 2), xw1 = ldg_in1(gx + bo * 1024 + m0 * 2 + 16);
    PROBE_UNITS(-10, 20);
    mbar_wait_b(hi + BAR(BAR_GO));
    const int mf = m0 + ((g >> 1) & 1) + 8 * (t >> 1), bf = 2 * (g & 1) + (t & 1);
    float ga[4];
    uint32_t gb2;
    {
      uint32_t u[4];
      int it = 0;
      while (true) {
#pragma unroll
        for (int i = 0; i < 4; i++) u[i] = ldg_rlx1(MOD + (m0 + (i & 1) + 8 * (i >> 1)) * 4 + (bo >> 1));
        gb2 = ldg_rlx1(MOD + (1536 + mf) * 4 + bf);
        if (min3(min3(u[0], u[1], u[2]), u[3], gb2) != 0) break;
        if (++it > SPIN_LIMIT) __trap();
      }
#pragma unroll
      for (int i = 0; i < 4; i++) ga[i] = (bo & 1) ? bf_hi(u[i]) : bf_lo(u[i]);
    }
    uint32_t x2a, x2b;
    {
      const uint32_t* const pi = pin(gs->X3A + cta * 512 + (4 * (g >> 1) + t) * 8 + (g & 1) * 4);
      uint32_t* const po = pin(gs->X3B + (g >> 1) * 2048 + cta * 16 + bo * 2);
      const uint32_t one = 0x3f80u << (8 * (g & 2)), s0 = g < 4 ? one : 0u, s1 = g < 4 ? 0u : one;
      const uint32_t e0 = pin32((g & 1) ? 0u : s0), e1 = pin32((g & 1) ? 0u : s1), o0 = pin32((g & 1) ? s0 : 0u), o1 = pin32((g & 1) ? s1 : 0u);
      PROBE_UNITS(20, 48);
      mbar_wait_b(hi + BAR(BAR_P5D));
      backoff(D_X3A);
      uint4 v[4];
      poll_vectors<4>(v, pi);
      TLW(37);
      float d0[4] = {0.f, 0.f, 0.f, 0.f}, d1[4] = {0.f, 0.f, 0.f, 0.f};
      mma_v(d0, v[0], e0, e1); mma_v(d1, v[2], o0, o1);
      mma_v(d0, v[1], e0, e1); mma_v(d1, v[3], o0, o1);
      float s[4] = {d0[0], d1[1], d0[2], d1[3]};
#pragma unroll
      for (int i = 0; i < 4; i++) s[i] += __shfl_xor_sync(~0u, s[i], 8);
#pragma unroll
      for (int i = 0; i < 4; i++) s[i] += __shfl_xor_sync(~0u, s[i], 16);
      x2a = pack_bf16(bf_lo(xw0) + ga[0] * s[0], bf_hi(xw0) + ga[1] * s[1]);
      x2b = pack_bf16(bf_lo(xw1) + ga[2] * s[2], bf_hi(xw1) + ga[3] * s[3]);
      stg_u64(po, x2a, x2b);
    }
    TLW(20);
    {
      const uint32_t a0 = __shfl_sync(~0u, x2a, 2 * bf), a1 = __shfl_sync(~0u, x2a, 2 * bf + 1);
      const uint32_t b0 = __shfl_sync(~0u, x2b, 2 * bf), b1 = __shfl_sync(~0u, x2b, 2 * bf + 1);
      const uint32_t y0 = (t & 2) ? b0 : a0, y1 = (t & 2) ? b1 : a1;
      const float r0 = (g & 2) ? bf_hi(y0) : bf_lo(y0), r1 = (g & 2) ? bf_hi(y1) : bf_lo(y1);
      const uint32_t* const pi = pin(gs->X4 + cta * NFF * 16 + (4 * (g >> 2) + t) * 16 + (g & 3) * 4);
      __nv_bfloat16* const fo = pin(gout + (2 * bf) * 512 + mf);
      const uint32_t one = (g & 1) ? 0x3f800000u : 0x00003f80u;
      const uint32_t s0 = pin32((g & 2) ? 0u : one), s1 = pin32((g & 2) ? one : 0u);
      if (cta < NFF) { mbar_wait_b(hi + BAR(BAR_P7D)); backoff(D_FIN); } else __nanosleep(1000);
      uint4 v[NFF / 8];
      poll_vectors<NFF / 8>(v, pi);
      TLW(38);
      float d[4][4] = {{0.f, 0.f, 0.f, 0.f}, {0.f, 0.f, 0.f, 0.f}, {0.f, 0.f, 0.f, 0.f}, {0.f, 0.f, 0.f, 0.f}};
#pragma unroll
      for (int i = 0; i < NFF / 8; i++) mma_v(d[i & 3], v[i], s0, s1);
      const bool up = t & 2;
      float v0 = up ? (d[0][2] + d[1][2]) + (d[2][2] + d[3][2]) : (d[0][0] + d[1][0]) + (d[2][0] + d[3][0]);
      float v1 = up ? (d[0][3] + d[1][3]) + (d[2][3] + d[3][3]) : (d[0][1] + d[1][1]) + (d[2][1] + d[3][1]);
      v0 += __shfl_xor_sync(~0u, v0, 16);
      v1 += __shfl_xor_sync(~0u, v1, 16);
      if (g < 4) {
        fo[0] = __float2bfloat16(r0 + bf_lo(gb2) * v0);
        fo[512] = __float2bfloat16(r1 + bf_hi(gb2) * v1);
      }
    }
    TLW(23);
    if (cta == 0 && lane == 0) stg1(&gs->epoch, epoch + 1);
    return;
  }

  if (w == 9) {
    mbar_wait(hi + BAR(BAR_EPOCH));
    const int par = lds1(hi + OFF_EPOCH) & 1;
    {
      const uint32_t* px = gs->QX[par] + bI * 8192 + lane * 256 + 63;
      uint32_t x0 = ldg_rlx1(px), x1 = ldg_rlx1(px + 64), x2 = ldg_rlx1(px + 128), x3 = ldg_rlx1(px + 192);
      mbar_wait(hi + BAR(BAR_P2E));
      backoff(D_QX);
      uint32_t donemask = 0;
      while (true) {
        const uint32_t okm = __ballot_sync(~0u, x0 != 0 && x1 != 0 && x2 != 0 && x3 != 0);
        const uint32_t full = okm & (okm >> 1) & (okm >> 2) & (okm >> 3) & 0x11111111u;
        if (((full & ~donemask) >> lane) & 1) mbar_arrive(hi + BAR(BAR_QXG) + 8 * (lane >> 2));
        donemask |= full;
        if (donemask == 0x11111111u) break;
        if (x0 == 0) x0 = ldg_rlx1(px);
        if (x1 == 0) x1 = ldg_rlx1(px + 64);
        if (x2 == 0) x2 = ldg_rlx1(px + 128);
        if (x3 == 0) x3 = ldg_rlx1(px + 192);
      }
    }
    if (lane == 0) {
      mbar_expect(hi + BAR(BAR_XE), 16384 + 4096);
      mbar_wait(hi + BAR(BAR_EMPTY + 2));
      mbar_wait(hi + BAR(BAR_FULL + XE_AT));
      TLW(33);
      bulk_load(hi + OFF_XE, gs->XE + cta * 4096, 16384, hi + BAR(BAR_XE));
      mbar_wait(hi + BAR(BAR_EMPTY + 3));
      bulk_load(hi + OFF_MLS, gs->MLE + hI * 1024, 4096, hi + BAR(BAR_XE));
    }
    return;
  }

  const int wg = w >> 2, wq = w & 3;
  uint32_t cf[8] = {cw0.x, cw0.y, cw0.z, cw0.w, cw1.x, cw1.y, cw1.z, cw1.w};
#pragma unroll
  for (int i = 0; i < 8; i++) {
    const float a = bf_lo(cf[i]), b = bf_hi(cf[i]);
    cf[i] = pack_bf16(__fdividef(a, 1.f + __expf(-a)), __fdividef(b, 1.f + __expf(-b)));
  }
  TL(1);
  {
    uint32_t* const mo = pin(gs->MODA + cta * 32 + lane);
    asm volatile("cp.async.wait_group 0;" ::: "memory");
    __syncwarp();
    TL(2);
    float d0[4] = {0.f, 0.f, 0.f, 0.f}, d1[4] = {0.f, 0.f, 0.f, 0.f};
    uint32_t r0[4], r1[4];
    ldsm4t(r0, hi + OFF_R0 + w * 1024 + lane * 16); ldsm4t(r1, hi + OFF_R0 + w * 1024 + 512 + lane * 16);
    mma_v(d0, make_uint4(r0[0], 0u, r0[1], 0u), cf[0], cf[1]); mma_v(d1, make_uint4(r0[2], 0u, r0[3], 0u), cf[2], cf[3]);
    mma_v(d0, make_uint4(r1[0], 0u, r1[1], 0u), cf[4], cf[5]); mma_v(d1, make_uint4(r1[2], 0u, r1[3], 0u), cf[6], cf[7]);
    sts2f(hi + OFF_P0S + tid * 8, d0[0] + d1[0], d0[1] + d1[1]);
    cbar();
    if (w == 0) {
      float2 v[8];
#pragma unroll
      for (int i = 0; i < 8; i++) v[i] = ldsf2(hi + OFF_P0S + (i * 32 + lane) * 8);
      stg1(mo, nz(pack_bf16(((v[0].x + v[1].x) + (v[2].x + v[3].x)) + ((v[4].x + v[5].x) + (v[6].x + v[7].x)),
                            ((v[0].y + v[1].y) + (v[2].y + v[3].y)) + ((v[4].y + v[5].y) + (v[6].y + v[7].y)))));
    }
  }
  const uint32_t ck0 = clk32();
  TL(3);
  {
    float v[16];
    const uint32_t u[8] = {xr0.x, xr0.y, xr0.z, xr0.w, xr1.x, xr1.y, xr1.z, xr1.w};
#pragma unroll
    for (int i = 0; i < 8; i++) { v[2 * i] = bf_lo(u[i]); v[2 * i + 1] = bf_hi(u[i]); }
    float s = (((v[0] + v[1]) + (v[2] + v[3])) + ((v[4] + v[5]) + (v[6] + v[7]))) + (((v[8] + v[9]) + (v[10] + v[11])) + ((v[12] + v[13]) + (v[14] + v[15])));
#pragma unroll
    for (int o = 16; o; o >>= 1) s += __shfl_xor_sync(~0u, s, o);
    const float mu = s * (1.f / 512.f);
    float q0 = 0.f, q1 = 0.f;
#pragma unroll
    for (int i = 0; i < 8; i++) { const float a = v[2 * i] - mu, b = v[2 * i + 1] - mu; q0 += a * a; q1 += b * b; }
    float q = q0 + q1;
#pragma unroll
    for (int o = 16; o; o >>= 1) q += __shfl_xor_sync(~0u, q, o);
    const float rs = rsqrtf(q * (1.f / 512.f) + 1e-5f);
#pragma unroll
    for (int i = 0; i < 4; i++)
      asm volatile("st.shared.u16 [%0], %1;" ::"r"(hi + OFF_BS + (32 * i + lane) * 16 + w * 2), "h"(__bfloat16_as_ushort(__float2bfloat16((bf_lo(xc[i]) - mu) * rs))) : "memory");
  }
  {
    cbar();
    const uint2 xn = lds2(hi + OFF_BS + tid * 8);
    uint32_t* const qpo = pin(gs->QP + (cta * 256 + tid) * 2);
    uint32_t a[8][4];
    const bool wq_ok = mbar_test(hi + BAR(BAR_FULL + U_WQ) + 16 * wg) && mbar_test(hi + BAR(BAR_FULL + U_WQ + 1) + 16 * wg);
    if (wq_ok) load_a_t(a, hi + OFF_R1 + wg * 16384, wq, lane);
    wait_until(ck0, D_MOD);
    while (min(min(sa.x, sa.y), min(ca.x, ca.y)) == 0) { sa = ldg_rlx2(modi); ca = ldg_rlx2(modi + 2048); }
    TL(41);
    sts2(hi + OFF_BS + tid * 8, hfma2(xn.x, hadd2(ca.x, ONE2), sa.x), hfma2(xn.y, hadd2(ca.y, ONE2), sa.y));
    __syncwarp();
    if (!wq_ok) {
      mbar_wait(hi + BAR(BAR_FULL + U_WQ) + 16 * wg); mbar_wait(hi + BAR(BAR_FULL + U_WQ + 1) + 16 * wg);
      load_a_t(a, hi + OFF_R1 + wg * 16384, wq, lane);
    }
    cbar();
    float d[4];
    mma128(d, a, hi + OFF_BS + lane * 16);
    stg_u64(qpo, pack_bf16(d[0], d[1]), pack_bf16(d[2], d[3]));
    if (lane == 0) mbar_arrive(hi + BAR(BAR_P1D));
  }
  const uint32_t ckq = clk32();
  TL(6);
  mbar_wait(hi + BAR(BAR_EPOCH));
  const int par = lds1(hi + OFF_EPOCH) & 1;
  uint32_t* const QX = gs->QX[par];
  {
    uint32_t a[8][4];
    {
      const int mi = lane >> 3, r = lane & 7;
      const int row = 16 * w + 8 * (mi & 1) + r;
      mbar_wait(hi + BAR(BAR_FULL + U_WUK) + 8 * wg); mbar_wait(hi + BAR(BAR_FULL + U_WUK + 2) + 8 * wg);
#pragma unroll
      for (int ks = 0; ks < 8; ks++) {
        const int chunk = 2 * ks + (mi >> 1);
        ldsm4(a[ks], hi + OFF_R2 + (ks >> 2) * 16384 + row * 128 + (((chunk & 7) ^ r) << 4));
      }
    }
    __syncwarp();
    if (lane == 0) mbar_arrive(hi + BAR(BAR_P2D));
    TL(8);
    uint32_t* const qxo = pin(QX + ((lane >> 1) * 32 + hI) * 256 + (128 * jI + 16 * w + 8 * (lane & 1)) / 2);
    wait_until(ckq, D_QP);
    sum4_to_smem(qp, qpi, hi + OFF_BS2 + (16 * w + g) * 16 + t * 4);
    TL(7);
    cbar();
    float d[4];
    mma128(d, a, hi + OFF_BS2 + lane * 16);
    const float sc = 0.08838834764831845f * 1.4426950408889634f;
    const uint32_t stg = hi + OFF_P0S + 4096 + w * 256;
    stsm2t(stg + (lane & 7) * 32 + ((lane >> 3) & 1) * 16, pack_bf16(d[0] * sc, d[1] * sc), pack_bf16(d[2] * sc, d[3] * sc));
    __syncwarp();
    if (lane < 16) stg_u128(qxo, lds4(stg + lane * 16));
    if (lane == 0) mbar_arrive(hi + BAR(BAR_P2E));
  }
  TL(9);
  {
    const int mi = lane >> 3, r = lane & 7;
    const uint32_t abase = hi + OFF_R0 + 8192 + (64 * w + 16 * (r >> 1) + 2 * (mi >> 1) + (r & 1)) * 32 + (mi & 1) * 16;
    mbar_wait(hi + BAR(BAR_FULL + U_WMOD) + 8 * wg);
    float d0[4] = {0.f, 0.f, 0.f, 0.f}, d1[4] = {0.f, 0.f, 0.f, 0.f};
    uint32_t a[4][4];
#pragma unroll
    for (int ks = 0; ks < 4; ks++) ldsm4t(a[ks], abase + ks * 128);
#pragma unroll
    for (int ks = 0; ks < 4; ks++) mma16816((ks & 1) ? d1 : d0, a[ks], cf[2 * ks], cf[2 * ks + 1]);
    sts4f(hi + OFF_P0S + tid * 16, d0[0] + d1[0], d0[1] + d1[1], d0[2] + d1[2], d0[3] + d1[3]);
    cbar();
    if (w < 2) {
      float2 v[8];
#pragma unroll
      for (int i = 0; i < 8; i++) v[i] = ldsf2(hi + OFF_P0S + (i * 32 + lane) * 16 + w * 8);
      stg1(gs->MODB[par] + cta * 64 + tid, nz(pack_bf16(((v[0].x + v[1].x) + (v[2].x + v[3].x)) + ((v[4].x + v[5].x) + (v[6].x + v[7].x)),
                                                        ((v[0].y + v[1].y) + (v[2].y + v[3].y)) + ((v[4].y + v[5].y) + (v[6].y + v[7].y)))));
    }
  }
  TL(31);
  uint32_t bc[8], bs[8];
  const uint32_t* const mbi = gs->MODB[par] + (512 + 64 * w) * 4 + lane;
  {
    const uint32_t* qx = pin(QX + bI * 8192 + w * 1024 + lane * 4);
    mbar_wait(hi + BAR(BAR_QXG) + 8 * w);
    TL(4);
    uint4 v[8];
#pragma unroll
    for (int i = 0; i < 8; i++) v[i] = ldg_u128(qx + i * 128);
#pragma unroll
    for (int i = 0; i < 8; i++) { bs[i] = ldg_rlx1(mbi + i * 32); bc[i] = ldg_rlx1(mbi + 2048 + i * 32); }
    cbar();
    while (true) {
      bool all = true;
#pragma unroll
      for (int i = 0; i < 8; i++) all = all && v[i].w != 0;
      if (all) break;
#pragma unroll
      for (int i = 0; i < 8; i++) if (v[i].w == 0) v[i] = ldg_u128(qx + i * 128);
    }
    TL(5);
#pragma unroll
    for (int i = 0; i < 8; i++) {
      const int hh = (4 * w + (i >> 1)) ^ (16 * rI), ch = 32 * (i & 1) + lane;
      sts4(hi + OFF_R0 + (ch >> 3) * 4096 + hh * 128 + (((ch & 7) ^ (hh & 7)) << 4), v[i]);
    }
    asm volatile("fence.proxy.async.shared::cta;" ::: "memory");
    cbar();
    if (tid == 0) mbar_arrive(hi + BAR(BAR_GO));
  }
  TL(10);

  {
    float O32[4][16], O16[4][8];
    uint32_t ebar;
    asm("mapa.shared::cluster.u32 %0, %1, %2;" : "=r"(ebar) : "r"(hi + BAR(BAR_EMPTY)), "r"(rI ^ (lane & 1)));
    const int x1o = ((2 * t * 4 + 2 * wg) * 64 + bI * 8 + pI) * 64 + (wq * 8 + g) * 2;
    uint32_t* const x1e = pin(gs->XE + x1o + (1 - rI) * (64 * 64 * 64));
    uint32_t* const x1l = pin(gs->X1 + x1o + rI * (64 * 64 * 64));
#pragma unroll
    for (int i = 0; i < 16; i++) O32[0][i] = O32[1][i] = O32[2][i] = O32[3][i] = 0.f;
#pragma unroll
    for (int i = 0; i < 4; i++) tie(O32[i]);
    auto box0 = [](int T) { return T == 2 ? dlo(box_off(16)) : T < 2 ? dlo(box_off(0)) + T * 4096 : dlo(box_off(24)) + (T - 3) * 4096; };
    auto box7 = [&](int T) { return T == 2 ? dlo(box_off(23)) : T == 4 ? dlo(box_off(39)) : box0(T) + 7 * 512; };

    auto pv = [&](int T, auto wc, auto& O) {
      constexpr int WG = decltype(wc)::value;
      const uint32_t d0 = box0(T) + WG * 2048, d3 = WG ? box7(T) : d0 + 1536, dp = dlo(OFF_PT) + (T & 1) * 256;
      wg_fence();
#pragma unroll
      for (int mb = 0; mb < 4; mb += 2) {
#pragma unroll
        for (int ks = 0; ks < 4; ks++) {
          wgmma_ss<1, 1>(O[mb], d0 + mb * 512 + ks * 128, dp + ks * 2);
          wgmma_ss<1, 1>(O[mb + 1], (mb ? d3 : d0 + 512) + ks * 128, dp + ks * 2);
        }
        wg_commit();
      }
    };
    auto rescale = [&](auto& d, const float (&alpha)[8]) {
#pragma unroll
      for (int i = 0; i < (int)(sizeof(d) / 4); i++) d[i] *= alpha[2 * (i >> 2) + (i & 1)];
    };
    auto put_o = [&](bool early, int jj, const float* a, const float* b) {
#pragma unroll
      for (int jn = 0; jn < 2; jn++)
#pragma unroll
        for (int e = 0; e < 2; e++) {
          const uint32_t x = pack_bf16(a[4 * jn + e], a[4 * jn + 2 + e]), y = pack_bf16(b[4 * jn + e], b[4 * jn + 2 + e]);
          if (early) stg_raw64(x1e + ((8 * jn + e) * 4 + jj) * 4096, x, (y | 1u) ^ par);
          else stg_u64(x1l + ((8 * jn + e) * 4 + jj) * 4096, x, y);
        }
    };
    auto finish_private = [&](int T) {
      wg_wait<0>();
#pragma unroll
      for (int i = 0; i < 4; i++) tie(O32[i]);
      if (lane < 2) mbar_arrive_cluster(ebar + 8 * T);
      TL(24 + T);
    };
    auto put_early = [&] {
      put_o(true, 0, O32[0] + 8, O32[1] + 8);
      put_o(true, 1, O32[2] + 8, O32[3] + 8);
#pragma unroll
      for (int i = 0; i < 32; i++) asm volatile("mov.b32 %0, %1;" : "=f"(O16[i >> 3][i & 7]) : "f"(O32[i >> 3][i & 7]));
      TL(27);
    };
    auto finish3 = [&] {
      wg_wait<0>();
#pragma unroll
      for (int i = 0; i < 4; i++) tie(O16[i]);
      if (lane == 0) mbar_arrive(hi + BAR(BAR_EMPTY + 3));
      TL(32);
      if (wg) mbar_wait(hi + BAR(BAR_CLR));
    };

    if (wg == 0) {
      float m_run = -INFINITY;
      float mh[8];
#pragma unroll
      for (int i = 0; i < 8; i++) mh[i] = 0.f;
      const uint32_t ptl = hi + OFF_PT + (8 * (lane >> 4) + (lane & 7)) * 128 + (((2 * wq + ((lane >> 3) & 1)) ^ (lane & 7)) << 4);
      auto tile = [&](int T, auto& O) {
        constexpr int NJ = sizeof(O[0]) / 16;
        float S[4 * NJ];
#pragma unroll
        for (int i = 0; i < 4 * NJ; i++) S[i] = 0.f;
        const uint32_t d0 = box0(T), d7 = box7(T), fb = hi + BAR(BAR_FULL) + 64 * T;
        sfor<0, 8>([&](auto jc) {
          constexpr int jj = decltype(jc)::value;
          mbar_wait(fb + 8 * jj);
          wg_fence();
          sfor<0, 4>([&](auto kc) {
            constexpr int ks = decltype(kc)::value;
            wgmma_ss<0, (jj | ks) != 0>(S, (jj == 7 ? d7 : d0 + jj * 512) + ks * 2, dlo(OFF_R0 + jj * 4096 + ks * 32));
          });
          wg_commit();
        });
        wg_wait<0>();
        tie(S);
        if (NJ == 2) TL(T == 4 ? 11 : 52);
        bool over = T == 0;
#pragma unroll 1
        do {
          if (over) {
            float mx[2 * NJ];
#pragma unroll
            for (int jn = 0; jn < NJ; jn++) { mx[2 * jn] = fmaxf(S[4 * jn], S[4 * jn + 2]); mx[2 * jn + 1] = fmaxf(S[4 * jn + 1], S[4 * jn + 3]); }
            float a4[4], a2[2], a1;
            if constexpr (NJ == 4) {
              const bool up = lane & 16;
#pragma unroll
              for (int i = 0; i < 4; i++) { const float send = up ? mx[i] : mx[4 + i]; const float keep = up ? mx[4 + i] : mx[i]; a4[i] = fmaxf(keep, __shfl_xor_sync(~0u, send, 16)); }
            } else {
#pragma unroll
              for (int i = 0; i < 4; i++) { a4[i] = fmaxf(mx[i], __shfl_xor_sync(~0u, mx[i], 16)); if (lane & 16) a4[i] = -INFINITY; }
            }
            {
              const bool up = lane & 8;
#pragma unroll
              for (int i = 0; i < 2; i++) { const float send = up ? a4[i] : a4[2 + i]; const float keep = up ? a4[2 + i] : a4[i]; a2[i] = fmaxf(keep, __shfl_xor_sync(~0u, send, 8)); }
            }
            {
              const bool up = lane & 4;
              const float send = up ? a2[0] : a2[1]; const float keep = up ? a2[1] : a2[0];
              a1 = fmaxf(keep, __shfl_xor_sync(~0u, send, 4));
            }
            stsf(hi + OFF_RED + (wq * 32 + 8 * (g >> 1) + 2 * t + (g & 1)) * 4, a1);
            wg0bar();
            const float mt = fmaxf(fmaxf(ldsf(hi + OFF_RED + lane * 4), ldsf(hi + OFF_RED + 128 + lane * 4)),
                                   fmaxf(ldsf(hi + OFF_RED + 256 + lane * 4), ldsf(hi + OFF_RED + 384 + lane * 4)));
            const float m_new = fmaxf(m_run, ceilf(mt));
            const float al_l = ex2(m_run - m_new);
            m_run = m_new;
            if (wq == 0) { stsf(hi + OFF_MREF + lane * 4, m_new); stsf(hi + OFF_ALPHA + lane * 4, al_l); }
#pragma unroll
            for (int i = 0; i < 2 * NJ; i++) mh[i] = __shfl_sync(~0u, m_new, 8 * (i >> 1) + 2 * t + (i & 1));
            if (T > 0) {
              float alpha[8];
#pragma unroll
              for (int i = 0; i < 2 * NJ; i++) alpha[i] = __shfl_sync(~0u, al_l, 8 * (i >> 1) + 2 * t + (i & 1));
#pragma unroll
              for (int mb = 0; mb < 4; mb++) rescale(O[mb], alpha);
            }
          }
          uint32_t pk[2 * NJ];
          float x[4 * NJ];
#pragma unroll
          for (int i = 0; i < 4 * NJ; i++) x[i] = S[i] - mh[2 * (i >> 2) + (i & 1)];
#pragma unroll
          for (int i = 0; i < 2 * NJ; i++) pk[i] = pack_bf16(ex2(x[2 * i]), ex2(x[2 * i + 1]));
#pragma unroll
          for (int hf = 0; hf < NJ / 2; hf++) stsm4t(ptl + (T & 1) * 4096 + hf * 2048, pk[4 * hf], pk[4 * hf + 1], pk[4 * hf + 2], pk[4 * hf + 3]);
          asm volatile("fence.proxy.async.shared::cta;" ::: "memory");
          if constexpr (NJ == 4) {
#pragma unroll
            for (int i = 0; i < 8; i++) x[i] = fmaxf(x[i], x[i + 8]);
          }
          over = cbar_or(fmaxf(fmaxf(fmaxf(x[0], x[1]), fmaxf(x[2], x[3])), fmaxf(fmaxf(x[4], x[5]), fmaxf(x[6], x[7]))) > 30.f);
        } while (__builtin_expect(over, 0));
        if (NJ == 2) TL(T == 4 ? 34 : 53);
        pv(T, IC<0>{}, O);
      };
#pragma unroll 1
      for (int T = 0; T < 3; T++) { tile(T, O32); finish_private(T); }
      put_early();
#pragma unroll 1
      for (int T = 3;; T++) {
        tile(T, O16);
        if (T == 4) break;
        finish3();
      }
      wg_wait<1>();
      tie(O16[0]); tie(O16[1]);
      TL(12);
      put_o(false, 0, O16[0], O16[1]);
      __syncwarp();
      wg_wait<0>();
      tie(O16[2]); tie(O16[3]);
      put_o(false, 1, O16[2], O16[3]);
    } else {
      float L32[16], L16[8];
#pragma unroll
      for (int i = 0; i < 16; i++) L32[i] = 0.f;
      tie(L32);
      uint32_t one[4];
      if (lane < 4) sts1(hi + OFF_ONES + w * 16 + lane * 4, ONE2);
      __syncwarp();
      { const uint4 o = lds4(hi + OFF_ONES + w * 16); one[0] = o.x; one[1] = o.y; one[2] = o.z; one[3] = o.w; }
      const int hl = 8 * (g >> 1) + 2 * t + (g & 1);
      uint32_t* const mlo = pin(gs->MLL + ((16 * rI + (hl & 15)) * 64 + (cta >> 1)) * 8 + (g >> 2) * 4);
      uint32_t* const meo = pin(gs->MLE + (((16 * wq + (hl & 15)) ^ (16 * rI)) * 128 + cta) * 8 + (g >> 2) * 4);
      const uint32_t mra = pin32(hi + OFF_MREF + (16 * wq + (hl & 15)) * 4);
      auto tile = [&](int T, auto& O, auto& L) {
        if (__builtin_expect(cbar_or(false), 0)) {
          cbar_or(false);
          float alpha[8];
#pragma unroll
          for (int jn = 0; jn < (int)(sizeof(L) / 16); jn++) { const float2 a = ldsf2(hi + OFF_ALPHA + (8 * jn + 2 * t) * 4); alpha[2 * jn] = a.x; alpha[2 * jn + 1] = a.y; }
#pragma unroll
          for (int mb = 0; mb < 4; mb++) rescale(O[mb], alpha);
          rescale(L, alpha);
        }
        pv(T, IC<1>{}, O);
#pragma unroll
        for (int ks = 0; ks < 4; ks++) wgmma_ones(L, one, dlo(OFF_PT) + (T & 1) * 256 + ks * 2);
        wg_commit();
      };
#pragma unroll 1
      for (int T = 0; T < 3; T++) { tile(T, O32, L32); finish_private(T); tie(L32); }
      if (wq < 2) {
        const float l0 = (g & 1) ? L32[1] : L32[0], l1 = (g & 1) ? L32[5] : L32[4], l2 = (g & 1) ? L32[9] : L32[8], l3 = (g & 1) ? L32[13] : L32[12];
        const uint32_t m = lds1(mra), l = (__float_as_uint(wq ? ((g & 2) ? l3 : l2) : ((g & 2) ? l1 : l0)) | 1u) ^ par;
        stg4_b128(meo, make_uint4(m, l, m, l));
      }
      put_early();
#pragma unroll
      for (int i = 0; i < 8; i++) asm volatile("mov.b32 %0, %1;" : "=f"(L16[i]) : "f"(L32[i]));
#pragma unroll 1
      for (int T = 3;; T++) {
        tile(T, O16, L16);
        if (T == 4) break;
        finish3();
        tie(L16);
      }
      const uint32_t mref = lds1(mra);
      wg_wait<2>();
      tie(O16[0]); tie(O16[1]);
      put_o(false, 0, O16[0], O16[1]);
      __syncwarp();
      wg_wait<1>();
      tie(O16[2]); tie(O16[3]);
      put_o(false, 1, O16[2], O16[3]);
      __syncwarp();
      wg_wait<0>();
      tie(L16);
      if (wq == 0) {
        const float l0 = (g & 1) ? L16[1] : L16[0], l1 = (g & 1) ? L16[5] : L16[4];
        const uint32_t l = nz(__float_as_uint((g & 2) ? l1 : l0));
        stg_u128(mlo, make_uint4(mref, l, mref, l));
      }
    }
  }
  const uint32_t ck1 = clk32();
  TL(13);

  uint32_t aw[8][4];
  {
    uint2 mle[4];
    uint4 ve[4];
    const uint32_t* const px = pin(gs->X1 + (cta * 64 + w * 8 + t) * 64 + 4 * g);
    mbar_wait(hi + BAR(BAR_XE));
#pragma unroll
    for (int i = 0; i < 4; i++) mle[i] = lds2(hi + OFF_MLS + (w * 16 + 2 * t + 8 * (i & 1) + ((hI >> 4) ^ (i >> 1))) * 32);
#pragma unroll
    for (int i = 0; i < 4; i++) ve[i] = lds4(hi + OFF_XE + (w * 8 + t) * 256 + g * 16 + (i >> 1) * 1024 + (i & 1) * 128);
    while (true) {
      uint32_t a = 1u, o = 0u;
#pragma unroll
      for (int i = 0; i < 4; i++) { a &= ve[i].y & ve[i].w & mle[i].y; o |= ve[i].y | ve[i].w | mle[i].y; }
      if (__all_sync(~0u, (par ? ~o : a) & 1)) break;
#pragma unroll
      for (int i = 0; i < 4; i++) {
        ve[i] = ldg_2u64(px + (gs->XE - gs->X1) + (i >> 1) * 256 + (i & 1) * 32);
        mle[i] = ldg_u64(gs->MLE + (hI * 128 + w * 16 + 2 * t + 8 * (i & 1) + ((hI >> 4) ^ (i >> 1))) * 8);
      }
      TL(55);
    }
    float M = fmaxf(fmaxf(__uint_as_float(mle[0].x), __uint_as_float(mle[1].x)), fmaxf(__uint_as_float(mle[2].x), __uint_as_float(mle[3].x)));
    M = fmaxf(M, __shfl_xor_sync(~0u, M, 1)); M = fmaxf(M, __shfl_xor_sync(~0u, M, 2));
    uint32_t wb[4];
#pragma unroll
    for (int i = 0; i < 4; i++) wb[i] = pack_bf16(ex2(__uint_as_float(mle[i].x) - M), 0.f);
    float Ls = bf_lo(wb[2]) * __uint_as_float(mle[2].y) + bf_lo(wb[3]) * __uint_as_float(mle[3].y);
    float d0[4] = {0.f, 0.f, 0.f, 0.f}, d1[4] = {0.f, 0.f, 0.f, 0.f};
#pragma unroll
    for (int i = 0; i < 4; i++) mma_v((i & 2) ? d1 : d0, ve[i], shl_clamp(wb[2 + (i >> 1)], 16 * g - 64 * (i & 1)), shl_clamp(wb[2 + (i >> 1)], 16 * g - 64 * (i & 1) - 32));
    uint32_t sel[4][2];
#pragma unroll
    for (int i = 0; i < 4; i++) { sel[i][0] = pin32(shl_clamp(wb[i >> 1], 16 * g - 64 * (i & 1))); sel[i][1] = pin32(shl_clamp(wb[i >> 1], 16 * g - 64 * (i & 1) - 32)); }
    const uint32_t* const pm = pin(gs->MLL + (hI * 64 + w * 8 + t) * 8);
    uint32_t* const x2o = pin(gs->X2 + (cta * 256 + tid) * 2);
    const uint32_t bso = pin32(hi + OFF_BS4 + w * 320 + (16 * (t >> 1) + 2 * g + (t & 1)) * 8), bsi = pin32(hi + OFF_BS4 + g * 320 + t * 16);
    TL(14);
    wait_until(ck1, X1_D0);
    uint2 ml[2];
    uint4 v[4];
#pragma unroll
    for (int i = 0; i < 4; i++) v[i] = ldg_2u64(px + (i >> 1) * 256 + (i & 1) * 32);
#pragma unroll
    for (int i = 0; i < 2; i++) ml[i] = ldg_u64(pm + i * 32);
    TL(43);
    {
      const int mi = lane >> 3, r = lane & 7;
      const uint32_t base = hi + OFF_WUV + wg * 16384 + (mi >> 1) * 8192 + ((r & 6) + 8 * (r & 1)) * 128;
      const int ch = 2 * wq + (mi & 1);
      mbar_wait(hi + BAR(BAR_FULL + U_WUV) + 16 * wg); mbar_wait(hi + BAR(BAR_FULL + U_WUV + 1) + 16 * wg);
#pragma unroll
      for (int ks = 0; ks < 8; ks++) ldsm4t(aw[ks], base + (ks >> 1) * 2048 + (ks & 1) * 128 + ((ch ^ ((r & 6) + (ks & 1))) << 4));
    }
    TL(44);
    while (min(min3(min3(v[0].y, v[0].w, v[1].y), v[1].w, ml[0].y), min3(min3(v[2].y, v[2].w, v[3].y), v[3].w, ml[1].y)) == 0) {
#pragma unroll
      for (int i = 0; i < 4; i++) if (v[i].y == 0 || v[i].w == 0) v[i] = ldg_2u64(px + (i >> 1) * 256 + (i & 1) * 32);
#pragma unroll
      for (int i = 0; i < 2; i++) if (ml[i].y == 0) ml[i] = ldg_u64(pm + i * 32);
    }
    if (__builtin_expect(__any_sync(~0u, ml[0].x != mle[0].x || ml[1].x != mle[1].x), 0)) {
      float M2 = fmaxf(M, fmaxf(__uint_as_float(ml[0].x), __uint_as_float(ml[1].x)));
      M2 = fmaxf(M2, __shfl_xor_sync(~0u, M2, 1)); M2 = fmaxf(M2, __shfl_xor_sync(~0u, M2, 2));
      const float f = ex2(M - M2);
      Ls *= f;
#pragma unroll
      for (int i = 0; i < 4; i++) { d0[i] *= f; d1[i] *= f; }
#pragma unroll
      for (int i = 0; i < 2; i++) wb[i] = pack_bf16(ex2(__uint_as_float(ml[i].x) - M2), 0.f);
#pragma unroll
      for (int i = 0; i < 4; i++) { sel[i][0] = shl_clamp(wb[i >> 1], 16 * g - 64 * (i & 1)); sel[i][1] = shl_clamp(wb[i >> 1], 16 * g - 64 * (i & 1) - 32); }
    }
    TL(15);
    mma_v(d0, v[0], sel[0][0], sel[0][1]); mma_v(d1, v[2], sel[2][0], sel[2][1]);
    mma_v(d0, v[1], sel[1][0], sel[1][1]); mma_v(d1, v[3], sel[3][0], sel[3][1]);
    Ls += bf_lo(wb[0]) * __uint_as_float(ml[0].y) + bf_lo(wb[1]) * __uint_as_float(ml[1].y);
    Ls += __shfl_xor_sync(~0u, Ls, 1); Ls += __shfl_xor_sync(~0u, Ls, 2);
    const float inv = __fdividef(1.f, Ls);
    sts2(bso, pack_bf16((d0[0] + d1[0]) * inv, (d0[1] + d1[1]) * inv), pack_bf16((d0[2] + d1[2]) * inv, (d0[3] + d1[3]) * inv));
    cbar();
    TL(16);
    float o[4][4] = {{0.f, 0.f, 0.f, 0.f}, {0.f, 0.f, 0.f, 0.f}, {0.f, 0.f, 0.f, 0.f}, {0.f, 0.f, 0.f, 0.f}};
    uint4 b[4];
#pragma unroll
    for (int kk = 0; kk < 4; kk++) b[kk] = lds4(bsi + kk * 64);
#pragma unroll
    for (int kk = 0; kk < 4; kk++) { mma16816(o[(2 * kk) & 3], aw[2 * kk], b[kk].x, b[kk].y); mma16816(o[(2 * kk + 1) & 3], aw[2 * kk + 1], b[kk].z, b[kk].w); }
    stg_u64(x2o, pack_bf16((o[0][0] + o[1][0]) + (o[2][0] + o[3][0]), (o[0][1] + o[1][1]) + (o[2][1] + o[3][1])),
            pack_bf16((o[0][2] + o[1][2]) + (o[2][2] + o[3][2]), (o[0][3] + o[1][3]) + (o[2][3] + o[3][3])));
  }
  const uint32_t ck2 = clk32();
  TL(17);
  {
    mbar_wait(hi + BAR(BAR_FULL + U_WO) + 16 * wg); mbar_wait(hi + BAR(BAR_FULL + U_WO + 1) + 16 * wg);
    load_a_t(aw, hi + OFF_WO + wg * 16384, wq, lane);
    uint32_t* const o = pin(gs->X3A + (4 * (8 * jI + w)) * 512 + g * 256 + hI * 8 + 2 * t);
    const uint32_t* const x2i = pin(gs->X2 + (hI * 4 * 256 + tid) * 2);
    const uint32_t bso = pin32(hi + OFF_BS5 + (16 * w + g) * 16 + t * 4), bsi = pin32(hi + OFF_BS5 + lane * 16);
    TL(45);
    wait_until(ck2, D_X2);
    uint2 v[4] = {{0u, 0u}, {0u, 0u}, {0u, 0u}, {0u, 0u}};
    sum4_to_smem(v, x2i, bso);
    cbar();
    TL(18);
    float d[4];
    mma128(d, aw, bsi);
    stg_u64(o, pack_bf16(d[0], d[1]), pack_bf16(d[2], d[3]));
    if (lane == 0) mbar_arrive(hi + BAR(BAR_P5D));
  }
  const uint32_t ck3 = clk32();
  TL(19);
  if (cta < NFF) {
    const int mi = lane >> 3, r = lane & 7;
    uint32_t a1[4][4], a2[4][4];
    while (true) {
      uint32_t mn = 0xffffffffu;
#pragma unroll
      for (int i = 0; i < 8; i++) mn = min3(mn, bs[i], bc[i]);
      if (__all_sync(~0u, mn != 0)) break;
#pragma unroll
      for (int i = 0; i < 8; i++) { bs[i] = ldg_rlx1(mbi + i * 32); bc[i] = ldg_rlx1(mbi + 2048 + i * 32); }
    }
#pragma unroll
    for (int i = 0; i < 8; i++) { bs[i] = movm(bs[i]); bc[i] = hadd2(movm(bc[i]), ONE2); }
    mbar_wait(hi + BAR(BAR_FULL + U_W1) + 8 * wg);
#pragma unroll
    for (int ks = 0; ks < 4; ks++) ldsm4t(a1[ks], hi + OFF_W1 + (64 * w + 16 * ks + 8 * (mi >> 1) + r) * 32 + (mi & 1) * 16);
    {
      float u[4] = {0.f, 0.f, 0.f, 0.f}, vv[4] = {0.f, 0.f, 0.f, 0.f};
#pragma unroll
      for (int ks = 0; ks < 4; ks++) { mma16816(u, a1[ks], bc[2 * ks], bc[2 * ks + 1]); mma16816(vv, a1[ks], bs[2 * ks], bs[2 * ks + 1]); }
      sts4f(hi + OFF_REDU + tid * 16, u[0], u[1], u[2], u[3]);
      sts4f(hi + OFF_REDV + tid * 16, vv[0], vv[1], vv[2], vv[3]);
    }
    cbar();
    const int lp = (tid >> 2) & 31, kq = tid & 3;
    const int fo = (lp >> 2) + 8 * (kq >> 1), bo = 2 * (lp & 3) + (kq & 1);
    float U = 0.f, V = 0.f;
    if (tid < 128) {
#pragma unroll
      for (int i = 0; i < 8; i++) { U += ldsf(hi + OFF_REDU + i * 512 + tid * 4); V += ldsf(hi + OFF_REDV + i * 512 + tid * 4); }
    }
    const uint32_t* xb = pin(gs->X3B + (cta & (NREP - 1)) * 2048 + (16 * w + t) * 16 + 2 * g);
    uint32_t* const ox = pin(gs->X4 + ((16 * w + (g >> 1)) * NFF + cta) * 16 + (g & 1) * 8 + 2 * t);
    const uint32_t h1o = pin32(hi + OFF_H1 + fo * 16 + bo * 2), sti = pin32(hi + OFF_REDS + bo * 64), sto = pin32(hi + OFF_REDS + g * 64 + w * 8);
    const bool w2ok = mbar_test(hi + BAR(BAR_FULL + U_W2) + 8 * wg);
    const uint32_t a2a = hi + OFF_W2 + w * 2048 + (8 * (mi >> 1) + r) * 128;
    if (w2ok) {
#pragma unroll
      for (int mb = 0; mb < 4; mb++) ldsm4t(a2[mb], a2a + (((2 * mb + (mi & 1)) ^ r) << 4));
    }
    TL(46);
    wait_until(ck3, D_X3B);
    uint2 x[4];
    {
      while (true) {
#pragma unroll
        for (int ks = 0; ks < 4; ks++) x[ks] = ldg_u64(xb + ks * 64);
        if (__all_sync(~0u, min(min(x[0].y, x[1].y), min(x[2].y, x[3].y)) != 0)) break;
      }
    }
    TL(21);
    float G[2][4] = {{0.f, 0.f, 0.f, 0.f}, {0.f, 0.f, 0.f, 0.f}}, S[2][4] = {{0.f, 0.f, 0.f, 0.f}, {0.f, 0.f, 0.f, 0.f}};
#pragma unroll
    for (int ks = 0; ks < 4; ks++) {
      const uint32_t s0[4] = {x[ks].x, ONE2, x[ks].y, ONE2};
      mma16816(S[ks & 1], s0, x[ks].x, x[ks].y);
      mma16816(G[ks & 1], a1[ks], hmul2(x[ks].x, bc[2 * ks]), hmul2(x[ks].y, bc[2 * ks + 1]));
    }
    if ((g >> 1) == t) sts2f(sto, (g & 1) ? S[0][3] + S[1][3] : S[0][2] + S[1][2], (g & 1) ? S[0][1] + S[1][1] : S[0][0] + S[1][0]);
    sts4f(hi + OFF_REDG + tid * 16, G[0][0] + G[1][0], G[0][1] + G[1][1], G[0][2] + G[1][2], G[0][3] + G[1][3]);
    cbar();
    TL(39);
    if (tid < 128) {
      float gv[8];
      float4 sv[4];
#pragma unroll
      for (int i = 0; i < 4; i++) sv[i] = ldsf4(sti + i * 16);
#pragma unroll
      for (int i = 0; i < 8; i++) gv[i] = ldsf(hi + OFF_REDG + i * 512 + tid * 4);
      const float s1 = ((sv[0].x + sv[0].z) + (sv[1].x + sv[1].z)) + ((sv[2].x + sv[2].z) + (sv[3].x + sv[3].z));
      const float s2 = ((sv[0].y + sv[0].w) + (sv[1].y + sv[1].w)) + ((sv[2].y + sv[2].w) + (sv[3].y + sv[3].w));
      const float gs_ = ((gv[0] + gv[1]) + (gv[2] + gv[3])) + ((gv[4] + gv[5]) + (gv[6] + gv[7]));
      const float mu = s1 * (1.f / 512.f);
      const float rs = rsqrtf(fmaxf(s2 * (1.f / 512.f) - mu * mu, 0.f) + 1e-5f);
      const float hv = fmaxf(rs * (gs_ - mu * U) + V, 0.f);
      asm volatile("st.shared.u16 [%0], %1;" ::"r"(h1o), "h"(__bfloat16_as_ushort(__float2bfloat16(hv))) : "memory");
    }
    if (!w2ok) {
      mbar_wait(hi + BAR(BAR_FULL + U_W2) + 8 * wg);
#pragma unroll
      for (int mb = 0; mb < 4; mb++) ldsm4t(a2[mb], a2a + (((2 * mb + (mi & 1)) ^ r) << 4));
    }
    cbar();
    TL(40);
    uint32_t b0, b1;
    ldsm2t(b0, b1, hi + OFF_H1 + (lane & 15) * 16);
#pragma unroll
    for (int mb = 0; mb < 4; mb++) {
      float o[4] = {0.f, 0.f, 0.f, 0.f};
      mma16816(o, a2[mb], b0, b1);
      stg_u64(ox + mb * 4 * NFF * 16, pack_bf16(o[0], o[1]), pack_bf16(o[2], o[3]));
    }
    TL(22);
    if (lane == 0) mbar_arrive(hi + BAR(BAR_P7D));
  }
}

typedef CUresult (*EncodeTiledFn)(CUtensorMap*, CUtensorMapDataType, cuuint32_t, void*, const cuuint64_t*, const cuuint64_t*,
                                  const cuuint32_t*, const cuuint32_t*, CUtensorMapInterleave, CUtensorMapSwizzle,
                                  CUtensorMapL2promotion, CUtensorMapFloatOOBfill);

void make_map(EncodeTiledFn enc, CUtensorMap* m, const void* base, uint64_t cols, uint64_t rows, uint32_t bc, uint32_t br,
              CUtensorMapSwizzle sw, CUtensorMapL2promotion promo) {
  cuuint64_t dims[2] = {cols, rows};
  cuuint64_t strides[1] = {cols * 2};
  cuuint32_t box[2] = {bc, br};
  cuuint32_t es[2] = {1, 1};
  enc(m, CU_TENSOR_MAP_DATA_TYPE_BFLOAT16, 2, const_cast<void*>(base), dims, strides, box, es, CU_TENSOR_MAP_INTERLEAVE_NONE, sw, promo,
      CU_TENSOR_MAP_FLOAT_OOB_FILL_NONE);
}
void make_map3(EncodeTiledFn enc, CUtensorMap* m, const void* base, uint64_t rows, uint32_t br, uint32_t bb) {
  cuuint64_t dims[3] = {64, rows, 8};
  cuuint64_t strides[2] = {1024, 128};
  cuuint32_t box[3] = {64, br, bb};
  cuuint32_t es[3] = {1, 1, 1};
  enc(m, CU_TENSOR_MAP_DATA_TYPE_BFLOAT16, 3, const_cast<void*>(base), dims, strides, box, es, CU_TENSOR_MAP_INTERLEAVE_NONE,
      CU_TENSOR_MAP_SWIZZLE_128B, CU_TENSOR_MAP_L2_PROMOTION_NONE, CU_TENSOR_MAP_FLOAT_OOB_FILL_NONE);
}

}

extern "C" void kernel_launch(void* const* d_in, const int* in_sizes, int n_in, void* d_out, int out_size) {
  (void)in_sizes; (void)n_in; (void)out_size;
  static EncodeTiledFn enc = nullptr;
  static Scratch* scratch = nullptr;
  if (!enc) {
    void* sp = nullptr;
    cudaGetSymbolAddress(&sp, g_s);
    scratch = (Scratch*)sp;
    void* fn = nullptr;
    cudaDriverEntryPointQueryResult q;
    cudaGetDriverEntryPoint("cuTensorMapEncodeTiled", &fn, cudaEnableDefault, &q);
    enc = (EncodeTiledFn)fn;
    cudaFuncSetAttribute(fused_decode_kernel, cudaFuncAttributeMaxDynamicSharedMemorySize, SMEM_BYTES);
  }
  Params P;
  make_map(enc, &P.ckv, d_in[1], 512, 8 * 4096, 64, 64, CU_TENSOR_MAP_SWIZZLE_128B, CU_TENSOR_MAP_L2_PROMOTION_NONE);
  make_map(enc, &P.wq, d_in[2], 4096, 512, 64, 64, CU_TENSOR_MAP_SWIZZLE_128B, CU_TENSOR_MAP_L2_PROMOTION_NONE);
  make_map(enc, &P.wuk, d_in[3], 4096, 512, 64, 64, CU_TENSOR_MAP_SWIZZLE_128B, CU_TENSOR_MAP_L2_PROMOTION_NONE);
  make_map(enc, &P.wuv, d_in[4], 4096, 512, 64, 64, CU_TENSOR_MAP_SWIZZLE_128B, CU_TENSOR_MAP_L2_PROMOTION_NONE);
  make_map(enc, &P.wo, d_in[5], 512, 4096, 64, 64, CU_TENSOR_MAP_SWIZZLE_128B, CU_TENSOR_MAP_L2_PROMOTION_NONE);
  make_map(enc, &P.w1, d_in[7], 1792, 512, FCH, 256, CU_TENSOR_MAP_SWIZZLE_NONE, CU_TENSOR_MAP_L2_PROMOTION_L2_128B);
  make_map3(enc, &P.w2, d_in[8], 1792, FCH, 4);
  make_map(enc, &P.wmod, d_in[10], 3072, 512, 16, 256, CU_TENSOR_MAP_SWIZZLE_NONE, CU_TENSOR_MAP_L2_PROMOTION_L2_128B);
  fused_decode_kernel<<<NCTA, NTHREADS, SMEM_BYTES>>>((__nv_bfloat16*)d_out, scratch, (const uint8_t*)d_in[10], (const uint8_t*)d_in[0],
                                                      (const uint8_t*)d_in[9], P);
}
```

```cpp
#include <cuda_runtime.h>
#include <cuda.h>
#include <cuda_bf16.h>
#include <stdint.h>

namespace {

constexpr int NCTA = 128;
constexpr int NTHREADS = 384;
constexpr int FCH = 16;
constexpr int NFF = 1792 / FCH;

constexpr uint32_t SB = 1024;
__host__ __device__ constexpr uint32_t slot(int i) { return SB + i * 8192; }
constexpr uint32_t OFF_R1 = slot(16);
constexpr uint32_t OFF_R2 = slot(20);
constexpr uint32_t OFF_PT = slot(23);
constexpr uint32_t OFF_R0 = slot(24);
constexpr uint32_t OFF_MISC = SB + 229376;
constexpr uint32_t OFF_BARS = OFF_MISC;
constexpr uint32_t OFF_FM = OFF_MISC + 736;
constexpr uint32_t OFF_EPOCH = OFF_MISC + 768;
constexpr uint32_t OFF_TL = OFF_MISC + 784;
constexpr uint32_t OFF_BS = OFF_MISC + 1024;
constexpr uint32_t SMEM_BYTES = 229376 + 3072;
constexpr uint32_t OFF_P0S = OFF_R0 + 24576;
constexpr uint32_t OFF_BS2 = OFF_R0 + 30720;
constexpr uint32_t OFF_RED = OFF_BS;
constexpr uint32_t OFF_ALPHA = OFF_BS + 512;
constexpr uint32_t OFF_MREF = OFF_BS + 640;
constexpr uint32_t OFF_FB = OFF_BS + 1024;
__host__ __device__ constexpr int box_slot(int n) { return n < 23 ? n : n - 23; }
constexpr uint32_t OFF_WUV = slot(17);
constexpr uint32_t OFF_XE = slot(21);
constexpr uint32_t OFF_BS4 = slot(0);
constexpr uint32_t OFF_BS5 = slot(0) + 4096;
constexpr uint32_t OFF_MLS = slot(0) + 4096;
constexpr uint32_t OFF_WO = slot(1);
constexpr uint32_t OFF_W1 = slot(5);
constexpr uint32_t OFF_W2 = slot(7);
constexpr uint32_t OFF_REDG = OFF_R0;
constexpr uint32_t OFF_REDS = OFF_R0 + 4096;
constexpr uint32_t OFF_REDU = OFF_R0 + 8192;
constexpr uint32_t OFF_REDV = OFF_R0 + 12288;
constexpr uint32_t OFF_H1 = OFF_R0 + 16384;

constexpr int BAR_FULL = 10;
constexpr int U_WQ = -10, U_WUK = -6, U_WMOD = -2, U_WUV = 40, U_WO = 44, U_W1 = 48, U_W2 = 50, NUNITS = 52;
constexpr int BAR_EMPTY = 62;
constexpr int BAR_GO = 66, BAR_CLR = 67, BAR_EPOCH = 68;
constexpr int BAR_P2E = 69, BAR_P5D = 70, BAR_P7D = 71;
constexpr int BAR_XE = 72;
constexpr int BAR_FM = 73;
constexpr int BAR_QXG = 74;
constexpr int NBARS = 82;
__host__ __device__ constexpr uint32_t BAR(int i) { return OFF_BARS + 8 * i; }
#define WIN_0 1
#define PACE_T0 450
#define PACE_DT 330
#define PACE_DTM 320
#define PACE_NM 8
#define PACE_DTE 330
#define PACE_GAP 200
#define PACE_DT2 370
#define CPA ""
#define PROMO CU_TENSOR_MAP_L2_PROMOTION_NONE
#define NPROBE 3
#define WIN_PRE 5
#define WIN_MID 8
#define WIN_END 8
#define WIN_TAIL 4
#define PACE_NS 200
#define CLR_CLK 220
#define CLR_AT 3
#define CLR_D0 0
#define D_MOD 400
#define D_QP 400
#define D_QX 900
#define QK_UNROLL 1
#define QK_FENCE 1
#define ML_FIRST 1
#define PV_SPLIT 3
#define XE_AT 37
#define EARLY_PER 2
#define CNT_AT 27
#define X1_D0 1300
#define D_X2 300
#define D_X3A 300
#define D_X3B 0
#define D_FIN 600

struct Scratch {
  uint32_t MODA[1024 * 4];
  uint32_t QP[128 * 256 * 2];
  uint32_t MODB[2][2048 * 4];
  uint32_t FL[2][128];
  uint32_t QX[2][8 * 32 * 256];
  uint32_t XE[128 * 64 * 64];
  uint32_t MLE[32 * 128 * 8];
  uint32_t epoch;
  uint32_t pad[31];
  uint32_t cnt;
  alignas(65536) uint32_t X3B[16384];
  uint32_t IN[128][16384];
};
__device__ uint8_t g_s[sizeof(Scratch) + 65536];

#define TL(idx) do {} while (0)
#define TLW(idx) do {} while (0)
#define PROBE_UNITS(a, b) do {} while (0)

struct Params {
  CUtensorMap wq, wuk, wmod, ckv, wuv, wo, w1, w2;
};

__device__ __forceinline__ void mbar_init(uint32_t bar, int cnt) { asm volatile("mbarrier.init.shared::cta.b64 [%0], %1;" ::"r"(bar), "r"(cnt)); }
__device__ __forceinline__ void mbar_expect(uint32_t bar, uint32_t bytes) { asm volatile("mbarrier.arrive.expect_tx.shared::cta.b64 _, [%0], %1;" ::"r"(bar), "r"(bytes) : "memory"); }
__device__ __forceinline__ void mbar_arrive(uint32_t bar) { asm volatile("mbarrier.arrive.shared::cta.b64 _, [%0];" ::"r"(bar) : "memory"); }
__device__ __forceinline__ void mbar_arrive_cluster(uint32_t bar) { asm volatile("mbarrier.arrive.shared::cluster.b64 _, [%0];" ::"r"(bar) : "memory"); }
__device__ __forceinline__ bool mbar_test(uint32_t bar) {
  uint32_t ok;
  asm volatile("{\n.reg .pred p;\nmbarrier.test_wait.parity.shared::cta.b64 p, [%1], 0;\nselp.u32 %0,1,0,p;\n}" : "=r"(ok) : "r"(bar) : "memory");
  return ok;
}
__device__ __forceinline__ uint32_t gtime32() { uint32_t c; asm volatile("mov.u32 %0, %%globaltimer_lo;" : "=r"(c) :: "memory"); return c; }
__device__ __forceinline__ uint32_t clk32() { uint32_t c; asm volatile("{\n.reg .u64 t;\nmov.u64 t, %%clock64;\ncvt.u32.u64 %0, t;\n}" : "=r"(c) :: "memory"); return c; }
__device__ __forceinline__ void wait_until(uint32_t c0, int clocks) { if (clocks > 0) while ((int)(clk32() - c0) < clocks) {} }
__device__ __forceinline__ void backoff(int clocks) { if (clocks > 0) wait_until(clk32(), clocks); }
__device__ __forceinline__ uint32_t pin32(uint32_t p) { asm volatile("" : "+r"(p)); return p; }
template <typename T> __device__ __forceinline__ T* pin(T* p) { asm volatile("" : "+l"(p)); return p; }
__device__ __forceinline__ uint32_t hold32(uint32_t p) { asm volatile("shfl.sync.bfly.b32 %0, %0, 0, 0x1f, 0xffffffff;" : "+r"(p) :: "memory"); return p; }
__device__ __forceinline__ float holdf(float p) { return __uint_as_float(hold32(__float_as_uint(p))); }
template <typename T> __device__ __forceinline__ T* hold(T* p) {
  asm volatile("{\n.reg .b32 a, b;\nmov.b64 {a, b}, %0;\nshfl.sync.bfly.b32 a, a, 0, 0x1f, 0xffffffff;\nshfl.sync.bfly.b32 b, b, 0, 0x1f, 0xffffffff;\nmov.b64 %0, {a, b};\n}" : "+l"(p) :: "memory");
  return p;
}
constexpr int SPIN_LIMIT = 1 << 22;
__device__ __forceinline__ void mbar_wait(uint32_t bar) {
  asm volatile("{\n.reg .pred p;\nMW_LOOP:\nmbarrier.try_wait.parity.shared::cta.b64 p, [%0], 0;\n@!p bra MW_LOOP;\n}" ::"r"(bar) : "memory");
}
__device__ __forceinline__ void mbar_wait_b(uint32_t bar) {
  asm volatile("{\n.reg .pred p;\n.reg .u32 c;\nmov.u32 c, 0;\n"
               "MW_LOOP:\nmbarrier.try_wait.parity.shared::cta.b64 p, [%0], 0;\n@p bra MW_DONE;\n"
               "add.u32 c, c, 1;\nsetp.lt.u32 p, c, 1048576;\n@p bra MW_LOOP;\ntrap;\nMW_DONE:\n}"
               ::"r"(bar) : "memory");
}
__device__ __forceinline__ void tma2d(uint32_t dst, const CUtensorMap* m, int c0, int c1, uint32_t bar, uint64_t pol) {
  asm volatile("cp.async.bulk.tensor.2d.shared::cluster.global.mbarrier::complete_tx::bytes.L2::cache_hint [%0], [%1, {%3,%4}], [%2], %5;"
               ::"r"(dst), "l"(m), "r"(bar), "r"(c0), "r"(c1), "l"(pol) : "memory");
}
__device__ __forceinline__ void tma2d_both(uint32_t dst, const CUtensorMap* m, int c0, int c1, uint32_t bar, uint64_t pol) {
  asm volatile("cp.async.bulk.tensor.2d.shared::cluster.global.mbarrier::complete_tx::bytes.multicast::cluster.L2::cache_hint [%0], [%1, {%3,%4}], [%2], %6, %5;"
               ::"r"(dst), "l"(m), "r"(bar), "r"(c0), "r"(c1), "l"(pol), "h"((uint16_t)3) : "memory");
}
__device__ __forceinline__ void tma3d(uint32_t dst, const CUtensorMap* m, int c0, int c1, int c2, uint32_t bar, uint64_t pol) {
  asm volatile("cp.async.bulk.tensor.3d.shared::cluster.global.mbarrier::complete_tx::bytes.L2::cache_hint [%0], [%1, {%3,%4,%5}], [%2], %6;"
               ::"r"(dst), "l"(m), "r"(bar), "r"(c0), "r"(c1), "r"(c2), "l"(pol) : "memory");
}
__device__ __forceinline__ void tma2d_nohint(uint32_t dst, const CUtensorMap* m, int c0, int c1, uint32_t bar) {
  asm volatile("cp.async.bulk.tensor.2d.shared::cluster.global.mbarrier::complete_tx::bytes [%0], [%1, {%3,%4}], [%2];"
               ::"r"(dst), "l"(m), "r"(bar), "r"(c0), "r"(c1) : "memory");
}
__device__ __forceinline__ void bulk_load(uint32_t dst, const void* src, uint32_t bytes, uint32_t bar) {
  asm volatile("cp.async.bulk.shared::cluster.global.mbarrier::complete_tx::bytes [%0], [%1], %2, [%3];" ::"r"(dst), "l"(src), "r"(bytes), "r"(bar) : "memory");
}
__device__ __forceinline__ void cbar() { asm volatile("bar.sync 1, 256;" ::: "memory"); }
__device__ __forceinline__ void wg0bar() { asm volatile("bar.sync 2, 128;" ::: "memory"); }
__device__ __forceinline__ bool cbar_or(bool p) {
  uint32_t r;
  asm volatile("{\n.reg .pred p, q;\nsetp.ne.u32 p, %1, 0;\nbarrier.cta.red.or.aligned.pred q, 1, 256, p;\nselp.u32 %0, 1, 0, q;\n}" : "=r"(r) : "r"((uint32_t)p) : "memory");
  return r;
}

__device__ __forceinline__ uint32_t ldg_rlx1(const void* p) { uint32_t v; asm volatile("ld.relaxed.gpu.global.u32 %0, [%1];" : "=r"(v) : "l"(p) : "memory"); return v; }
__device__ __forceinline__ void stg4(void* p, uint4 v) { asm volatile("st.relaxed.gpu.global.v4.u32 [%0], {%1,%2,%3,%4};" ::"l"(p), "r"(v.x), "r"(v.y), "r"(v.z), "r"(v.w) : "memory"); }
__device__ __forceinline__ void stg1(void* p, uint32_t a) { asm volatile("st.relaxed.gpu.global.u32 [%0], %1;" ::"l"(p), "r"(a) : "memory"); }
__device__ __forceinline__ uint32_t nz(uint32_t w) { return max(w, 1u); }
__device__ __forceinline__ uint32_t min3(uint32_t a, uint32_t b, uint32_t c) { return min(min(a, b), c); }

__device__ __forceinline__ uint32_t pack_bf16(float lo, float hi) { uint32_t r; asm("cvt.rn.bf16x2.f32 %0, %1, %2;" : "=r"(r) : "f"(hi), "f"(lo)); return r; }
__device__ __forceinline__ float bf_lo(uint32_t w) { return __uint_as_float(w << 16); }
__device__ __forceinline__ float bf_hi(uint32_t w) { return __uint_as_float(w & 0xffff0000u); }
__device__ __forceinline__ float ex2(float x) { float r; asm("ex2.approx.ftz.f32 %0, %1;" : "=f"(r) : "f"(x)); return r; }
__device__ __forceinline__ uint32_t shl_clamp(uint32_t x, int s) { uint32_t r; asm("shl.b32 %0, %1, %2;" : "=r"(r) : "r"(x), "r"(s)); return r; }

__device__ __forceinline__ void ldsm4(uint32_t (&r)[4], uint32_t a) { asm volatile("ldmatrix.sync.aligned.m8n8.x4.shared.b16 {%0,%1,%2,%3}, [%4];" : "=r"(r[0]), "=r"(r[1]), "=r"(r[2]), "=r"(r[3]) : "r"(a) : "memory"); }
__device__ __forceinline__ void ldsm4t(uint32_t (&r)[4], uint32_t a) { asm volatile("ldmatrix.sync.aligned.m8n8.x4.trans.shared.b16 {%0,%1,%2,%3}, [%4];" : "=r"(r[0]), "=r"(r[1]), "=r"(r[2]), "=r"(r[3]) : "r"(a) : "memory"); }
__device__ __forceinline__ void ldsm2t(uint32_t& r0, uint32_t& r1, uint32_t a) { asm volatile("ldmatrix.sync.aligned.m8n8.x2.trans.shared.b16 {%0,%1}, [%2];" : "=r"(r0), "=r"(r1) : "r"(a) : "memory"); }
__device__ __forceinline__ void stsm4t(uint32_t a, uint32_t r0, uint32_t r1, uint32_t r2, uint32_t r3) { asm volatile("stmatrix.sync.aligned.m8n8.x4.trans.shared.b16 [%0], {%1,%2,%3,%4};" ::"r"(a), "r"(r0), "r"(r1), "r"(r2), "r"(r3) : "memory"); }
__device__ __forceinline__ void stsm2t(uint32_t a, uint32_t r0, uint32_t r1) { asm volatile("stmatrix.sync.aligned.m8n8.x2.trans.shared.b16 [%0], {%1,%2};" ::"r"(a), "r"(r0), "r"(r1) : "memory"); }
__device__ __forceinline__ void mma16816(float (&d)[4], const uint32_t (&a)[4], uint32_t b0, uint32_t b1) {
  asm volatile("mma.sync.aligned.m16n8k16.row.col.f32.bf16.bf16.f32 {%0,%1,%2,%3}, {%4,%5,%6,%7}, {%8,%9}, {%0,%1,%2,%3};"
               : "+f"(d[0]), "+f"(d[1]), "+f"(d[2]), "+f"(d[3]) : "r"(a[0]), "r"(a[1]), "r"(a[2]), "r"(a[3]), "r"(b0), "r"(b1));
}
__device__ __forceinline__ void mma_v(float (&d)[4], const uint4& a, uint32_t b0, uint32_t b1) {
  asm volatile("mma.sync.aligned.m16n8k16.row.col.f32.bf16.bf16.f32 {%0,%1,%2,%3}, {%4,%5,%6,%7}, {%8,%9}, {%0,%1,%2,%3};"
               : "+f"(d[0]), "+f"(d[1]), "+f"(d[2]), "+f"(d[3]) : "r"(a.x), "r"(a.y), "r"(a.z), "r"(a.w), "r"(b0), "r"(b1));
}
__device__ __forceinline__ void sts1(uint32_t a, uint32_t v) { asm volatile("st.shared.u32 [%0], %1;" ::"r"(a), "r"(v) : "memory"); }
__device__ __forceinline__ void sts2(uint32_t a, uint32_t x, uint32_t y) { asm volatile("st.shared.v2.u32 [%0], {%1,%2};" ::"r"(a), "r"(x), "r"(y) : "memory"); }
__device__ __forceinline__ void sts4(uint32_t a, uint4 v) { asm volatile("st.shared.v4.u32 [%0], {%1,%2,%3,%4};" ::"r"(a), "r"(v.x), "r"(v.y), "r"(v.z), "r"(v.w) : "memory"); }
__device__ __forceinline__ void sts4f(uint32_t a, float x, float y, float z, float w) { asm volatile("st.shared.v4.f32 [%0], {%1,%2,%3,%4};" ::"r"(a), "f"(x), "f"(y), "f"(z), "f"(w) : "memory"); }
__device__ __forceinline__ void sts2f(uint32_t a, float x, float y) { asm volatile("st.shared.v2.f32 [%0], {%1,%2};" ::"r"(a), "f"(x), "f"(y) : "memory"); }
__device__ __forceinline__ void stsf(uint32_t a, float v) { asm volatile("st.shared.f32 [%0], %1;" ::"r"(a), "f"(v) : "memory"); }
__device__ __forceinline__ uint32_t lds1(uint32_t a) { uint32_t v; asm volatile("ld.shared.u32 %0, [%1];" : "=r"(v) : "r"(a) : "memory"); return v; }
__device__ __forceinline__ uint2 lds2(uint32_t a) { uint2 v; asm volatile("ld.shared.v2.u32 {%0,%1}, [%2];" : "=r"(v.x), "=r"(v.y) : "r"(a) : "memory"); return v; }
__device__ __forceinline__ float ldsf(uint32_t a) { float v; asm volatile("ld.shared.f32 %0, [%1];" : "=f"(v) : "r"(a) : "memory"); return v; }
__device__ __forceinline__ float2 ldsf2(uint32_t a) { float2 v; asm volatile("ld.shared.v2.f32 {%0,%1}, [%2];" : "=f"(v.x), "=f"(v.y) : "r"(a) : "memory"); return v; }
__device__ __forceinline__ float4 ldsf4(uint32_t a) { float4 v; asm volatile("ld.shared.v4.f32 {%0,%1,%2,%3}, [%4];" : "=f"(v.x), "=f"(v.y), "=f"(v.z), "=f"(v.w) : "r"(a) : "memory"); return v; }
__device__ __forceinline__ uint4 lds4(uint32_t a) { uint4 v; asm volatile("ld.shared.v4.u32 {%0,%1,%2,%3}, [%4];" : "=r"(v.x), "=r"(v.y), "=r"(v.z), "=r"(v.w) : "r"(a) : "memory"); return v; }

__device__ __forceinline__ void wg_fence() { asm volatile("wgmma.fence.sync.aligned;" ::: "memory"); }
__device__ __forceinline__ void wg_commit() { asm volatile("wgmma.commit_group.sync.aligned;" ::: "memory"); }
template <int N> __device__ __forceinline__ void wg_wait() { asm volatile("wgmma.wait_group.sync.aligned %0;" ::"n"(N) : "memory"); }
__host__ __device__ constexpr uint32_t dlo(uint32_t addr) { return (addr >> 4) | 0x10000u; }
constexpr uint32_t ONE2 = 0x3f803f80u;
template <int TA, int ACC> __device__ __forceinline__ void wgmma_ss(float (&d)[16], uint32_t da, uint32_t db) {
  asm volatile("{\n.reg .b64 da, db;\nmov.b64 da, {%16, 0x40000040};\nmov.b64 db, {%17, 0x40000040};\n"
               "wgmma.mma_async.sync.aligned.m64n32k16.f32.bf16.bf16 {%0,%1,%2,%3,%4,%5,%6,%7,%8,%9,%10,%11,%12,%13,%14,%15}, da, db, %18, 1, 1, %19, 0;\n}"
               : "+f"(d[0]), "+f"(d[1]), "+f"(d[2]), "+f"(d[3]), "+f"(d[4]), "+f"(d[5]), "+f"(d[6]), "+f"(d[7]),
                 "+f"(d[8]), "+f"(d[9]), "+f"(d[10]), "+f"(d[11]), "+f"(d[12]), "+f"(d[13]), "+f"(d[14]), "+f"(d[15])
               : "r"(da), "r"(db), "n"(ACC), "n"(TA));
}
template <int TA, int ACC> __device__ __forceinline__ void wgmma_ss(float (&d)[8], uint32_t da, uint32_t db) {
  asm volatile("{\n.reg .b64 da, db;\nmov.b64 da, {%8, 0x40000040};\nmov.b64 db, {%9, 0x40000040};\n"
               "wgmma.mma_async.sync.aligned.m64n16k16.f32.bf16.bf16 {%0,%1,%2,%3,%4,%5,%6,%7}, da, db, %10, 1, 1, %11, 0;\n}"
               : "+f"(d[0]), "+f"(d[1]), "+f"(d[2]), "+f"(d[3]), "+f"(d[4]), "+f"(d[5]), "+f"(d[6]), "+f"(d[7])
               : "r"(da), "r"(db), "n"(ACC), "n"(TA));
}
__device__ __forceinline__ void wgmma_ss_p(float (&d)[16], uint32_t da, uint32_t db, int acc) {
  asm volatile("{\n.reg .pred p;\n.reg .b64 da, db;\nsetp.ne.b32 p, %18, 0;\nmov.b64 da, {%16, 0x40000040};\nmov.b64 db, {%17, 0x40000040};\n"
               "wgmma.mma_async.sync.aligned.m64n32k16.f32.bf16.bf16 {%0,%1,%2,%3,%4,%5,%6,%7,%8,%9,%10,%11,%12,%13,%14,%15}, da, db, p, 1, 1, 0, 0;\n}"
               : "+f"(d[0]), "+f"(d[1]), "+f"(d[2]), "+f"(d[3]), "+f"(d[4]), "+f"(d[5]), "+f"(d[6]), "+f"(d[7]),
                 "+f"(d[8]), "+f"(d[9]), "+f"(d[10]), "+f"(d[11]), "+f"(d[12]), "+f"(d[13]), "+f"(d[14]), "+f"(d[15])
               : "r"(da), "r"(db), "r"(acc));
}
__device__ __forceinline__ void wgmma_ss_p(float (&d)[8], uint32_t da, uint32_t db, int acc) {
  asm volatile("{\n.reg .pred p;\n.reg .b64 da, db;\nsetp.ne.b32 p, %10, 0;\nmov.b64 da, {%8, 0x40000040};\nmov.b64 db, {%9, 0x40000040};\n"
               "wgmma.mma_async.sync.aligned.m64n16k16.f32.bf16.bf16 {%0,%1,%2,%3,%4,%5,%6,%7}, da, db, p, 1, 1, 0, 0;\n}"
               : "+f"(d[0]), "+f"(d[1]), "+f"(d[2]), "+f"(d[3]), "+f"(d[4]), "+f"(d[5]), "+f"(d[6]), "+f"(d[7])
               : "r"(da), "r"(db), "r"(acc));
}
template <int K> __device__ __forceinline__ void tie(float (&d)[K]) {
#pragma unroll
  for (int i = 0; i < K; i += 8)
    asm volatile("" : "+f"(d[i]), "+f"(d[i + 1]), "+f"(d[i + 2]), "+f"(d[i + 3]), "+f"(d[i + 4]), "+f"(d[i + 5]), "+f"(d[i + 6]), "+f"(d[i + 7]) :: "memory");
}
template <bool C, typename A, typename B> __device__ __forceinline__ auto& pick(A& a, B& b) { if constexpr (C) return a; else return b; }
#define PRAGMA(x) _Pragma(#x)
#define UNROLL(n) PRAGMA(unroll n)
template <int I> struct IC { static constexpr int value = I; };
template <int B, int E, typename F> __device__ __forceinline__ void sfor(F&& f) { if constexpr (B < E) { f(IC<B>{}); sfor<B + 1, E>(f); } }

__device__ __forceinline__ uint2 ldg_u64(const void* p) {
  uint2 v; asm volatile("{\n.reg .b64 a;\nld.relaxed.gpu.global.b64 a, [%2];\nmov.b64 {%0,%1}, a;\n}" : "=r"(v.x), "=r"(v.y) : "l"(p) : "memory"); return v;
}
__device__ __forceinline__ uint4 ldg_2u64(const void* p) {
  uint4 v; asm volatile("{\n.reg .b64 a, b;\nld.relaxed.gpu.global.v2.b64 {a, b}, [%4];\nmov.b64 {%0,%1}, a;\nmov.b64 {%2,%3}, b;\n}" : "=r"(v.x), "=r"(v.y), "=r"(v.z), "=r"(v.w) : "l"(p) : "memory"); return v;
}
__device__ __forceinline__ uint4 ldg_u128(const void* p) {
  uint4 v; asm volatile("{\n.reg .b64 a, b;\n.reg .b128 q;\nld.relaxed.gpu.global.b128 q, [%4];\nmov.b128 {a, b}, q;\nmov.b64 {%0,%1}, a;\nmov.b64 {%2,%3}, b;\n}" : "=r"(v.x), "=r"(v.y), "=r"(v.z), "=r"(v.w) : "l"(p) : "memory"); return v;
}
__device__ __forceinline__ void stg_u64(void* p, uint32_t x, uint32_t y) {
  asm volatile("{\n.reg .b64 a;\nmov.b64 a, {%1,%2};\nst.relaxed.gpu.global.b64 [%0], a;\n}" ::"l"(p), "r"(x), "r"(max(y, 1u)) : "memory");
}
__device__ __forceinline__ uint64_t pair64(uint32_t x, uint32_t y) { uint64_t a; asm("mov.b64 %0, {%1,%2};" : "=l"(a) : "r"(x), "r"(y)); return a; }
__device__ __forceinline__ void stg_b64(void* p, uint64_t a) { asm volatile("st.relaxed.gpu.global.b64 [%0], %1;" ::"l"(p), "l"(a) : "memory"); }
__device__ __forceinline__ void stg4_b128(void* p, uint4 v) {
  asm volatile("{\n.reg .b64 a, b;\n.reg .b128 q;\nmov.b64 a, {%1,%2};\nmov.b64 b, {%3,%4};\nmov.b128 q, {a, b};\nst.relaxed.gpu.global.b128 [%0], q;\n}" ::"l"(p), "r"(v.x), "r"(v.y), "r"(v.z), "r"(v.w) : "memory");
}
__device__ __forceinline__ void stg_u128(void* p, uint4 v) {
  asm volatile("{\n.reg .b64 a, b;\n.reg .b128 q;\nmov.b64 a, {%1,%2};\nmov.b64 b, {%3,%4};\nmov.b128 q, {a, b};\nst.relaxed.gpu.global.b128 [%0], q;\n}" ::"l"(p), "r"(v.x), "r"(v.y), "r"(v.z), "r"(max(v.w, 1u)) : "memory");
}
__device__ __forceinline__ uint32_t hmul2(uint32_t a, uint32_t b) { uint32_t r; asm("mul.rn.bf16x2 %0, %1, %2;" : "=r"(r) : "r"(a), "r"(b)); return r; }
__device__ __forceinline__ uint32_t hadd2(uint32_t a, uint32_t b) { uint32_t r; asm("add.rn.bf16x2 %0, %1, %2;" : "=r"(r) : "r"(a), "r"(b)); return r; }
__device__ __forceinline__ uint32_t hfma2(uint32_t a, uint32_t b, uint32_t c) { uint32_t r; asm("fma.rn.bf16x2 %0, %1, %2, %3;" : "=r"(r) : "r"(a), "r"(b), "r"(c)); return r; }
__device__ __forceinline__ uint32_t movm(uint32_t a) { uint32_t d; asm volatile("movmatrix.sync.aligned.m8n8.trans.b16 %0, %1;" : "=r"(d) : "r"(a)); return d; }
__device__ __forceinline__ uint2 ldg_rlx2(const void* p) { uint2 v; asm volatile("ld.relaxed.gpu.global.v2.u32 {%0,%1}, [%2];" : "=r"(v.x), "=r"(v.y) : "l"(p) : "memory"); return v; }
__device__ __forceinline__ uint4 ldg_in4(const void* p) { uint4 v; asm volatile("ld.global.nc.v4.u32 {%0,%1,%2,%3}, [%4];" : "=r"(v.x), "=r"(v.y), "=r"(v.z), "=r"(v.w) : "l"(p)); return v; }
__device__ __forceinline__ uint32_t ldg_in1(const void* p) { uint32_t v; asm volatile("ld.global.nc.u32 %0, [%1];" : "=r"(v) : "l"(p)); return v; }
__device__ __forceinline__ uint32_t ldg_inh(const void* p) { uint16_t v; asm volatile("ld.global.nc.u16 %0, [%1];" : "=h"(v) : "l"(p)); return v; }

__device__ __forceinline__ void sum4_to_smem(uint2 (&v)[4], const uint32_t* x, const uint32_t* y, uint32_t dst) {
  while (min(min(v[0].y, v[1].y), min(v[2].y, v[3].y)) == 0) {
#pragma unroll
    for (int i = 0; i < 4; i++) v[i] = ldg_u64(((i & 2) ? y : x) + (i & 1) * 512);
  }
  const float c0 = (bf_lo(v[0].x) + bf_lo(v[1].x)) + (bf_lo(v[2].x) + bf_lo(v[3].x));
  const float c1 = (bf_hi(v[0].x) + bf_hi(v[1].x)) + (bf_hi(v[2].x) + bf_hi(v[3].x));
  const float c2 = (bf_lo(v[0].y) + bf_lo(v[1].y)) + (bf_lo(v[2].y) + bf_lo(v[3].y));
  const float c3 = (bf_hi(v[0].y) + bf_hi(v[1].y)) + (bf_hi(v[2].y) + bf_hi(v[3].y));
  sts1(dst, pack_bf16(c0, c1));
  sts1(dst + 128, pack_bf16(c2, c3));
}
__device__ __forceinline__ void load_a_t(uint32_t (&a)[8][4], uint32_t box, int wq, int lane) {
  const int mi = lane >> 3, r = lane & 7;
  const uint32_t base = box + (8 * (mi >> 1) + r) * 128 + (((2 * wq + (mi & 1)) ^ r) << 4);
#pragma unroll
  for (int ks = 0; ks < 8; ks++) ldsm4t(a[ks], base + ks * 2048);
}
__device__ __forceinline__ void mma128(float (&d)[4], const uint32_t (&a)[8][4], uint32_t bs) {
  float e[4][4] = {{0.f, 0.f, 0.f, 0.f}, {0.f, 0.f, 0.f, 0.f}, {0.f, 0.f, 0.f, 0.f}, {0.f, 0.f, 0.f, 0.f}};
  uint32_t b[4][4];
#pragma unroll
  for (int kk = 0; kk < 4; kk++) ldsm4t(b[kk], bs + 32 * kk * 16);
#pragma unroll
  for (int kk = 0; kk < 4; kk++) { mma16816(e[(2 * kk) & 3], a[2 * kk], b[kk][0], b[kk][1]); mma16816(e[(2 * kk + 1) & 3], a[2 * kk + 1], b[kk][2], b[kk][3]); }
#pragma unroll
  for (int i = 0; i < 4; i++) d[i] = (e[0][i] + e[1][i]) + (e[2][i] + e[3][i]);
}
template <int NL> __device__ __forceinline__ void poll_vectors(uint4 (&v)[NL], const uint32_t* p, const uint32_t* q) {
  int it = 0;
  while (true) {
#pragma unroll
    for (int i = 0; i < NL; i++) v[i] = ldg_2u64(i < NL / 2 ? p + i * 128 : q + (i - NL / 2) * 128);
    uint32_t m0 = min(v[0].y, v[0].w), m1 = min(v[1].y, v[1].w);
#pragma unroll
    for (int i = 2; i < NL; i += 2) { m0 = min3(m0, v[i].y, v[i].w); m1 = min3(m1, v[i + 1].y, v[i + 1].w); }
    if (__all_sync(~0u, min(m0, m1) != 0)) break;
    if (++it > SPIN_LIMIT) __trap();
  }
}

__global__ void __cluster_dims__(2, 1, 1) __launch_bounds__(NTHREADS, 1)
fused_decode_kernel(__nv_bfloat16* __restrict__ gout, Scratch* __restrict__ gs, const uint8_t* __restrict__ gwmod,
                    const uint8_t* __restrict__ gx, const uint8_t* __restrict__ gc,
                    const __grid_constant__ Params P) {
  extern __shared__ __align__(1024) uint8_t smem_raw[];
  const uint32_t hi = pin32((uint32_t)__cvta_generic_to_shared(smem_raw) - SB);
  const int tid = threadIdx.x, lane = tid & 31;
  const int w = __shfl_sync(0xffffffffu, tid >> 5, 0);
  const int cta = blockIdx.x;
  const int g = lane >> 2, t = lane & 3;
  const int hI = cta >> 2, jI = cta & 3;
  const int bI = cta >> 4, pI = (cta >> 1) & 7, rI = cta & 1;

  uint32_t epoch0 = 0;
  uint32_t tnext = 0;
  if (tid == 320) epoch0 = ldg_rlx1(&gs->epoch);
  uint4 cw0, cw1, xr0, xr1;
  uint32_t xc[4];
  uint2 sa, ca, qp[4];
  const uint32_t* const modi = gs->MODA + 512 * jI + tid * 2;
  const uint32_t* const qpi = gs->QP + (hI * 4 * 256 + tid) * 2;
  if (w < 8) {
    const uint8_t* wm = gwmod + 16 * cta + (size_t)(64 * w + lane) * 6144;
    const uint32_t dst = hi + OFF_R0 + w * 1024 + (((lane >> 1) & 7) * 8 + 2 * (lane >> 4) + (lane & 1)) * 16;
    asm volatile("cp.async.cg.shared.global" CPA " [%0], [%1], 16;" ::"r"(dst), "l"(wm) : "memory");
    asm volatile("cp.async.cg.shared.global" CPA " [%0], [%1], 16;" ::"r"(dst + 64), "l"(wm + 32 * 6144) : "memory");
    asm volatile("cp.async.commit_group;" ::: "memory");
    cw0 = ldg_in4(gc + g * 1024 + w * 128 + t * 32); cw1 = ldg_in4(gc + g * 1024 + w * 128 + t * 32 + 16);
    xr0 = ldg_in4(gx + w * 1024 + lane * 16); xr1 = ldg_in4(gx + w * 1024 + 512 + lane * 16);
#pragma unroll
    for (int i = 0; i < 4; i++) xc[i] = ldg_inh(gx + w * 1024 + jI * 256 + i * 64 + lane * 2);
    sa = ca = qp[0] = qp[1] = qp[2] = qp[3] = make_uint2(0, 0);
    if (hI == 0) { sa = ldg_rlx2(modi); ca = ldg_rlx2(modi + 2048); }
    if (jI == 0) {
#pragma unroll
      for (int i = 0; i < 4; i++) qp[i] = ldg_u64(qpi + i * 512);
    }
  }
  auto half_of = [&](int c, int k) { return ((lds1(hi + OFF_FM + (c >> 5) * 4) >> (c & 31)) ^ k) & 1; };
  auto inbox = [&](int c, int k, uint32_t bits, int pos, int off) { return gs->IN[0] + (uint32_t)(c * 16384 + k * 2048 + off + (((bits >> pos) & 1) << 10)); };
  auto front_unit = [&](int k, uint64_t pol) {
    const uint32_t bar = hi + BAR(k);
    if (k < 8) tma2d(hi + OFF_R1 + ((k & 4) + 2 * (k & 1) + ((k >> 1) & 1)) * 8192, k < 4 ? &P.wq : &P.wuk, 128 * hI + 64 * (k & 1), 128 * jI + 64 * ((k >> 1) & 1), bar, pol);
    else tma2d_nohint(hi + OFF_R0 + (k - 7) * 8192, &P.wmod, 1024 + 16 * cta, 256 * (k - 8), bar);
  };
  if (tid == 256) {
    if (hi & 0xffffff) __trap();
#pragma unroll
    for (int i = 0; i < WIN_0; i++) mbar_init(hi + BAR(i), 1);
    asm volatile("fence.mbarrier_init.release.cluster;" ::: "memory");
    uint64_t pol; asm volatile("createpolicy.fractional.L2::evict_first.b64 %0, 1.0;" : "=l"(pol));
#pragma unroll
    for (int i = 0; i < WIN_0; i++) front_unit(i, pol);
    tnext = gtime32() + PACE_T0;
    TLW(42);
  } else if (tid == 288) {
#pragma unroll
    for (int i = WIN_0; i < NBARS; i++)
      mbar_init(hi + BAR(i), (i >= BAR_EMPTY && i < BAR_EMPTY + 4) ? 16 : (i >= BAR_P2E && i <= BAR_P7D) ? 8 : 1);
    asm volatile("fence.mbarrier_init.release.cluster;" ::: "memory");
  }
  __syncthreads();
  TL(0);

  if (w == 8) {
    mbar_expect(hi + BAR(0) + 8 * lane, 8192);
    if (lane < BAR_EMPTY - 32) mbar_expect(hi + BAR(32) + 8 * lane, 8192);
    __syncwarp();
    const int h = hI, j = jI;
    if (lane == 0) {
      uint64_t pol; asm volatile("createpolicy.fractional.L2::evict_first.b64 %0, 1.0;" : "=l"(pol));
      auto pace = [&](int dt) { if (PACE_DT > 0) { while ((int)(gtime32() - tnext) < 0) {} tnext += dt; } };
      asm volatile("prefetch.tensormap [%0];" ::"l"(&P.wuk) : "memory");
      asm volatile("prefetch.tensormap [%0];" ::"l"(&P.wmod) : "memory");
      asm volatile("prefetch.tensormap [%0];" ::"l"(&P.ckv) : "memory");
#pragma unroll 1
      for (int k = WIN_0; k < 10; k++) { if (k >= WIN_PRE) mbar_wait(hi + BAR(0) + 8 * (k - WIN_PRE)); pace(PACE_DT); front_unit(k, pol); }
      bool go = false;
      const int row0 = bI * 4096 + (cta & 15) * 64;
#pragma unroll 1
      for (int n = 0; n < 24; n++) {
        if (n == 16) mbar_wait(hi + BAR(BAR_P2E));
        if (n == 23) mbar_wait(hi + BAR(BAR_EMPTY));
        if (!go) go = mbar_test(hi + BAR(BAR_GO));
        mbar_wait(hi + BAR(BAR_FULL) + 8 * (n - (go ? WIN_MID : WIN_PRE)));
        pace(n >= PACE_NM ? PACE_DTM : PACE_DT);
        tma2d(hi + slot(box_slot(n)), &P.ckv, (n & 7) * 64, row0 + (n >> 3) * 1024, hi + BAR(BAR_FULL) + 8 * n, pol);
      }
      asm volatile("prefetch.tensormap [%0];" ::"l"(&P.wuv) : "memory");
      asm volatile("prefetch.tensormap [%0];" ::"l"(&P.wo) : "memory");
      asm volatile("prefetch.tensormap [%0];" ::"l"(&P.w1) : "memory");
      asm volatile("prefetch.tensormap [%0];" ::"l"(&P.w2) : "memory");
      const int row1 = bI * 4096 + (24 + pI) * 64;
      tnext += rI * (PACE_DT / 2) - PACE_DT / 4;
#pragma unroll 1
      for (int n = 24 + rI; n < 40; n += 2) {
        const int c = n - 23;
        const int m = c >= 2 * WIN_END ? n - 2 * WIN_END : 23 - (2 * WIN_END - c) / 2;
        mbar_wait(hi + BAR(BAR_FULL) + 8 * m);
        mbar_wait(hi + BAR(BAR_EMPTY) + (c & ~7));
        pace(PACE_DTE);
        tma2d_both(hi + slot(box_slot(n)), &P.ckv, (n & 7) * 64, row1 + (n >> 3) * 512, hi + BAR(BAR_FULL) + 8 * n, pol);
      }
      mbar_wait(hi + BAR(BAR_EMPTY + 2));
      tnext += PACE_GAP;
#pragma unroll 1
      for (int n = U_WUV; n < (cta < NFF ? NUNITS : U_W1); n++) {
        const int c = n - 39, u = n & 3;
        mbar_wait(hi + BAR(BAR_FULL) + 8 * (c >= WIN_TAIL ? n - WIN_TAIL : 39 - 2 * (WIN_TAIL - c)));
        if (n == U_WO) mbar_wait(hi + BAR(BAR_EMPTY + 3));
        const uint32_t bar = hi + BAR(BAR_FULL) + 8 * n, dst = hi + slot(n < U_WO ? n - 23 : n - 43);
        pace(PACE_DT2);
        if (n < U_W1) tma2d(dst, n < U_WO ? &P.wuv : &P.wo, 128 * (n < U_WO ? h : j) + 64 * (u >> 1), 128 * (n < U_WO ? j : h) + 64 * (u & 1), bar, pol);
        else if (n < U_W2) tma2d_nohint(dst, &P.w1, FCH * cta, 256 * (u & 1), bar);
        else tma3d(dst, &P.w2, 0, FCH * cta, 4 * (u & 1), bar, pol);
      }
    }
    return;
  }

  if (w == 11) {
    const uint4 z = make_uint4(0, 0, 0, 0);
    float d[4] = {0.f, 0.f, 0.f, 0.f};
    const uint32_t a[4] = {0u, 0u, 0u, 0u};
    auto pace = [&] {
      mma16816(d, a, 0u, 0u);
    };
    auto pace_until = [&](int bar) { do { pace(); __nanosleep(PACE_NS); } while (!mbar_test(hi + BAR(bar))); };
    pace();
    uint32_t f = 0, f2 = 0;
    {
      uint32_t* const p = ((lane & 2) ? gs->X3B + 4 * 2048 + cta * 8 : gs->IN[cta] + 4 * 2048 + 960) + ((lane & 1) << 10);
      if (lane < 8) stg4(p + (lane & 4), z);
      __syncwarp();
      uint32_t best = ~0u;
#pragma unroll 1
      for (int i = 0; i < 4 * NPROBE; i++) {
        uint32_t v = 0;
        const uint32_t c0 = clk32();
        if (lane == (i & 3)) asm volatile("atom.relaxed.gpu.global.exch.b32 %0, [%1], %2;" : "=r"(v) : "l"(p), "r"(i) : "memory");
        v = __shfl_sync(~0u, v, i & 3);
        const uint32_t dt = clk32() - c0 + (v >> 31);
        if (lane == (i & 3)) best = min(best, dt);
        pace();
      }
      const uint32_t m = __ballot_sync(~0u, best < __shfl_xor_sync(~0u, best, 1));
      f = (m >> 1) & 1; f2 = (m >> 3) & 1;
    }
    mbar_wait(hi + BAR(BAR_EPOCH));
    const uint32_t epoch = lds1(hi + OFF_EPOCH);
    const int par = epoch & 1;
    if (lane == 0) stg1(gs->FL[par] + cta, 1 + f);
    TLW(51);
    if (CLR_AT == 2) pace_until(BAR_GO);
    if (CLR_AT == 3) pace_until(BAR_P2E);
    backoff(CLR_D0);
#pragma unroll 1
    for (int i = 0; i < 16; i++) {
      const uint32_t c0 = clk32();
      uint32_t* p = gs->IN[cta] + (i >> 1) * 2048 + (((f ^ (i >> 1)) & 1) << 10) + (i & 1) * 512 + lane * 4;
#pragma unroll
      for (int q = 0; q < 4; q++) stg4(p + q * 128, z);
      if (i == 0 && lane < 16) stg4(gs->X3B + cta * 64 + lane * 4, z);
      if (CLR_AT != 2 && !mbar_test(hi + BAR(BAR_GO))) pace();
      wait_until(c0, CLR_CLK);
    }
    TLW(35);
    asm volatile("fence.acq_rel.gpu;" ::: "memory");
    __syncwarp();
    if (lane == 0) asm volatile("red.relaxed.gpu.global.add.u32 [%0], 1;" ::"l"(&gs->cnt) : "memory");
    TLW(36);
    mbar_wait(hi + BAR(BAR_GO));
    {
      uint32_t u[4];
      do {
#pragma unroll
        for (int i = 0; i < 4; i++) u[i] = ldg_rlx1(gs->FL[par] + 32 * i + lane);
      } while (!__all_sync(~0u, min(min(u[0], u[1]), min(u[2], u[3])) != 0));
      const uint4 m = make_uint4(__ballot_sync(~0u, u[0] == 2), __ballot_sync(~0u, u[1] == 2), __ballot_sync(~0u, u[2] == 2), __ballot_sync(~0u, u[3] == 2));
      if (lane == 0) sts4(hi + OFF_FM, m);
      __syncwarp();
      const uint2 m2 = lds2(hi + OFF_FM + 8 * rI);
      const uint32_t mh = (lds1(hi + OFF_FM + (hI >> 3) * 4) >> (4 * (hI & 7))) & 15;
#pragma unroll 1
      for (int v = 0; v < 8; v++) {
        const int sh = 8 * t + 2 * (v >> 2) + (bI >> 2);
        uint32_t fb = (((m2.x >> sh) & 0x11) | (((m2.y >> sh) & 0x11) << 1)) ^ ((bI & 1) ? 0x33 : 0);
        fb |= mh << 8;
        fb |= half_of(4 * (8 * jI + v) + (g >> 1), 0) << 12;
        fb |= half_of((16 * rI + 4 * (v & 3) + (lane >> 3)) * 4 + (lane & 2), 0) << 13;
        fb |= ((f2 ^ (v >> 2)) & 1) << 14;
        fb |= (((lds1(hi + OFF_FM + (v >> 1) * 4) >> (16 * (v & 1) + (g >> 1))) & 0x1111) ^ (cta >= 56 ? 0x1111 : 0)) << 16;
        sts1(hi + OFF_FB + (v * 32 + lane) * 4, fb);
      }
      __syncwarp();
      if (lane == 0) mbar_arrive(hi + BAR(BAR_FM));
    }
    if (lane == 0) stg1(gs->FL[par ^ 1] + cta, 0u);
#pragma unroll
    for (int i = 0; i < 4; i++) stg4(gs->QP + cta * 512 + (i * 32 + lane) * 4, z);
#pragma unroll
    for (int i = 0; i < 4; i++) stg4(gs->QX[par ^ 1] + cta * 512 + (i * 32 + lane) * 4, z);
    if (lane < 8) stg4(gs->MODA + cta * 32 + lane * 4, z);
    if (lane < 16) stg4(gs->MODB[par ^ 1] + cta * 64 + lane * 4, z);
    mbar_wait(hi + BAR(BAR_FULL + CNT_AT));
    while ((int)(ldg_rlx1(&gs->cnt) - (epoch + 1) * NCTA) < 0) __nanosleep(100);
    if (lane == 0) mbar_arrive(hi + BAR(BAR_CLR));
    TLW(54);
    mbar_wait(hi + BAR(BAR_FULL + U_WUV + 1));
    pace_until(BAR_P5D);
    if (cta < NFF) pace_until(BAR_P7D);
    if (d[0] != 0.f) __trap();
    return;
  }
  if (w == 10) {
    const int m0 = 16 * hI + 2 * jI;
    const int bo = lane & 7;
    const uint32_t epoch = __shfl_sync(~0u, epoch0, 0);
    if (lane == 0) { sts1(hi + OFF_EPOCH, epoch); mbar_arrive(hi + BAR(BAR_EPOCH)); }
    const int par = epoch & 1;
    const uint32_t* MOD = gs->MODB[par];
    const uint32_t xw0 = ldg_in1(gx + bo * 1024 + m0 * 2), xw1 = ldg_in1(gx + bo * 1024 + m0 * 2 + 16);
    PROBE_UNITS(-10, 16);
    mbar_wait_b(hi + BAR(BAR_GO));
    const int mf = m0 + ((g >> 1) & 1) + 8 * (t >> 1), bf = 2 * (g & 1) + (t & 1);
    float ga[4];
    uint32_t gb2;
    {
      uint32_t u[4];
      int it = 0;
      while (true) {
#pragma unroll
        for (int i = 0; i < 4; i++) u[i] = ldg_rlx1(MOD + (m0 + (i & 1) + 8 * (i >> 1)) * 4 + (bo >> 1));
        gb2 = ldg_rlx1(MOD + (1536 + mf) * 4 + bf);
        if (min3(min3(u[0], u[1], u[2]), u[3], gb2) != 0) break;
        if (++it > SPIN_LIMIT) __trap();
      }
#pragma unroll
      for (int i = 0; i < 4; i++) ga[i] = (bo & 1) ? bf_hi(u[i]) : bf_lo(u[i]);
    }
    uint32_t x2a, x2b;
    mbar_wait_b(hi + BAR(BAR_FM));
    const uint32_t fo_ = half_of(cta, 0);
    {
      const uint32_t* const pi = pin(inbox(cta, 6, fo_, 0, (4 * (g >> 1) + t) * 8 + (g & 1) * 4));
      uint32_t* const po = pin(gs->X3B + (g >> 2) * 4096 + (cta >> 6) * 2048 + ((g >> 1) & 1) * 1024 + (cta & 63) * 16 + bo * 2);
      const uint32_t one = 0x3f80u << (8 * (g & 2)), s0 = g < 4 ? one : 0u, s1 = g < 4 ? 0u : one;
      const uint32_t e0 = pin32((g & 1) ? 0u : s0), e1 = pin32((g & 1) ? 0u : s1), o0 = pin32((g & 1) ? s0 : 0u), o1 = pin32((g & 1) ? s1 : 0u);
      PROBE_UNITS(16, 48);
      mbar_wait_b(hi + BAR(BAR_P5D));
      backoff(D_X3A);
      uint4 v[4];
      poll_vectors<4>(v, pi, pi + 256);
      TLW(37);
      float d0[4] = {0.f, 0.f, 0.f, 0.f}, d1[4] = {0.f, 0.f, 0.f, 0.f};
      mma_v(d0, v[0], e0, e1); mma_v(d1, v[2], o0, o1);
      mma_v(d0, v[1], e0, e1); mma_v(d1, v[3], o0, o1);
      float s[4] = {d0[0], d1[1], d0[2], d1[3]};
#pragma unroll
      for (int i = 0; i < 4; i++) s[i] += __shfl_xor_sync(~0u, s[i], 8);
#pragma unroll
      for (int i = 0; i < 4; i++) s[i] += __shfl_xor_sync(~0u, s[i], 16);
      x2a = pack_bf16(bf_lo(xw0) + ga[0] * s[0], bf_hi(xw0) + ga[1] * s[1]);
      x2b = pack_bf16(bf_lo(xw1) + ga[2] * s[2], bf_hi(xw1) + ga[3] * s[3]);
      stg_u64(po, x2a, x2b);
    }
    TLW(20);
    {
      const uint32_t a0 = __shfl_sync(~0u, x2a, 2 * bf), a1 = __shfl_sync(~0u, x2a, 2 * bf + 1);
      const uint32_t b0 = __shfl_sync(~0u, x2b, 2 * bf), b1 = __shfl_sync(~0u, x2b, 2 * bf + 1);
      const uint32_t y0 = (t & 2) ? b0 : a0, y1 = (t & 2) ? b1 : a1;
      const float r0 = (g & 2) ? bf_hi(y0) : bf_lo(y0), r1 = (g & 2) ? bf_hi(y1) : bf_lo(y1);
      const uint32_t* const pi = pin(inbox(cta, 4, fo_, 0, (4 * (g >> 2) + t) * 16 + (g & 3) * 4));
      const uint32_t* const pj = pin(inbox(cta, 5, ~fo_, 0, (4 * (g >> 2) + t) * 16 + (g & 3) * 4));
      __nv_bfloat16* const fo = pin(gout + (2 * bf) * 512 + mf);
      const uint32_t one = (g & 1) ? 0x3f800000u : 0x00003f80u;
      const uint32_t s0 = pin32((g & 2) ? 0u : one), s1 = pin32((g & 2) ? one : 0u);
      if (cta < NFF) { mbar_wait_b(hi + BAR(BAR_P7D)); backoff(D_FIN); } else __nanosleep(1000);
      uint4 v[NFF / 8];
      poll_vectors<NFF / 8>(v, pi, pj);
      TLW(38);
      float d[4][4] = {{0.f, 0.f, 0.f, 0.f}, {0.f, 0.f, 0.f, 0.f}, {0.f, 0.f, 0.f, 0.f}, {0.f, 0.f, 0.f, 0.f}};
#pragma unroll
      for (int i = 0; i < NFF / 8; i++) mma_v(d[i & 3], v[i], s0, s1);
      const bool up = t & 2;
      float v0 = up ? (d[0][2] + d[1][2]) + (d[2][2] + d[3][2]) : (d[0][0] + d[1][0]) + (d[2][0] + d[3][0]);
      float v1 = up ? (d[0][3] + d[1][3]) + (d[2][3] + d[3][3]) : (d[0][1] + d[1][1]) + (d[2][1] + d[3][1]);
      v0 += __shfl_xor_sync(~0u, v0, 16);
      v1 += __shfl_xor_sync(~0u, v1, 16);
      if (g < 4) {
        fo[0] = __float2bfloat16(r0 + bf_lo(gb2) * v0);
        fo[512] = __float2bfloat16(r1 + bf_hi(gb2) * v1);
      }
    }
    TLW(23);
    if (cta == 0 && lane == 0) stg1(&gs->epoch, epoch + 1);
    return;
  }

  if (w == 9) {
    mbar_wait(hi + BAR(BAR_EPOCH));
    const int par = lds1(hi + OFF_EPOCH) & 1;
    {
      const uint32_t* px = gs->QX[par] + bI * 8192 + lane * 256 + 63;
      uint32_t x0 = ldg_rlx1(px), x1 = ldg_rlx1(px + 64), x2 = ldg_rlx1(px + 128), x3 = ldg_rlx1(px + 192);
      mbar_wait(hi + BAR(BAR_P2E));
      backoff(D_QX);
      uint32_t donemask = 0;
      while (true) {
        const uint32_t okm = __ballot_sync(~0u, x0 != 0 && x1 != 0 && x2 != 0 && x3 != 0);
        const uint32_t full = okm & (okm >> 1) & (okm >> 2) & (okm >> 3) & 0x11111111u;
        if (((full & ~donemask) >> lane) & 1) mbar_arrive(hi + BAR(BAR_QXG) + 8 * (lane >> 2));
        donemask |= full;
        if (donemask == 0x11111111u) break;
        if (x0 == 0) x0 = ldg_rlx1(px);
        if (x1 == 0) x1 = ldg_rlx1(px + 64);
        if (x2 == 0) x2 = ldg_rlx1(px + 128);
        if (x3 == 0) x3 = ldg_rlx1(px + 192);
      }
    }
    if (lane == 0) {
      mbar_expect(hi + BAR(BAR_XE), 16384 + 4096);
      mbar_wait(hi + BAR(BAR_EMPTY + 3));
      mbar_wait(hi + BAR(BAR_FULL + XE_AT));
      TLW(33);
      bulk_load(hi + OFF_XE, gs->XE + cta * 4096, 16384, hi + BAR(BAR_XE));
      bulk_load(hi + OFF_MLS, gs->MLE + hI * 1024, 4096, hi + BAR(BAR_XE));
    }
    return;
  }

  const int wg = w >> 2, wq = w & 3;
  uint32_t cf[8] = {cw0.x, cw0.y, cw0.z, cw0.w, cw1.x, cw1.y, cw1.z, cw1.w};
#pragma unroll
  for (int i = 0; i < 8; i++) {
    const float a = bf_lo(cf[i]), b = bf_hi(cf[i]);
    cf[i] = pack_bf16(__fdividef(a, 1.f + __expf(-a)), __fdividef(b, 1.f + __expf(-b)));
  }
  TL(1);
  {
    uint32_t* const mo = pin(gs->MODA + cta * 32 + lane);
    asm volatile("cp.async.wait_group 0;" ::: "memory");
    __syncwarp();
    TL(2);
    float d0[4] = {0.f, 0.f, 0.f, 0.f}, d1[4] = {0.f, 0.f, 0.f, 0.f};
    uint32_t r0[4], r1[4];
    ldsm4t(r0, hi + OFF_R0 + w * 1024 + lane * 16); ldsm4t(r1, hi + OFF_R0 + w * 1024 + 512 + lane * 16);
    mma_v(d0, make_uint4(r0[0], 0u, r0[1], 0u), cf[0], cf[1]); mma_v(d1, make_uint4(r0[2], 0u, r0[3], 0u), cf[2], cf[3]);
    mma_v(d0, make_uint4(r1[0], 0u, r1[1], 0u), cf[4], cf[5]); mma_v(d1, make_uint4(r1[2], 0u, r1[3], 0u), cf[6], cf[7]);
    sts2f(hi + OFF_P0S + tid * 8, d0[0] + d1[0], d0[1] + d1[1]);
    cbar();
    if (w == 0) {
      float2 v[8];
#pragma unroll
      for (int i = 0; i < 8; i++) v[i] = ldsf2(hi + OFF_P0S + (i * 32 + lane) * 8);
      stg1(mo, nz(pack_bf16(((v[0].x + v[1].x) + (v[2].x + v[3].x)) + ((v[4].x + v[5].x) + (v[6].x + v[7].x)),
                            ((v[0].y + v[1].y) + (v[2].y + v[3].y)) + ((v[4].y + v[5].y) + (v[6].y + v[7].y)))));
    }
  }
  const uint32_t ck0 = clk32();
  TL(3);
  {
    float v[16];
    const uint32_t u[8] = {xr0.x, xr0.y, xr0.z, xr0.w, xr1.x, xr1.y, xr1.z, xr1.w};
#pragma unroll
    for (int i = 0; i < 8; i++) { v[2 * i] = bf_lo(u[i]); v[2 * i + 1] = bf_hi(u[i]); }
    float s = (((v[0] + v[1]) + (v[2] + v[3])) + ((v[4] + v[5]) + (v[6] + v[7]))) + (((v[8] + v[9]) + (v[10] + v[11])) + ((v[12] + v[13]) + (v[14] + v[15])));
#pragma unroll
    for (int o = 16; o; o >>= 1) s += __shfl_xor_sync(~0u, s, o);
    const float mu = s * (1.f / 512.f);
    float q0 = 0.f, q1 = 0.f;
#pragma unroll
    for (int i = 0; i < 8; i++) { const float a = v[2 * i] - mu, b = v[2 * i + 1] - mu; q0 += a * a; q1 += b * b; }
    float q = q0 + q1;
#pragma unroll
    for (int o = 16; o; o >>= 1) q += __shfl_xor_sync(~0u, q, o);
    const float rs = rsqrtf(q * (1.f / 512.f) + 1e-5f);
#pragma unroll
    for (int i = 0; i < 4; i++)
      asm volatile("st.shared.u16 [%0], %1;" ::"r"(hi + OFF_BS + (32 * i + lane) * 16 + w * 2), "h"(__bfloat16_as_ushort(__float2bfloat16((bf_lo(xc[i]) - mu) * rs))) : "memory");
  }
  {
    cbar();
    const uint2 xn = lds2(hi + OFF_BS + tid * 8);
    uint32_t* const qpo = pin(gs->QP + (cta * 256 + tid) * 2);
    uint32_t a[8][4];
    const bool wq_ok = mbar_test(hi + BAR(BAR_FULL + U_WQ) + 8 * wg) && mbar_test(hi + BAR(BAR_FULL + U_WQ + 2) + 8 * wg);
    if (wq_ok) load_a_t(a, hi + OFF_R1 + wg * 16384, wq, lane);
    wait_until(ck0, D_MOD);
    while (min(min(sa.x, sa.y), min(ca.x, ca.y)) == 0) { sa = ldg_rlx2(modi); ca = ldg_rlx2(modi + 2048); }
    TL(41);
    sts2(hi + OFF_BS + tid * 8, hfma2(xn.x, hadd2(ca.x, ONE2), sa.x), hfma2(xn.y, hadd2(ca.y, ONE2), sa.y));
    __syncwarp();
    if (!wq_ok) {
      mbar_wait(hi + BAR(BAR_FULL + U_WQ) + 8 * wg); mbar_wait(hi + BAR(BAR_FULL + U_WQ + 2) + 8 * wg);
      load_a_t(a, hi + OFF_R1 + wg * 16384, wq, lane);
    }
    cbar();
    float d[4];
    mma128(d, a, hi + OFF_BS + lane * 16);
    stg_u64(qpo, pack_bf16(d[0], d[1]), pack_bf16(d[2], d[3]));
  }
  const uint32_t ckq = clk32();
  TL(6);
  mbar_wait(hi + BAR(BAR_EPOCH));
  const int par = lds1(hi + OFF_EPOCH) & 1;
  uint32_t* const QX = gs->QX[par];
  {
    uint32_t a[8][4];
    {
      const int mi = lane >> 3, r = lane & 7;
      const int row = 16 * w + 8 * (mi & 1) + r;
      mbar_wait(hi + BAR(BAR_FULL + U_WUK) + 16 * wg); mbar_wait(hi + BAR(BAR_FULL + U_WUK + 1) + 16 * wg);
#pragma unroll
      for (int ks = 0; ks < 8; ks++) {
        const int chunk = 2 * ks + (mi >> 1);
        ldsm4(a[ks], hi + OFF_R2 + (ks >> 2) * 16384 + row * 128 + (((chunk & 7) ^ r) << 4));
      }
    }
    TL(8);
    uint32_t* const qxo = pin(QX + ((lane >> 1) * 32 + hI) * 256 + (128 * jI + 16 * w + 8 * (lane & 1)) / 2);
    wait_until(ckq, D_QP);
    sum4_to_smem(qp, qpi, qpi + 1024, hi + OFF_BS2 + (16 * w + g) * 16 + t * 4);
    TL(7);
    cbar();
    float d[4];
    mma128(d, a, hi + OFF_BS2 + lane * 16);
    const float sc = 0.08838834764831845f * 1.4426950408889634f;
    const uint32_t stg = hi + OFF_P0S + 4096 + w * 256;
    stsm2t(stg + (lane & 7) * 32 + ((lane >> 3) & 1) * 16, pack_bf16(d[0] * sc, d[1] * sc), pack_bf16(d[2] * sc, d[3] * sc));
    __syncwarp();
    if (lane < 16) stg_u128(qxo, lds4(stg + lane * 16));
    if (lane == 0) mbar_arrive(hi + BAR(BAR_P2E));
  }
  TL(9);
  {
    const int mi = lane >> 3, r = lane & 7;
    const uint32_t abase = hi + OFF_R0 + 8192 + (64 * w + 16 * (r >> 1) + 2 * (mi >> 1) + (r & 1)) * 32 + (mi & 1) * 16;
    mbar_wait(hi + BAR(BAR_FULL + U_WMOD) + 8 * wg);
    float d0[4] = {0.f, 0.f, 0.f, 0.f}, d1[4] = {0.f, 0.f, 0.f, 0.f};
    uint32_t a[4][4];
#pragma unroll
    for (int ks = 0; ks < 4; ks++) ldsm4t(a[ks], abase + ks * 128);
#pragma unroll
    for (int ks = 0; ks < 4; ks++) mma16816((ks & 1) ? d1 : d0, a[ks], cf[2 * ks], cf[2 * ks + 1]);
    sts4f(hi + OFF_P0S + tid * 16, d0[0] + d1[0], d0[1] + d1[1], d0[2] + d1[2], d0[3] + d1[3]);
    cbar();
    if (w < 2) {
      float2 v[8];
#pragma unroll
      for (int i = 0; i < 8; i++) v[i] = ldsf2(hi + OFF_P0S + (i * 32 + lane) * 16 + w * 8);
      stg1(gs->MODB[par] + cta * 64 + tid, nz(pack_bf16(((v[0].x + v[1].x) + (v[2].x + v[3].x)) + ((v[4].x + v[5].x) + (v[6].x + v[7].x)),
                                                        ((v[0].y + v[1].y) + (v[2].y + v[3].y)) + ((v[4].y + v[5].y) + (v[6].y + v[7].y)))));
    }
  }
  TL(31);
  uint32_t bc[8], bs[8], fb = 0;
  const uint32_t* const mbi = gs->MODB[par] + (512 + 64 * w) * 4 + lane;
  {
    const uint32_t* qx = pin(QX + bI * 8192 + w * 1024 + lane * 4);
    mbar_wait(hi + BAR(BAR_QXG) + 8 * w);
    TL(4);
    uint4 v[8];
#pragma unroll
    for (int i = 0; i < 8; i++) v[i] = ldg_u128(qx + i * 128);
#pragma unroll
    for (int i = 0; i < 8; i++) { bs[i] = ldg_rlx1(mbi + i * 32); bc[i] = ldg_rlx1(mbi + 2048 + i * 32); }
    cbar();
    while (true) {
      bool all = true;
#pragma unroll
      for (int i = 0; i < 8; i++) all = all && v[i].w != 0;
      if (all) break;
#pragma unroll
      for (int i = 0; i < 8; i++) if (v[i].w == 0) v[i] = ldg_u128(qx + i * 128);
    }
    TL(5);
#pragma unroll
    for (int i = 0; i < 8; i++) {
      const int hh = (4 * w + (i >> 1)) ^ (16 * rI), ch = 32 * (i & 1) + lane;
      sts4(hi + OFF_R0 + (ch >> 3) * 4096 + hh * 128 + (((ch & 7) ^ (hh & 7)) << 4), v[i]);
    }
    asm volatile("fence.proxy.async.shared::cta;" ::: "memory");
    cbar();
    if (tid == 0) mbar_arrive(hi + BAR(BAR_GO));
  }
  TL(10);

  uint32_t ck1;
  const uint32_t *px, *pm;
  {
    float O32[4][16], O16[4][8];
    uint32_t ebar;
    asm("mapa.shared::cluster.u32 %0, %1, %2;" : "=r"(ebar) : "r"(hi + BAR(BAR_EMPTY)), "r"(rI ^ (lane & 1)));
#pragma unroll
    for (int i = 0; i < 16; i++) O32[0][i] = O32[1][i] = O32[2][i] = O32[3][i] = 0.f;
#pragma unroll
    for (int i = 0; i < 4; i++) tie(O32[i]);
    auto pv2 = [&](int T, int WG, auto& O, int mb, int k0, int k1) {
      const int n = 8 * T + 4 * WG + mb;
      const uint32_t da = dlo(SB) + (sizeof(O[0]) == 64 ? n : n - 23) * 512, db = (WG && mb && T == 2) ? dlo(SB) : da + 512, dp = dlo(OFF_PT) + (T & 1) * 256;
#pragma unroll
      for (int ks = k0; ks < k1; ks++) { wgmma_ss<1, 1>(O[mb], da + ks * 128, dp + ks * 2); wgmma_ss<1, 1>(O[mb + 1], db + ks * 128, dp + ks * 2); }
      wg_commit();
    };
    auto pv = [&](int T, int WG, auto& O) { wg_fence(); pv2(T, WG, O, 0, 0, 4); pv2(T, WG, O, 2, 0, 4); };
    auto release = [&](int T, auto& O) {
      wg_wait<0>();
#pragma unroll
      for (int i = 0; i < 4; i++) tie(O[i]);
      if (lane < 2) mbar_arrive_cluster(ebar + 8 * T);
      TL(T < 3 ? 24 + T : 32);
    };
    auto rescale = [&](auto& O) {
#pragma unroll
      for (int jn = 0; jn < (int)(sizeof(O[0]) / 16); jn++) {
        const float2 a = ldsf2(hi + OFF_ALPHA + (8 * jn + 2 * t) * 4);
#pragma unroll
        for (int mb = 0; mb < 4; mb++) { O[mb][4 * jn] *= a.x; O[mb][4 * jn + 1] *= a.y; O[mb][4 * jn + 2] *= a.x; O[mb][4 * jn + 3] *= a.y; }
      }
    };
    uint64_t oe[8];
    uint32_t* const x1e = hold(gs->XE + (((16 * (1 - rI) + 2 * t) * 4 + 2 * wg) * 64 + (cta >> 1)) * 64 + (wq * 8 + g) * 2);
    auto split_o = [&] {
#pragma unroll
      for (int i = 0; i < 8; i++) {
        const int jj = i >> 2, r = 8 + 4 * ((i >> 1) & 1) + (i & 1);
        oe[i] = pair64(pack_bf16(O32[2 * jj][r], O32[2 * jj][r + 2]), (pack_bf16(O32[2 * jj + 1][r], O32[2 * jj + 1][r + 2]) | 1u) ^ par);
      }
#pragma unroll
      for (int i = 0; i < 32; i++) asm volatile("mov.b32 %0, %1;" : "=f"(O16[i >> 3][i & 7]) : "f"(O32[i >> 3][i & 7]));
    };
    auto put_early = [&](int i) { stg_b64(x1e + ((8 * ((i >> 1) & 1) + (i & 1)) * 4 + (i >> 2)) * 4096, oe[i]); };
    uint32_t* x1l[4];
    auto late_addr = [&] {
      mbar_wait(hi + BAR(BAR_FM));
      fb = lds1(hi + OFF_FB + tid * 4);
#pragma unroll
      for (int i = 0; i < 4; i++)
        x1l[i] = hold(inbox((16 * rI + 2 * t) * 4 + 2 * wg + (bI >> 2), bI & 3, fb, 4 * (i & 1) + (i >> 1), pI * 128 + (wq * 8 + g) * 2));
      px = hold(inbox((cta & ~1) + wg, wq, (fb >> (8 + (jI & 2) + wg)) ^ wq, 0, t * 128 + rI * 64 + 4 * g));
      pm = hold(inbox(cta & ~1, 6, fb, 8 + (jI & 2), 512 + (w * 8 + t) * 8));
    };
    auto put_late = [&](int jj) {
#pragma unroll
      for (int i = 0; i < 4; i++) {
        const int jn = i >> 1, e = i & 1, r = 4 * jn + e;
        stg_u64(x1l[i] + (8 * jn + e) * 4 * 16384 + jj * 64, pack_bf16(O16[2 * jj][r], O16[2 * jj][r + 2]), pack_bf16(O16[2 * jj + 1][r], O16[2 * jj + 1][r + 2]));
      }
    };
    auto last_products = [&](int WG, auto&& between) {
      wg_fence();
      pv2(4, WG, O16, 0, 0, 4);
      ck1 = clk32();
      pv2(4, WG, O16, 2, 0, PV_SPLIT);
      between();
      wg_wait<1>();
      tie(O16[0]); tie(O16[1]);
      TL(12);
      put_late(0);
      __syncwarp();
      if (PV_SPLIT < 4) { wg_fence(); pv2(4, WG, O16, 2, PV_SPLIT, 4); }
      wg_wait<0>();
      tie(O16[2]); tie(O16[3]);
      TL(50);
      put_late(1);
    };

    if (wg == 0) {
      float S32[16], S16[8];
      float m_run = -INFINITY;
      float mh[8];
#pragma unroll
      for (int i = 0; i < 16; i++) S32[i] = S16[i & 7] = mh[i & 7] = 0.f;
      const uint32_t ptl = hold32(hi + OFF_PT + (8 * (lane >> 4) + (lane & 7)) * 128 + (((2 * wq + ((lane >> 3) & 1)) ^ (lane & 7)) << 4));
      auto landed = [&](int T) { return __ballot_sync(~0u, mbar_test(hi + BAR(BAR_FULL + 8 * T) + 8 * (lane & 7))); };
      auto softmax = [&](int T, auto& O, auto& S) {
        constexpr int NJ = sizeof(S) / 16;
        wg_wait<0>();
        tie(S);
        if (NJ == 2) TL(T == 4 ? 11 : 52);
        bool over = T == 0;
#pragma unroll 1
        do {
          if (over) {
            float mx[2 * NJ];
#pragma unroll
            for (int jn = 0; jn < NJ; jn++) { mx[2 * jn] = fmaxf(S[4 * jn], S[4 * jn + 2]); mx[2 * jn + 1] = fmaxf(S[4 * jn + 1], S[4 * jn + 3]); }
            float a4[4], a2[2], a1;
            if constexpr (NJ == 4) {
              const bool up = lane & 16;
#pragma unroll
              for (int i = 0; i < 4; i++) { const float send = up ? mx[i] : mx[4 + i]; const float keep = up ? mx[4 + i] : mx[i]; a4[i] = fmaxf(keep, __shfl_xor_sync(~0u, send, 16)); }
            } else {
#pragma unroll
              for (int i = 0; i < 4; i++) { a4[i] = fmaxf(mx[i], __shfl_xor_sync(~0u, mx[i], 16)); if (lane & 16) a4[i] = -INFINITY; }
            }
            {
              const bool up = lane & 8;
#pragma unroll
              for (int i = 0; i < 2; i++) { const float send = up ? a4[i] : a4[2 + i]; const float keep = up ? a4[2 + i] : a4[i]; a2[i] = fmaxf(keep, __shfl_xor_sync(~0u, send, 8)); }
            }
            {
              const bool up = lane & 4;
              const float send = up ? a2[0] : a2[1]; const float keep = up ? a2[1] : a2[0];
              a1 = fmaxf(keep, __shfl_xor_sync(~0u, send, 4));
            }
            stsf(hi + OFF_RED + (wq * 32 + 8 * (g >> 1) + 2 * t + (g & 1)) * 4, a1);
            wg0bar();
            const float mt = fmaxf(fmaxf(ldsf(hi + OFF_RED + lane * 4), ldsf(hi + OFF_RED + 128 + lane * 4)),
                                   fmaxf(ldsf(hi + OFF_RED + 256 + lane * 4), ldsf(hi + OFF_RED + 384 + lane * 4)));
            const float m_new = fmaxf(m_run, ceilf(mt));
            if (wq == 0) { stsf(hi + OFF_MREF + lane * 4, m_new); stsf(hi + OFF_ALPHA + lane * 4, ex2(m_run - m_new)); }
            m_run = m_new;
#pragma unroll
            for (int i = 0; i < 2 * NJ; i++) mh[i] = __shfl_sync(~0u, m_new, 8 * (i >> 1) + 2 * t + (i & 1));
            if (T > 0) { wg0bar(); rescale(O); }
          }
          uint32_t pk[2 * NJ];
          float x[4 * NJ];
#pragma unroll
          for (int i = 0; i < 4 * NJ; i++) x[i] = S[i] - mh[2 * (i >> 2) + (i & 1)];
#pragma unroll
          for (int i = 0; i < 2 * NJ; i++) pk[i] = pack_bf16(ex2(x[2 * i]), ex2(x[2 * i + 1]));
#pragma unroll
          for (int hf = 0; hf < NJ / 2; hf++) stsm4t(ptl + (T & 1) * 4096 + hf * 2048, pk[4 * hf], pk[4 * hf + 1], pk[4 * hf + 2], pk[4 * hf + 3]);
          asm volatile("fence.proxy.async.shared::cta;" ::: "memory");
          if constexpr (NJ == 4) {
#pragma unroll
            for (int i = 0; i < 8; i++) x[i] = fmaxf(x[i], x[i + 8]);
          }
          over = cbar_or(fmaxf(fmaxf(fmaxf(x[0], x[1]), fmaxf(x[2], x[3])), fmaxf(fmaxf(x[4], x[5]), fmaxf(x[6], x[7]))) > 64.f);
        } while (__builtin_expect(over, 0));
        if (NJ == 2) TL(T == 4 ? 34 : 53);
      };
      uint32_t have = 0;
#pragma unroll 1
      for (int T = 0; T < 3; T++) {
        UNROLL(QK_UNROLL)
        for (int jj = 0; jj < 8; jj++) {
          const uint32_t da = dlo(SB) + box_slot(8 * T + jj) * 512, db = dlo(OFF_R0) + jj * 256;
          mbar_wait(hi + BAR(BAR_FULL) + 64 * T + 8 * jj);
          wg_fence();
          wgmma_ss_p(S32, da, db, jj);
#pragma unroll
          for (int ks = 1; ks < 4; ks++) wgmma_ss<0, 1>(S32, da + ks * 2, db + ks * 2);
          wg_commit();
        }
        softmax(T, O32, S32);
        pv(T, 0, O32);
        have = landed(3);
        release(T, O32);
      }
      split_o();
#pragma unroll
      for (int i = 0; i < 4; i++) x1l[i] = nullptr;
      px = pm = nullptr;
      TL(27);
#pragma unroll 1
      for (int T = 3;; T++) {
        sfor<0, 8>([&](auto jc) {
          constexpr int jj = decltype(jc)::value;
          const uint32_t da = dlo(SB) + (8 * T + jj - 23) * 512, db = dlo(OFF_R0) + jj * 256;
          if (!((have >> jj) & 1)) mbar_wait(hi + BAR(BAR_FULL) + 64 * T + 8 * jj);
          if (QK_FENCE || jj == 0) wg_fence();
          wgmma_ss<0, jj != 0>(S16, da, db);
#pragma unroll
          for (int ks = 1; ks < 4; ks++) wgmma_ss<0, 1>(S16, da + ks * 2, db + ks * 2);
          if (QK_FENCE || jj == 7) wg_commit();
          if (T == 3) {
#pragma unroll
            for (int i = jj * EARLY_PER; i < min(8, (jj + 1) * EARLY_PER); i++) put_early(i);
          }
        });
        softmax(T, O16, S16);
        if (T == 4) break;
        pv(3, 0, O16);
        late_addr();
        have = landed(4);
        release(3, O16);
      }
      last_products(0, [] {});
    } else {
      float ls[2] = {0.f, 0.f};
      const int hr = 4 * wq + (lane >> 3);
      const uint32_t ptl = hi + OFF_PT + (tid & 127) * 16;
      auto sum8 = [](const uint4& v) { return ((bf_lo(v.x) + bf_hi(v.x)) + (bf_lo(v.y) + bf_hi(v.y))) + ((bf_lo(v.z) + bf_hi(v.z)) + (bf_lo(v.w) + bf_hi(v.w))); };
      auto row_sum = [](float l) { l += __shfl_xor_sync(~0u, l, 1); l += __shfl_xor_sync(~0u, l, 2); return l + __shfl_xor_sync(~0u, l, 4); };
      auto get_p = [&](auto& O) {
        if (__builtin_expect(cbar_or(false), 0)) {
          cbar_or(false);
          rescale(O);
          ls[0] *= ldsf(hi + OFF_ALPHA + hr * 4);
          if (sizeof(O[0]) == 64) ls[1] *= ldsf(hi + OFF_ALPHA + 64 + hr * 4);
        }
      };
#pragma unroll 1
      for (int T = 0; T < 3; T++) {
        get_p(O32);
        pv(T, 1, O32);
        ls[0] += sum8(lds4(ptl + (T & 1) * 4096));
        ls[1] += sum8(lds4(ptl + (T & 1) * 4096 + 2048));
        release(T, O32);
      }
      split_o();
      {
        const float l0 = row_sum(ls[0]), l1 = row_sum(ls[1]);
        const int hl = hr + 8 * (lane & 2);
        const uint32_t m = lds1(hi + OFF_MREF + hl * 4), l = (__float_as_uint((lane & 2) ? l1 : l0) | 1u) ^ par;
        if (!(lane & 4)) stg4_b128(gs->MLE + ((hl ^ (16 * rI)) * 128 + cta) * 8 + (lane & 1) * 4, make_uint4(m, l, m, l));
#pragma unroll
        for (int i = 0; i < 8; i++) put_early(i);
      }
      get_p(O16);
      pv(3, 1, O16);
      ls[0] += sum8(lds4(ptl + 4096));
      release(3, O16);
      late_addr();
      uint32_t* const mlo = hold(inbox((16 * rI + hr) * 4 + (lane & 2), 6, fb, 13, 512 + (cta >> 1) * 8 + (lane & 1) * 4));
      mbar_wait(hi + BAR(BAR_CLR));
      get_p(O16);
      float lf;
      uint32_t mf;
      last_products(1, [&] { mf = lds1(hi + OFF_MREF + hr * 4); lf = ls[0] + sum8(lds4(ptl)); if (ML_FIRST) {
        const uint32_t l = nz(__float_as_uint(row_sum(lf)));
        if (!(lane & 4)) stg4_b128(mlo, make_uint4(mf, l, mf, l));
      } });
      if (!ML_FIRST) {
        const uint32_t l = nz(__float_as_uint(row_sum(lf)));
        if (!(lane & 4)) stg4_b128(mlo, make_uint4(mf, l, mf, l));
      }
    }
  }
  TL(13);

  uint32_t aw[8][4];
  {
    uint2 mle[4];
    uint4 ve[4];
    mbar_wait(hi + BAR(BAR_XE));
#pragma unroll
    for (int i = 0; i < 4; i++) mle[i] = lds2(hi + OFF_MLS + (w * 16 + 2 * t + 8 * (i & 1) + ((hI >> 4) ^ (i >> 1))) * 32);
#pragma unroll
    for (int i = 0; i < 4; i++) ve[i] = lds4(hi + OFF_XE + (w * 8 + t) * 256 + g * 16 + (i >> 1) * 1024 + (i & 1) * 128);
    wait_until(ck1, X1_D0);
    uint2 ml[2];
    uint4 v[4];
#pragma unroll
    for (int i = 0; i < 4; i++) v[i] = ldg_2u64(px + (i >> 1) * 512 + (i & 1) * 32);
#pragma unroll
    for (int i = 0; i < 2; i++) ml[i] = ldg_u64(pm + i * 32);
    TL(43);
#pragma unroll 1
    while (true) {
      uint32_t a = 1u, o = 0u;
#pragma unroll
      for (int i = 0; i < 4; i++) { a &= ve[i].y & ve[i].w & mle[i].y; o |= ve[i].y | ve[i].w | mle[i].y; }
      if (__all_sync(~0u, (par ? ~o : a) & 1)) break;
#pragma unroll
      for (int i = 0; i < 4; i++) {
        ve[i] = ldg_2u64(gs->XE + (cta * 64 + w * 8 + t) * 64 + 4 * g + (i >> 1) * 256 + (i & 1) * 32);
        mle[i] = ldg_u64(gs->MLE + (hI * 128 + w * 16 + 2 * t + 8 * (i & 1) + ((hI >> 4) ^ (i >> 1))) * 8);
      }
      TL(55);
    }
    float M = fmaxf(fmaxf(__uint_as_float(mle[0].x), __uint_as_float(mle[1].x)), fmaxf(__uint_as_float(mle[2].x), __uint_as_float(mle[3].x)));
    M = fmaxf(M, __shfl_xor_sync(~0u, M, 1)); M = fmaxf(M, __shfl_xor_sync(~0u, M, 2));
    uint32_t wb[4];
#pragma unroll
    for (int i = 0; i < 4; i++) wb[i] = pack_bf16(ex2(__uint_as_float(mle[i].x) - M), 0.f);
    float Ls = bf_lo(wb[2]) * __uint_as_float(mle[2].y) + bf_lo(wb[3]) * __uint_as_float(mle[3].y);
    float d0[4] = {0.f, 0.f, 0.f, 0.f}, d1[4] = {0.f, 0.f, 0.f, 0.f};
#pragma unroll
    for (int i = 0; i < 4; i++) mma_v((i & 2) ? d1 : d0, ve[i], shl_clamp(wb[2 + (i >> 1)], 16 * g - 64 * (i & 1)), shl_clamp(wb[2 + (i >> 1)], 16 * g - 64 * (i & 1) - 32));
    uint32_t sel[4][2];
#pragma unroll
    for (int i = 0; i < 4; i++) { sel[i][0] = pin32(shl_clamp(wb[i >> 1], 16 * g - 64 * (i & 1))); sel[i][1] = pin32(shl_clamp(wb[i >> 1], 16 * g - 64 * (i & 1) - 32)); }
    uint32_t* const x2o = pin(inbox(4 * hI + (jI >> 1) + (~jI & 2), 7, ~fb, 8 + (jI >> 1) + (~jI & 2), (jI & 1) * 512 + tid * 2));
    uint32_t* const x2p = pin(inbox(4 * hI + (jI >> 1) + (jI & 2), 7, ~fb, 8 + (jI >> 1) + (jI & 2), (jI & 1) * 512 + tid * 2));
    const uint32_t bso = pin32(hi + OFF_BS4 + w * 320 + (16 * (t >> 1) + 2 * g + (t & 1)) * 8), bsi = pin32(hi + OFF_BS4 + g * 320 + t * 16);
    TL(14);
    {
      const int mi = lane >> 3, r = lane & 7;
      const uint32_t base = hi + OFF_WUV + wg * 16384 + (mi >> 1) * 8192 + ((r & 6) + 8 * (r & 1)) * 128;
      const int ch = 2 * wq + (mi & 1);
      mbar_wait(hi + BAR(BAR_FULL + U_WUV) + 16 * wg); mbar_wait(hi + BAR(BAR_FULL + U_WUV + 1) + 16 * wg);
#pragma unroll
      for (int ks = 0; ks < 8; ks++) ldsm4t(aw[ks], base + (ks >> 1) * 2048 + (ks & 1) * 128 + ((ch ^ ((r & 6) + (ks & 1))) << 4));
    }
    TL(44);
    while (min(min3(min3(v[0].y, v[0].w, v[1].y), v[1].w, ml[0].y), min3(min3(v[2].y, v[2].w, v[3].y), v[3].w, ml[1].y)) == 0) {
#pragma unroll
      for (int i = 0; i < 4; i++) if (v[i].y == 0 || v[i].w == 0) v[i] = ldg_2u64(px + (i >> 1) * 512 + (i & 1) * 32);
#pragma unroll
      for (int i = 0; i < 2; i++) if (ml[i].y == 0) ml[i] = ldg_u64(pm + i * 32);
    }
    if (__builtin_expect(__any_sync(~0u, ml[0].x != mle[0].x || ml[1].x != mle[1].x), 0)) {
      float M2 = fmaxf(M, fmaxf(__uint_as_float(ml[0].x), __uint_as_float(ml[1].x)));
      M2 = fmaxf(M2, __shfl_xor_sync(~0u, M2, 1)); M2 = fmaxf(M2, __shfl_xor_sync(~0u, M2, 2));
      const float f = ex2(M - M2);
      Ls *= f;
#pragma unroll
      for (int i = 0; i < 4; i++) { d0[i] *= f; d1[i] *= f; }
#pragma unroll
      for (int i = 0; i < 2; i++) wb[i] = pack_bf16(ex2(__uint_as_float(ml[i].x) - M2), 0.f);
#pragma unroll
      for (int i = 0; i < 4; i++) { sel[i][0] = shl_clamp(wb[i >> 1], 16 * g - 64 * (i & 1)); sel[i][1] = shl_clamp(wb[i >> 1], 16 * g - 64 * (i & 1) - 32); }
    }
    TL(15);
    mma_v(d0, v[0], sel[0][0], sel[0][1]); mma_v(d1, v[2], sel[2][0], sel[2][1]);
    mma_v(d0, v[1], sel[1][0], sel[1][1]); mma_v(d1, v[3], sel[3][0], sel[3][1]);
    Ls += bf_lo(wb[0]) * __uint_as_float(ml[0].y) + bf_lo(wb[1]) * __uint_as_float(ml[1].y);
    Ls += __shfl_xor_sync(~0u, Ls, 1); Ls += __shfl_xor_sync(~0u, Ls, 2);
    const float inv = __fdividef(1.f, Ls);
    sts2(bso, pack_bf16((d0[0] + d1[0]) * inv, (d0[1] + d1[1]) * inv), pack_bf16((d0[2] + d1[2]) * inv, (d0[3] + d1[3]) * inv));
    cbar();
    TL(16);
    float o[4][4] = {{0.f, 0.f, 0.f, 0.f}, {0.f, 0.f, 0.f, 0.f}, {0.f, 0.f, 0.f, 0.f}, {0.f, 0.f, 0.f, 0.f}};
    uint4 b[4];
#pragma unroll
    for (int kk = 0; kk < 4; kk++) b[kk] = lds4(bsi + kk * 64);
#pragma unroll
    for (int kk = 0; kk < 4; kk++) { mma16816(o[(2 * kk) & 3], aw[2 * kk], b[kk].x, b[kk].y); mma16816(o[(2 * kk + 1) & 3], aw[2 * kk + 1], b[kk].z, b[kk].w); }
    const uint32_t y0 = pack_bf16((o[0][0] + o[1][0]) + (o[2][0] + o[3][0]), (o[0][1] + o[1][1]) + (o[2][1] + o[3][1]));
    const uint32_t y1 = pack_bf16((o[0][2] + o[1][2]) + (o[2][2] + o[3][2]), (o[0][3] + o[1][3]) + (o[2][3] + o[3][3]));
    stg_u64(x2o, y0, y1);
    stg_u64(x2p, y0, y1);
  }
  const uint32_t ck2 = clk32();
  TL(17);
  {
    uint32_t* const o = pin(inbox(4 * (8 * jI + w) + (g >> 1), 6, fb, 12, (g & 1) * 256 + hI * 8 + 2 * t));
    const uint32_t* const x2i = pin(inbox(cta & ~1, 7, ~fb, 8 + (jI & 2), tid * 2));
    const uint32_t* const x2j = pin(inbox(cta | 1, 7, ~fb, 8 + (jI | 1), tid * 2));
    const uint32_t bso = pin32(hi + OFF_BS5 + (16 * w + g) * 16 + t * 4), bsi = pin32(hi + OFF_BS5 + lane * 16);
    TL(45);
    wait_until(ck2, D_X2);
    uint2 v[4];
#pragma unroll
    for (int i = 0; i < 4; i++) v[i] = ldg_u64(((i & 2) ? x2j : x2i) + (i & 1) * 512);
    const bool wo_ok = mbar_test(hi + BAR(BAR_FULL + U_WO) + 16 * wg) && mbar_test(hi + BAR(BAR_FULL + U_WO + 1) + 16 * wg);
    if (wo_ok) load_a_t(aw, hi + OFF_WO + wg * 16384, wq, lane);
    sum4_to_smem(v, x2i, x2j, bso);
    __syncwarp();
    if (!wo_ok) {
      mbar_wait(hi + BAR(BAR_FULL + U_WO) + 16 * wg); mbar_wait(hi + BAR(BAR_FULL + U_WO + 1) + 16 * wg);
      load_a_t(aw, hi + OFF_WO + wg * 16384, wq, lane);
    }
    cbar();
    TL(18);
    float d[4];
    mma128(d, aw, bsi);
    stg_u64(o, pack_bf16(d[0], d[1]), pack_bf16(d[2], d[3]));
    if (lane == 0) mbar_arrive(hi + BAR(BAR_P5D));
  }
  const uint32_t ck3 = clk32();
  TL(19);
  if (cta < NFF) {
    const int mi = lane >> 3, r = lane & 7;
    uint32_t a1[4][4], a2[4][4];
    while (true) {
      uint32_t mn = 0xffffffffu;
#pragma unroll
      for (int i = 0; i < 8; i++) mn = min3(mn, bs[i], bc[i]);
      if (__all_sync(~0u, mn != 0)) break;
#pragma unroll
      for (int i = 0; i < 8; i++) { bs[i] = ldg_rlx1(mbi + i * 32); bc[i] = ldg_rlx1(mbi + 2048 + i * 32); }
    }
#pragma unroll
    for (int i = 0; i < 8; i++) { bs[i] = movm(bs[i]); bc[i] = hadd2(movm(bc[i]), ONE2); }
    mbar_wait(hi + BAR(BAR_FULL + U_W1) + 8 * wg);
#pragma unroll
    for (int ks = 0; ks < 4; ks++) ldsm4t(a1[ks], hi + OFF_W1 + (64 * w + 16 * ks + 8 * (mi >> 1) + r) * 32 + (mi & 1) * 16);
    {
      float u[4] = {0.f, 0.f, 0.f, 0.f}, vv[4] = {0.f, 0.f, 0.f, 0.f};
#pragma unroll
      for (int ks = 0; ks < 4; ks++) { mma16816(u, a1[ks], bc[2 * ks], bc[2 * ks + 1]); mma16816(vv, a1[ks], bs[2 * ks], bs[2 * ks + 1]); }
      sts4f(hi + OFF_REDU + tid * 16, u[0], u[1], u[2], u[3]);
      sts4f(hi + OFF_REDV + tid * 16, vv[0], vv[1], vv[2], vv[3]);
    }
    cbar();
    const int lp = (tid >> 2) & 31, kq = tid & 3;
    const int fo = (lp >> 2) + 8 * (kq >> 1), bo = 2 * (lp & 3) + (kq & 1);
    float U = 0.f, V = 0.f;
    if (tid < 128) {
#pragma unroll
      for (int i = 0; i < 8; i++) { U += ldsf(hi + OFF_REDU + i * 512 + tid * 4); V += ldsf(hi + OFF_REDV + i * 512 + tid * 4); }
    }
    const uint32_t* xb = pin(gs->X3B + ((cta >> 1) & 1) * 4096 + wg * 2048 + (((fb >> 14) & 1) << 10) + (16 * wq + t) * 16 + 2 * g);
    uint32_t* ox[4];
#pragma unroll
    for (int mb = 0; mb < 4; mb++) ox[mb] = pin(inbox(16 * w + 4 * mb + (g >> 1), 4 + (cta >= 56), fb, 16 + 4 * mb, (cta >= 56 ? cta - 56 : cta) * 16 + (g & 1) * 8 + 2 * t));
    const uint32_t h1o = pin32(hi + OFF_H1 + fo * 16 + bo * 2), sti = pin32(hi + OFF_REDS + bo * 64), sto = pin32(hi + OFF_REDS + g * 64 + w * 8);
    const bool w2ok = mbar_test(hi + BAR(BAR_FULL + U_W2) + 8 * wg);
    const uint32_t a2a = hi + OFF_W2 + w * 2048 + (8 * (mi >> 1) + r) * 128;
    if (w2ok) {
#pragma unroll
      for (int mb = 0; mb < 4; mb++) ldsm4t(a2[mb], a2a + (((2 * mb + (mi & 1)) ^ r) << 4));
    }
    TL(46);
    wait_until(ck3, D_X3B);
    uint2 x[4];
    {
      while (true) {
#pragma unroll
        for (int ks = 0; ks < 4; ks++) x[ks] = ldg_u64(xb + ks * 64);
        if (__all_sync(~0u, min(min(x[0].y, x[1].y), min(x[2].y, x[3].y)) != 0)) break;
      }
    }
    TL(21);
    float G[2][4] = {{0.f, 0.f, 0.f, 0.f}, {0.f, 0.f, 0.f, 0.f}}, S[2][4] = {{0.f, 0.f, 0.f, 0.f}, {0.f, 0.f, 0.f, 0.f}};
#pragma unroll
    for (int ks = 0; ks < 4; ks++) {
      const uint32_t s0[4] = {x[ks].x, ONE2, x[ks].y, ONE2};
      mma16816(S[ks & 1], s0, x[ks].x, x[ks].y);
      mma16816(G[ks & 1], a1[ks], hmul2(x[ks].x, bc[2 * ks]), hmul2(x[ks].y, bc[2 * ks + 1]));
    }
    if ((g >> 1) == t) sts2f(sto, (g & 1) ? S[0][3] + S[1][3] : S[0][2] + S[1][2], (g & 1) ? S[0][1] + S[1][1] : S[0][0] + S[1][0]);
    sts4f(hi + OFF_REDG + tid * 16, G[0][0] + G[1][0], G[0][1] + G[1][1], G[0][2] + G[1][2], G[0][3] + G[1][3]);
    cbar();
    TL(39);
    if (tid < 128) {
      float gv[8];
      float4 sv[4];
#pragma unroll
      for (int i = 0; i < 4; i++) sv[i] = ldsf4(sti + i * 16);
#pragma unroll
      for (int i = 0; i < 8; i++) gv[i] = ldsf(hi + OFF_REDG + i * 512 + tid * 4);
      const float s1 = ((sv[0].x + sv[0].z) + (sv[1].x + sv[1].z)) + ((sv[2].x + sv[2].z) + (sv[3].x + sv[3].z));
      const float s2 = ((sv[0].y + sv[0].w) + (sv[1].y + sv[1].w)) + ((sv[2].y + sv[2].w) + (sv[3].y + sv[3].w));
      const float gs_ = ((gv[0] + gv[1]) + (gv[2] + gv[3])) + ((gv[4] + gv[5]) + (gv[6] + gv[7]));
      const float mu = s1 * (1.f / 512.f);
      const float rs = rsqrtf(fmaxf(s2 * (1.f / 512.f) - mu * mu, 0.f) + 1e-5f);
      const float hv = fmaxf(rs * (gs_ - mu * U) + V, 0.f);
      asm volatile("st.shared.u16 [%0], %1;" ::"r"(h1o), "h"(__bfloat16_as_ushort(__float2bfloat16(hv))) : "memory");
    }
    if (!w2ok) {
      mbar_wait(hi + BAR(BAR_FULL + U_W2) + 8 * wg);
#pragma unroll
      for (int mb = 0; mb < 4; mb++) ldsm4t(a2[mb], a2a + (((2 * mb + (mi & 1)) ^ r) << 4));
    }
    cbar();
    TL(40);
    uint32_t b0, b1;
    ldsm2t(b0, b1, hi + OFF_H1 + (lane & 15) * 16);
#pragma unroll
    for (int mb = 0; mb < 4; mb++) {
      float o[4] = {0.f, 0.f, 0.f, 0.f};
      mma16816(o, a2[mb], b0, b1);
      stg_u64(ox[mb], pack_bf16(o[0], o[1]), pack_bf16(o[2], o[3]));
    }
    TL(22);
    if (lane == 0) mbar_arrive(hi + BAR(BAR_P7D));
  }
}

typedef CUresult (*EncodeTiledFn)(CUtensorMap*, CUtensorMapDataType, cuuint32_t, void*, const cuuint64_t*, const cuuint64_t*,
                                  const cuuint32_t*, const cuuint32_t*, CUtensorMapInterleave, CUtensorMapSwizzle,
                                  CUtensorMapL2promotion, CUtensorMapFloatOOBfill);

void make_map(EncodeTiledFn enc, CUtensorMap* m, const void* base, uint64_t cols, uint64_t rows, uint32_t bc, uint32_t br,
              CUtensorMapSwizzle sw, CUtensorMapL2promotion promo) {
  cuuint64_t dims[2] = {cols, rows};
  cuuint64_t strides[1] = {cols * 2};
  cuuint32_t box[2] = {bc, br};
  cuuint32_t es[2] = {1, 1};
  enc(m, CU_TENSOR_MAP_DATA_TYPE_BFLOAT16, 2, const_cast<void*>(base), dims, strides, box, es, CU_TENSOR_MAP_INTERLEAVE_NONE, sw, promo,
      CU_TENSOR_MAP_FLOAT_OOB_FILL_NONE);
}
void make_map3(EncodeTiledFn enc, CUtensorMap* m, const void* base, uint64_t rows, uint32_t br, uint32_t bb) {
  cuuint64_t dims[3] = {64, rows, 8};
  cuuint64_t strides[2] = {1024, 128};
  cuuint32_t box[3] = {64, br, bb};
  cuuint32_t es[3] = {1, 1, 1};
  enc(m, CU_TENSOR_MAP_DATA_TYPE_BFLOAT16, 3, const_cast<void*>(base), dims, strides, box, es, CU_TENSOR_MAP_INTERLEAVE_NONE,
      CU_TENSOR_MAP_SWIZZLE_128B, CU_TENSOR_MAP_L2_PROMOTION_NONE, CU_TENSOR_MAP_FLOAT_OOB_FILL_NONE);
}

}

extern "C" void kernel_launch(void* const* d_in, const int* in_sizes, int n_in, void* d_out, int out_size) {
  (void)in_sizes; (void)n_in; (void)out_size;
  static EncodeTiledFn enc = nullptr;
  static Scratch* scratch = nullptr;
  if (!enc) {
    void* sp = nullptr;
    cudaGetSymbolAddress(&sp, g_s);
    scratch = (Scratch*)(((uintptr_t)sp + 65535) & ~(uintptr_t)65535);
    void* fn = nullptr;
    cudaDriverEntryPointQueryResult q;
    cudaGetDriverEntryPoint("cuTensorMapEncodeTiled", &fn, cudaEnableDefault, &q);
    enc = (EncodeTiledFn)fn;
    cudaFuncSetAttribute(fused_decode_kernel, cudaFuncAttributeMaxDynamicSharedMemorySize, SMEM_BYTES);
  }
  Params P;
  make_map(enc, &P.ckv, d_in[1], 512, 8 * 4096, 64, 64, CU_TENSOR_MAP_SWIZZLE_128B, CU_TENSOR_MAP_L2_PROMOTION_NONE);
  make_map(enc, &P.wq, d_in[2], 4096, 512, 64, 64, CU_TENSOR_MAP_SWIZZLE_128B, CU_TENSOR_MAP_L2_PROMOTION_NONE);
  make_map(enc, &P.wuk, d_in[3], 4096, 512, 64, 64, CU_TENSOR_MAP_SWIZZLE_128B, CU_TENSOR_MAP_L2_PROMOTION_NONE);
  make_map(enc, &P.wuv, d_in[4], 4096, 512, 64, 64, CU_TENSOR_MAP_SWIZZLE_128B, CU_TENSOR_MAP_L2_PROMOTION_NONE);
  make_map(enc, &P.wo, d_in[5], 512, 4096, 64, 64, CU_TENSOR_MAP_SWIZZLE_128B, CU_TENSOR_MAP_L2_PROMOTION_NONE);
  make_map(enc, &P.w1, d_in[7], 1792, 512, FCH, 256, CU_TENSOR_MAP_SWIZZLE_NONE, PROMO);
  make_map3(enc, &P.w2, d_in[8], 1792, FCH, 4);
  make_map(enc, &P.wmod, d_in[10], 3072, 512, 16, 256, CU_TENSOR_MAP_SWIZZLE_NONE, PROMO);
  fused_decode_kernel<<<NCTA, NTHREADS, SMEM_BYTES>>>((__nv_bfloat16*)d_out, scratch, (const uint8_t*)d_in[10], (const uint8_t*)d_in[0],
                                                      (const uint8_t*)d_in[9], P);
}
```

```cpp
#include <cuda_runtime.h>
#include <cuda.h>
#include <cuda_bf16.h>
#include <stdint.h>

namespace {

constexpr int NCTA = 128;
constexpr int NTHREADS = 384;
constexpr int FCH = 16;
constexpr int NFF = 1792 / FCH;

constexpr uint32_t SB = 1024;
__host__ __device__ constexpr uint32_t slot(int i) { return SB + i * 8192; }
constexpr uint32_t OFF_R1 = slot(16);
constexpr uint32_t OFF_R2 = slot(20);
constexpr uint32_t OFF_PT = slot(23);
constexpr uint32_t OFF_R0 = slot(24);
constexpr uint32_t OFF_MISC = SB + 229376;
constexpr uint32_t OFF_BARS = OFF_MISC;
constexpr uint32_t OFF_FM = OFF_MISC + 736;
constexpr uint32_t OFF_EPOCH = OFF_MISC + 768;
constexpr uint32_t OFF_TL = OFF_MISC + 784;
constexpr uint32_t OFF_BS = OFF_MISC + 1024;
constexpr uint32_t SMEM_BYTES = 229376 + 3072;
constexpr uint32_t OFF_P0S = OFF_R0 + 24576;
constexpr uint32_t OFF_BS2 = OFF_R0 + 30720;
constexpr uint32_t OFF_RED = OFF_BS;
constexpr uint32_t OFF_ALPHA = OFF_BS + 512;
constexpr uint32_t OFF_MREF = OFF_BS + 640;
constexpr uint32_t OFF_FB = OFF_BS + 1024;
__host__ __device__ constexpr int box_slot(int n) { return n < 23 ? n : n == 23 ? 0 : n - 21; }
constexpr uint32_t OFF_WM = slot(1);
constexpr uint32_t OFF_WUV = slot(19);
constexpr uint32_t OFF_XE = slot(1);
constexpr uint32_t OFF_BS4 = slot(0);
constexpr uint32_t OFF_BS5 = slot(0) + 4096;
constexpr uint32_t OFF_MLS = slot(0) + 4096;
constexpr uint32_t OFF_WO = slot(3);
constexpr uint32_t OFF_W1 = slot(7);
constexpr uint32_t OFF_W2 = slot(9);
constexpr uint32_t OFF_REDG = OFF_R0;
constexpr uint32_t OFF_REDS = OFF_R0 + 4096;
constexpr uint32_t OFF_REDU = OFF_R0 + 8192;
constexpr uint32_t OFF_REDV = OFF_R0 + 12288;
constexpr uint32_t OFF_H1 = OFF_R0 + 16384;

constexpr int BAR_FULL = 8;
constexpr int U_WQ = -8, U_WUK = -4, U_WUV = 40, U_WO = 44, U_W1 = 48, U_W2 = 50, NUNITS = 52, U_WMOD = 52;
constexpr int BAR_EMPTY = 62;
constexpr int BAR_GO = 66, BAR_CLR = 67, BAR_EPOCH = 68;
constexpr int BAR_P2E = 69, BAR_P5D = 70, BAR_P7D = 71;
constexpr int BAR_XE = 72;
constexpr int BAR_FM = 73;
constexpr int BAR_QXG = 74;
constexpr int BAR_P0D = 82;
constexpr int BAR_WA = 83;
constexpr int NBARS = 87;
__host__ __device__ constexpr uint32_t BAR(int i) { return OFF_BARS + 8 * i; }
#define CPA_N 4
#define PACE_T0 520
#define PACE_DT 325
#define PACE_DTM 315
#define PACE_NM 10
#define PACE_DTE 330
#define WM0 24
#define WM1 32
#define PACE_GAP 50
#define PACE_DT2 360
#define PROMO CU_TENSOR_MAP_L2_PROMOTION_NONE
#define NPROBE 3
#define WIN_PRE 5
#define WIN_MID 8
#define WIN_END 8
#define WIN_TAIL 4
#define PACE_NS 200
#define CLR_CLK 220
#define CLR_AT 3
#define CLR_D0 0
#define D_MOD 100
#define MOD_AT 3
#define D_QP 400
#define D_QX 900
#define QK_UNROLL 1
#define QK_FENCE 1
#define ML_FIRST 1
#define P0B_LATE (WM1 > 26)
#define XE_E 3
#define PV_SPLIT 3
#define XE_AT 37
#define EARLY_PER 1
#define EARLY_N 8
#define EARLY_GAP 0
#define CNT_AT 27
#define X1_D0 1100
#define D_X2 200
#define D_X3A 400
#define D_X3B 0
#define D_FIN 600

struct Scratch {
  uint32_t MODA[1024 * 4];
  uint32_t QP[128 * 256 * 2];
  uint32_t MODB[2][2048 * 4];
  uint32_t FL[2][128];
  uint32_t QX[2][8 * 32 * 256];
  uint32_t XE[128 * 64 * 64];
  uint32_t MLE[32 * 128 * 8];
  uint32_t epoch;
  uint32_t pad[31];
  uint32_t cnt;
  alignas(65536) uint32_t X3B[16384];
  uint32_t IN[128][16384];
};
__device__ uint8_t g_s[sizeof(Scratch) + 65536];

#define TL(idx) do {} while (0)
#define TLW(idx) do {} while (0)
#define PROBE_UNITS(a, b) do {} while (0)

struct Params {
  CUtensorMap wma, wq, wuk, wmod, ckv, wuv, wo, w1, w2;
};

__device__ __forceinline__ void mbar_init(uint32_t bar, int cnt) { asm volatile("mbarrier.init.shared::cta.b64 [%0], %1;" ::"r"(bar), "r"(cnt)); }
__device__ __forceinline__ void mbar_expect(uint32_t bar, uint32_t bytes) { asm volatile("mbarrier.arrive.expect_tx.shared::cta.b64 _, [%0], %1;" ::"r"(bar), "r"(bytes) : "memory"); }
__device__ __forceinline__ void mbar_arrive(uint32_t bar) { asm volatile("mbarrier.arrive.shared::cta.b64 _, [%0];" ::"r"(bar) : "memory"); }
__device__ __forceinline__ void mbar_arrive_cluster(uint32_t bar) { asm volatile("mbarrier.arrive.shared::cluster.b64 _, [%0];" ::"r"(bar) : "memory"); }
__device__ __forceinline__ bool mbar_test(uint32_t bar) {
  uint32_t ok;
  asm volatile("{\n.reg .pred p;\nmbarrier.test_wait.parity.shared::cta.b64 p, [%1], 0;\nselp.u32 %0,1,0,p;\n}" : "=r"(ok) : "r"(bar) : "memory");
  return ok;
}
__device__ __forceinline__ uint32_t gtime32() { uint32_t c; asm volatile("mov.u32 %0, %%globaltimer_lo;" : "=r"(c) :: "memory"); return c; }
__device__ __forceinline__ uint32_t clk32() { uint32_t c; asm volatile("{\n.reg .u64 t;\nmov.u64 t, %%clock64;\ncvt.u32.u64 %0, t;\n}" : "=r"(c) :: "memory"); return c; }
__device__ __forceinline__ void wait_until(uint32_t c0, int clocks) { if (clocks > 0) while ((int)(clk32() - c0) < clocks) {} }
__device__ __forceinline__ void backoff(int clocks) { if (clocks > 0) wait_until(clk32(), clocks); }
__device__ __forceinline__ uint32_t pin32(uint32_t p) { asm volatile("" : "+r"(p)); return p; }
template <typename T> __device__ __forceinline__ T* pin(T* p) { asm volatile("" : "+l"(p)); return p; }
__device__ __forceinline__ uint32_t hold32(uint32_t p) { asm volatile("shfl.sync.bfly.b32 %0, %0, 0, 0x1f, 0xffffffff;" : "+r"(p) :: "memory"); return p; }
__device__ __forceinline__ float holdf(float p) { return __uint_as_float(hold32(__float_as_uint(p))); }
template <typename T> __device__ __forceinline__ T* hold(T* p) {
  asm volatile("{\n.reg .b32 a, b;\nmov.b64 {a, b}, %0;\nshfl.sync.bfly.b32 a, a, 0, 0x1f, 0xffffffff;\nshfl.sync.bfly.b32 b, b, 0, 0x1f, 0xffffffff;\nmov.b64 %0, {a, b};\n}" : "+l"(p) :: "memory");
  return p;
}
constexpr int SPIN_LIMIT = 1 << 22;
__device__ __forceinline__ void mbar_wait(uint32_t bar) {
  asm volatile("{\n.reg .pred p;\nMW_LOOP:\nmbarrier.try_wait.parity.shared::cta.b64 p, [%0], 0;\n@!p bra MW_LOOP;\n}" ::"r"(bar) : "memory");
}
__device__ __forceinline__ void mbar_wait_b(uint32_t bar) {
  asm volatile("{\n.reg .pred p;\n.reg .u32 c;\nmov.u32 c, 0;\n"
               "MW_LOOP:\nmbarrier.try_wait.parity.shared::cta.b64 p, [%0], 0;\n@p bra MW_DONE;\n"
               "add.u32 c, c, 1;\nsetp.lt.u32 p, c, 1048576;\n@p bra MW_LOOP;\ntrap;\nMW_DONE:\n}"
               ::"r"(bar) : "memory");
}
__device__ __forceinline__ void tma2d(uint32_t dst, const CUtensorMap* m, int c0, int c1, uint32_t bar, uint64_t pol) {
  asm volatile("cp.async.bulk.tensor.2d.shared::cluster.global.mbarrier::complete_tx::bytes.L2::cache_hint [%0], [%1, {%3,%4}], [%2], %5;"
               ::"r"(dst), "l"(m), "r"(bar), "r"(c0), "r"(c1), "l"(pol) : "memory");
}
__device__ __forceinline__ void tma2d_both(uint32_t dst, const CUtensorMap* m, int c0, int c1, uint32_t bar, uint64_t pol) {
  asm volatile("cp.async.bulk.tensor.2d.shared::cluster.global.mbarrier::complete_tx::bytes.multicast::cluster.L2::cache_hint [%0], [%1, {%3,%4}], [%2], %6, %5;"
               ::"r"(dst), "l"(m), "r"(bar), "r"(c0), "r"(c1), "l"(pol), "h"((uint16_t)3) : "memory");
}
__device__ __forceinline__ void tma3d(uint32_t dst, const CUtensorMap* m, int c0, int c1, int c2, uint32_t bar, uint64_t pol) {
  asm volatile("cp.async.bulk.tensor.3d.shared::cluster.global.mbarrier::complete_tx::bytes.L2::cache_hint [%0], [%1, {%3,%4,%5}], [%2], %6;"
               ::"r"(dst), "l"(m), "r"(bar), "r"(c0), "r"(c1), "r"(c2), "l"(pol) : "memory");
}
__device__ __forceinline__ void tma2d_nohint(uint32_t dst, const CUtensorMap* m, int c0, int c1, uint32_t bar) {
  asm volatile("cp.async.bulk.tensor.2d.shared::cluster.global.mbarrier::complete_tx::bytes [%0], [%1, {%3,%4}], [%2];"
               ::"r"(dst), "l"(m), "r"(bar), "r"(c0), "r"(c1) : "memory");
}
__device__ __forceinline__ void bulk_load(uint32_t dst, const void* src, uint32_t bytes, uint32_t bar) {
  asm volatile("cp.async.bulk.shared::cluster.global.mbarrier::complete_tx::bytes [%0], [%1], %2, [%3];" ::"r"(dst), "l"(src), "r"(bytes), "r"(bar) : "memory");
}
__device__ __forceinline__ void cbar() { asm volatile("bar.sync 1, 256;" ::: "memory"); }
__device__ __forceinline__ void wg0bar() { asm volatile("bar.sync 2, 128;" ::: "memory"); }
__device__ __forceinline__ bool cbar_or(bool p) {
  uint32_t r;
  asm volatile("{\n.reg .pred p, q;\nsetp.ne.u32 p, %1, 0;\nbarrier.cta.red.or.aligned.pred q, 1, 256, p;\nselp.u32 %0, 1, 0, q;\n}" : "=r"(r) : "r"((uint32_t)p) : "memory");
  return r;
}

__device__ __forceinline__ uint32_t ldg_rlx1(const void* p) { uint32_t v; asm volatile("ld.relaxed.gpu.global.u32 %0, [%1];" : "=r"(v) : "l"(p) : "memory"); return v; }
__device__ __forceinline__ void stg4(void* p, uint4 v) { asm volatile("st.relaxed.gpu.global.v4.u32 [%0], {%1,%2,%3,%4};" ::"l"(p), "r"(v.x), "r"(v.y), "r"(v.z), "r"(v.w) : "memory"); }
__device__ __forceinline__ void stg1(void* p, uint32_t a) { asm volatile("st.relaxed.gpu.global.u32 [%0], %1;" ::"l"(p), "r"(a) : "memory"); }
__device__ __forceinline__ uint32_t nz(uint32_t w) { uint32_t r; asm("max.u32 %0, %1, 1;" : "=r"(r) : "r"(w)); return r; }
__device__ __forceinline__ uint32_t min3(uint32_t a, uint32_t b, uint32_t c) { return min(min(a, b), c); }

__device__ __forceinline__ uint32_t pack_bf16(float lo, float hi) { uint32_t r; asm("cvt.rn.bf16x2.f32 %0, %1, %2;" : "=r"(r) : "f"(hi), "f"(lo)); return r; }
__device__ __forceinline__ float bf_lo(uint32_t w) { return __uint_as_float(w << 16); }
__device__ __forceinline__ float bf_hi(uint32_t w) { return __uint_as_float(w & 0xffff0000u); }
__device__ __forceinline__ float ex2(float x) { float r; asm("ex2.approx.ftz.f32 %0, %1;" : "=f"(r) : "f"(x)); return r; }
__device__ __forceinline__ float rcp(float x) { float r; asm("rcp.approx.ftz.f32 %0, %1;" : "=f"(r) : "f"(x)); return r; }
__device__ __forceinline__ float rsq(float x) { float r; asm("rsqrt.approx.ftz.f32 %0, %1;" : "=f"(r) : "f"(x)); return r; }
__device__ __forceinline__ uint32_t silu2(uint32_t c) {
  const float a = bf_lo(c), b = bf_hi(c);
  return pack_bf16(__fdividef(a, 1.f + __expf(-a)), __fdividef(b, 1.f + __expf(-b)));
}
__device__ __forceinline__ uint32_t shl_clamp(uint32_t x, int s) { uint32_t r; asm("shl.b32 %0, %1, %2;" : "=r"(r) : "r"(x), "r"(s)); return r; }

__device__ __forceinline__ void ldsm4(uint32_t (&r)[4], uint32_t a) { asm volatile("ldmatrix.sync.aligned.m8n8.x4.shared.b16 {%0,%1,%2,%3}, [%4];" : "=r"(r[0]), "=r"(r[1]), "=r"(r[2]), "=r"(r[3]) : "r"(a) : "memory"); }
__device__ __forceinline__ void ldsm4t(uint32_t (&r)[4], uint32_t a) { asm volatile("ldmatrix.sync.aligned.m8n8.x4.trans.shared.b16 {%0,%1,%2,%3}, [%4];" : "=r"(r[0]), "=r"(r[1]), "=r"(r[2]), "=r"(r[3]) : "r"(a) : "memory"); }
__device__ __forceinline__ void ldsm2t(uint32_t& r0, uint32_t& r1, uint32_t a) { asm volatile("ldmatrix.sync.aligned.m8n8.x2.trans.shared.b16 {%0,%1}, [%2];" : "=r"(r0), "=r"(r1) : "r"(a) : "memory"); }
__device__ __forceinline__ void stsm4t(uint32_t a, uint32_t r0, uint32_t r1, uint32_t r2, uint32_t r3) { asm volatile("stmatrix.sync.aligned.m8n8.x4.trans.shared.b16 [%0], {%1,%2,%3,%4};" ::"r"(a), "r"(r0), "r"(r1), "r"(r2), "r"(r3) : "memory"); }
__device__ __forceinline__ void stsm2t(uint32_t a, uint32_t r0, uint32_t r1) { asm volatile("stmatrix.sync.aligned.m8n8.x2.trans.shared.b16 [%0], {%1,%2};" ::"r"(a), "r"(r0), "r"(r1) : "memory"); }
__device__ __forceinline__ void mma16816(float (&d)[4], const uint32_t (&a)[4], uint32_t b0, uint32_t b1) {
  asm volatile("mma.sync.aligned.m16n8k16.row.col.f32.bf16.bf16.f32 {%0,%1,%2,%3}, {%4,%5,%6,%7}, {%8,%9}, {%0,%1,%2,%3};"
               : "+f"(d[0]), "+f"(d[1]), "+f"(d[2]), "+f"(d[3]) : "r"(a[0]), "r"(a[1]), "r"(a[2]), "r"(a[3]), "r"(b0), "r"(b1));
}
__device__ __forceinline__ void mma_v(float (&d)[4], const uint4& a, uint32_t b0, uint32_t b1) {
  asm volatile("mma.sync.aligned.m16n8k16.row.col.f32.bf16.bf16.f32 {%0,%1,%2,%3}, {%4,%5,%6,%7}, {%8,%9}, {%0,%1,%2,%3};"
               : "+f"(d[0]), "+f"(d[1]), "+f"(d[2]), "+f"(d[3]) : "r"(a.x), "r"(a.y), "r"(a.z), "r"(a.w), "r"(b0), "r"(b1));
}
__device__ __forceinline__ void sts1(uint32_t a, uint32_t v) { asm volatile("st.shared.u32 [%0], %1;" ::"r"(a), "r"(v) : "memory"); }
__device__ __forceinline__ void sts2(uint32_t a, uint32_t x, uint32_t y) { asm volatile("st.shared.v2.u32 [%0], {%1,%2};" ::"r"(a), "r"(x), "r"(y) : "memory"); }
__device__ __forceinline__ void sts4(uint32_t a, uint4 v) { asm volatile("st.shared.v4.u32 [%0], {%1,%2,%3,%4};" ::"r"(a), "r"(v.x), "r"(v.y), "r"(v.z), "r"(v.w) : "memory"); }
__device__ __forceinline__ void sts4f(uint32_t a, float x, float y, float z, float w) { asm volatile("st.shared.v4.f32 [%0], {%1,%2,%3,%4};" ::"r"(a), "f"(x), "f"(y), "f"(z), "f"(w) : "memory"); }
__device__ __forceinline__ void sts2f(uint32_t a, float x, float y) { asm volatile("st.shared.v2.f32 [%0], {%1,%2};" ::"r"(a), "f"(x), "f"(y) : "memory"); }
__device__ __forceinline__ void stsf(uint32_t a, float v) { asm volatile("st.shared.f32 [%0], %1;" ::"r"(a), "f"(v) : "memory"); }
__device__ __forceinline__ uint32_t lds1(uint32_t a) { uint32_t v; asm volatile("ld.shared.u32 %0, [%1];" : "=r"(v) : "r"(a) : "memory"); return v; }
__device__ __forceinline__ uint2 lds2(uint32_t a) { uint2 v; asm volatile("ld.shared.v2.u32 {%0,%1}, [%2];" : "=r"(v.x), "=r"(v.y) : "r"(a) : "memory"); return v; }
__device__ __forceinline__ float ldsf(uint32_t a) { float v; asm volatile("ld.shared.f32 %0, [%1];" : "=f"(v) : "r"(a) : "memory"); return v; }
__device__ __forceinline__ float2 ldsf2(uint32_t a) { float2 v; asm volatile("ld.shared.v2.f32 {%0,%1}, [%2];" : "=f"(v.x), "=f"(v.y) : "r"(a) : "memory"); return v; }
__device__ __forceinline__ float4 ldsf4(uint32_t a) { float4 v; asm volatile("ld.shared.v4.f32 {%0,%1,%2,%3}, [%4];" : "=f"(v.x), "=f"(v.y), "=f"(v.z), "=f"(v.w) : "r"(a) : "memory"); return v; }
__device__ __forceinline__ uint4 lds4(uint32_t a) { uint4 v; asm volatile("ld.shared.v4.u32 {%0,%1,%2,%3}, [%4];" : "=r"(v.x), "=r"(v.y), "=r"(v.z), "=r"(v.w) : "r"(a) : "memory"); return v; }

__device__ __forceinline__ void wg_fence() { asm volatile("wgmma.fence.sync.aligned;" ::: "memory"); }
__device__ __forceinline__ void wg_commit() { asm volatile("wgmma.commit_group.sync.aligned;" ::: "memory"); }
template <int N> __device__ __forceinline__ void wg_wait() { asm volatile("wgmma.wait_group.sync.aligned %0;" ::"n"(N) : "memory"); }
__host__ __device__ constexpr uint32_t dlo(uint32_t addr) { return (addr >> 4) | 0x10000u; }
constexpr uint32_t ONE2 = 0x3f803f80u;
template <int TA, int ACC> __device__ __forceinline__ void wgmma_ss(float (&d)[16], uint32_t da, uint32_t db) {
  asm volatile("{\n.reg .b64 da, db;\nmov.b64 da, {%16, 0x40000040};\nmov.b64 db, {%17, 0x40000040};\n"
               "wgmma.mma_async.sync.aligned.m64n32k16.f32.bf16.bf16 {%0,%1,%2,%3,%4,%5,%6,%7,%8,%9,%10,%11,%12,%13,%14,%15}, da, db, %18, 1, 1, %19, 0;\n}"
               : "+f"(d[0]), "+f"(d[1]), "+f"(d[2]), "+f"(d[3]), "+f"(d[4]), "+f"(d[5]), "+f"(d[6]), "+f"(d[7]),
                 "+f"(d[8]), "+f"(d[9]), "+f"(d[10]), "+f"(d[11]), "+f"(d[12]), "+f"(d[13]), "+f"(d[14]), "+f"(d[15])
               : "r"(da), "r"(db), "n"(ACC), "n"(TA));
}
template <int TA, int ACC> __device__ __forceinline__ void wgmma_ss(float (&d)[8], uint32_t da, uint32_t db) {
  asm volatile("{\n.reg .b64 da, db;\nmov.b64 da, {%8, 0x40000040};\nmov.b64 db, {%9, 0x40000040};\n"
               "wgmma.mma_async.sync.aligned.m64n16k16.f32.bf16.bf16 {%0,%1,%2,%3,%4,%5,%6,%7}, da, db, %10, 1, 1, %11, 0;\n}"
               : "+f"(d[0]), "+f"(d[1]), "+f"(d[2]), "+f"(d[3]), "+f"(d[4]), "+f"(d[5]), "+f"(d[6]), "+f"(d[7])
               : "r"(da), "r"(db), "n"(ACC), "n"(TA));
}
__device__ __forceinline__ void wgmma_n8(float (&d)[4], uint32_t da, uint32_t db) {
  asm volatile("{\n.reg .b64 da, db;\nmov.b64 da, {%4, 0x40000040};\nmov.b64 db, {%5, 0x40000040};\n"
               "wgmma.mma_async.sync.aligned.m64n8k16.f32.bf16.bf16 {%0,%1,%2,%3}, da, db, 1, 1, 1, 1, 0;\n}"
               : "+f"(d[0]), "+f"(d[1]), "+f"(d[2]), "+f"(d[3]) : "r"(da), "r"(db));
}
__device__ __forceinline__ void wgmma_ss_p(float (&d)[16], uint32_t da, uint32_t db, int acc) {
  asm volatile("{\n.reg .pred p;\n.reg .b64 da, db;\nsetp.ne.b32 p, %18, 0;\nmov.b64 da, {%16, 0x40000040};\nmov.b64 db, {%17, 0x40000040};\n"
               "wgmma.mma_async.sync.aligned.m64n32k16.f32.bf16.bf16 {%0,%1,%2,%3,%4,%5,%6,%7,%8,%9,%10,%11,%12,%13,%14,%15}, da, db, p, 1, 1, 0, 0;\n}"
               : "+f"(d[0]), "+f"(d[1]), "+f"(d[2]), "+f"(d[3]), "+f"(d[4]), "+f"(d[5]), "+f"(d[6]), "+f"(d[7]),
                 "+f"(d[8]), "+f"(d[9]), "+f"(d[10]), "+f"(d[11]), "+f"(d[12]), "+f"(d[13]), "+f"(d[14]), "+f"(d[15])
               : "r"(da), "r"(db), "r"(acc));
}
__device__ __forceinline__ void wgmma_ss_p(float (&d)[8], uint32_t da, uint32_t db, int acc) {
  asm volatile("{\n.reg .pred p;\n.reg .b64 da, db;\nsetp.ne.b32 p, %10, 0;\nmov.b64 da, {%8, 0x40000040};\nmov.b64 db, {%9, 0x40000040};\n"
               "wgmma.mma_async.sync.aligned.m64n16k16.f32.bf16.bf16 {%0,%1,%2,%3,%4,%5,%6,%7}, da, db, p, 1, 1, 0, 0;\n}"
               : "+f"(d[0]), "+f"(d[1]), "+f"(d[2]), "+f"(d[3]), "+f"(d[4]), "+f"(d[5]), "+f"(d[6]), "+f"(d[7])
               : "r"(da), "r"(db), "r"(acc));
}
template <int K> __device__ __forceinline__ void tie(float (&d)[K]) {
#pragma unroll
  for (int i = 0; i < K; i += 8)
    asm volatile("" : "+f"(d[i]), "+f"(d[i + 1]), "+f"(d[i + 2]), "+f"(d[i + 3]), "+f"(d[i + 4]), "+f"(d[i + 5]), "+f"(d[i + 6]), "+f"(d[i + 7]) :: "memory");
}
template <bool C, typename A, typename B> __device__ __forceinline__ auto& pick(A& a, B& b) { if constexpr (C) return a; else return b; }
__device__ __forceinline__ void tie(uint4& v) { asm volatile("" : "+r"(v.x), "+r"(v.y), "+r"(v.z), "+r"(v.w) :: "memory"); }
__device__ __forceinline__ void tie(uint2& v) { asm volatile("" : "+r"(v.x), "+r"(v.y) :: "memory"); }
#define PRAGMA(x) _Pragma(#x)
#define UNROLL(n) PRAGMA(unroll n)
template <int I> struct IC { static constexpr int value = I; };
template <int B, int E, typename F> __device__ __forceinline__ void sfor(F&& f) { if constexpr (B < E) { f(IC<B>{}); sfor<B + 1, E>(f); } }

__device__ __forceinline__ uint2 ldg_u64(const void* p) {
  uint2 v; asm volatile("{\n.reg .b64 a;\nld.relaxed.gpu.global.b64 a, [%2];\nmov.b64 {%0,%1}, a;\n}" : "=r"(v.x), "=r"(v.y) : "l"(p) : "memory"); return v;
}
__device__ __forceinline__ uint4 ldg_2u64(const void* p) {
  uint4 v; asm volatile("{\n.reg .b64 a, b;\nld.relaxed.gpu.global.v2.b64 {a, b}, [%4];\nmov.b64 {%0,%1}, a;\nmov.b64 {%2,%3}, b;\n}" : "=r"(v.x), "=r"(v.y), "=r"(v.z), "=r"(v.w) : "l"(p) : "memory"); return v;
}
__device__ __forceinline__ uint4 ldg_u128(const void* p) {
  uint4 v; asm volatile("{\n.reg .b64 a, b;\n.reg .b128 q;\nld.relaxed.gpu.global.b128 q, [%4];\nmov.b128 {a, b}, q;\nmov.b64 {%0,%1}, a;\nmov.b64 {%2,%3}, b;\n}" : "=r"(v.x), "=r"(v.y), "=r"(v.z), "=r"(v.w) : "l"(p) : "memory"); return v;
}
__device__ __forceinline__ void stg_u64(void* p, uint32_t x, uint32_t y) {
  asm volatile("{\n.reg .b64 a;\nmov.b64 a, {%1,%2};\nst.relaxed.gpu.global.b64 [%0], a;\n}" ::"l"(p), "r"(x), "r"(nz(y)) : "memory");
}
__device__ __forceinline__ uint64_t pair64(uint32_t x, uint32_t y) { uint64_t a; asm("mov.b64 %0, {%1,%2};" : "=l"(a) : "r"(x), "r"(y)); return a; }
__device__ __forceinline__ void stg_b64(void* p, uint64_t a) { asm volatile("st.relaxed.gpu.global.b64 [%0], %1;" ::"l"(p), "l"(a) : "memory"); }
__device__ __forceinline__ void stg4_b128(void* p, uint4 v) {
  asm volatile("{\n.reg .b64 a, b;\n.reg .b128 q;\nmov.b64 a, {%1,%2};\nmov.b64 b, {%3,%4};\nmov.b128 q, {a, b};\nst.relaxed.gpu.global.b128 [%0], q;\n}" ::"l"(p), "r"(v.x), "r"(v.y), "r"(v.z), "r"(v.w) : "memory");
}
__device__ __forceinline__ void stg_u128(void* p, uint4 v) {
  asm volatile("{\n.reg .b64 a, b;\n.reg .b128 q;\nmov.b64 a, {%1,%2};\nmov.b64 b, {%3,%4};\nmov.b128 q, {a, b};\nst.relaxed.gpu.global.b128 [%0], q;\n}" ::"l"(p), "r"(v.x), "r"(v.y), "r"(v.z), "r"(nz(v.w)) : "memory");
}
__device__ __forceinline__ uint32_t hmul2(uint32_t a, uint32_t b) { uint32_t r; asm("mul.rn.bf16x2 %0, %1, %2;" : "=r"(r) : "r"(a), "r"(b)); return r; }
__device__ __forceinline__ uint32_t hadd2(uint32_t a, uint32_t b) { uint32_t r; asm("add.rn.bf16x2 %0, %1, %2;" : "=r"(r) : "r"(a), "r"(b)); return r; }
__device__ __forceinline__ uint32_t hfma2(uint32_t a, uint32_t b, uint32_t c) { uint32_t r; asm("fma.rn.bf16x2 %0, %1, %2, %3;" : "=r"(r) : "r"(a), "r"(b), "r"(c)); return r; }
__device__ __forceinline__ uint32_t movm(uint32_t a) { uint32_t d; asm volatile("movmatrix.sync.aligned.m8n8.trans.b16 %0, %1;" : "=r"(d) : "r"(a)); return d; }
__device__ __forceinline__ uint2 ldg_rlx2(const void* p) { uint2 v; asm volatile("ld.relaxed.gpu.global.v2.u32 {%0,%1}, [%2];" : "=r"(v.x), "=r"(v.y) : "l"(p) : "memory"); return v; }
__device__ __forceinline__ uint4 ldg_in4(const void* p) { uint4 v; asm volatile("ld.global.nc.v4.u32 {%0,%1,%2,%3}, [%4];" : "=r"(v.x), "=r"(v.y), "=r"(v.z), "=r"(v.w) : "l"(p) : "memory"); return v; }
__device__ __forceinline__ uint32_t ldg_in1(const void* p) { uint32_t v; asm volatile("ld.global.nc.u32 %0, [%1];" : "=r"(v) : "l"(p)); return v; }
__device__ __forceinline__ uint32_t ldg_inh(const void* p) { uint16_t v; asm volatile("ld.global.nc.u16 %0, [%1];" : "=h"(v) : "l"(p) : "memory"); return v; }

__device__ __forceinline__ void sum4_to_smem(uint2 (&v)[4], const uint32_t* x, const uint32_t* y, uint32_t dst) {
  uint32_t r0, r1;
#pragma unroll 1
  while (true) {
    const bool ok = __all_sync(~0u, min(min3(v[0].y, v[1].y, v[2].y), v[3].y) != 0);
    r0 = pack_bf16((bf_lo(v[0].x) + bf_lo(v[1].x)) + (bf_lo(v[2].x) + bf_lo(v[3].x)), (bf_hi(v[0].x) + bf_hi(v[1].x)) + (bf_hi(v[2].x) + bf_hi(v[3].x)));
    r1 = pack_bf16((bf_lo(v[0].y) + bf_lo(v[1].y)) + (bf_lo(v[2].y) + bf_lo(v[3].y)), (bf_hi(v[0].y) + bf_hi(v[1].y)) + (bf_hi(v[2].y) + bf_hi(v[3].y)));
    sts1(dst, r0);
    sts1(dst + 128, r1);
    if (ok) break;
#pragma unroll
    for (int i = 0; i < 4; i++) v[i] = ldg_u64(((i & 2) ? y : x) + (i & 1) * 512);
  }
}
__device__ __forceinline__ void load_a_t(uint32_t (&a)[8][4], uint32_t box, int wq, int lane) {
  const int mi = lane >> 3, r = lane & 7;
  const uint32_t base = box + (8 * (mi >> 1) + r) * 128 + (((2 * wq + (mi & 1)) ^ r) << 4);
#pragma unroll
  for (int ks = 0; ks < 8; ks++) ldsm4t(a[ks], base + ks * 2048);
}
__device__ __forceinline__ void mma128(float (&d)[4], const uint32_t (&a)[8][4], uint32_t bs) {
  float e[4][4] = {{0.f, 0.f, 0.f, 0.f}, {0.f, 0.f, 0.f, 0.f}, {0.f, 0.f, 0.f, 0.f}, {0.f, 0.f, 0.f, 0.f}};
  uint32_t b[4][4];
#pragma unroll
  for (int kk = 0; kk < 4; kk++) ldsm4t(b[kk], bs + 32 * kk * 16);
#pragma unroll
  for (int kk = 0; kk < 4; kk++) { mma16816(e[(2 * kk) & 3], a[2 * kk], b[kk][0], b[kk][1]); mma16816(e[(2 * kk + 1) & 3], a[2 * kk + 1], b[kk][2], b[kk][3]); }
#pragma unroll
  for (int i = 0; i < 4; i++) d[i] = (e[0][i] + e[1][i]) + (e[2][i] + e[3][i]);
}
template <int NL, typename F> __device__ __forceinline__ void poll_vectors(const uint32_t* p, const uint32_t* q, F&& f) {
  int it = 0;
  bool ok;
#pragma unroll 1
  do {
    if (++it > SPIN_LIMIT) __trap();
    uint4 v[NL];
#pragma unroll
    for (int i = 0; i < NL; i++) v[i] = ldg_2u64(i < NL / 2 ? p + i * 128 : q + (i - NL / 2) * 128);
    f(v);
    uint32_t m0 = min(v[0].y, v[0].w), m1 = min(v[1].y, v[1].w);
#pragma unroll
    for (int i = 2; i < NL; i += 2) { m0 = min3(m0, v[i].y, v[i].w); m1 = min3(m1, v[i + 1].y, v[i + 1].w); }
    ok = __all_sync(~0u, min(m0, m1) != 0);
  } while (!ok);
}

__global__ void __cluster_dims__(2, 1, 1) __launch_bounds__(NTHREADS, 1)
fused_decode_kernel(__nv_bfloat16* __restrict__ gout, Scratch* __restrict__ gs, const uint8_t* __restrict__ gwq,
                    const uint8_t* __restrict__ gx, const uint8_t* __restrict__ gc,
                    const __grid_constant__ Params P) {
  extern __shared__ __align__(1024) uint8_t smem_raw[];
  const uint32_t hi = pin32((uint32_t)__cvta_generic_to_shared(smem_raw) - SB);
  const int tid = threadIdx.x, lane = tid & 31;
  const int w = __shfl_sync(0xffffffffu, tid >> 5, 0);
  const int cta = blockIdx.x;
  const int g = lane >> 2, t = lane & 3;
  const int hI = cta >> 2, jI = cta & 3;
  const int bI = cta >> 4, pI = (cta >> 1) & 7, rI = cta & 1;

  uint32_t epoch0 = 0;
  if (tid == 320) epoch0 = ldg_rlx1(&gs->epoch);
  const bool p0a = (cta & 7) == 0;
  uint4 cw0, cw1, xr0, xr1;
  uint32_t xc;
  uint2 sa, ca, qp[4];
  const uint32_t* const modi = gs->MODA + 512 * jI + tid * 2;
  const uint32_t* const qpi = gs->QP + (hI * 4 * 256 + tid) * 2;
  if (w < 8) {
    const uint8_t* src = gwq + (size_t)(128 * jI + (tid >> 4)) * 8192 + hI * 256 + (tid & 15) * 16;
    const uint32_t dst = hi + OFF_R1 + ((tid >> 3) & 1) * 16384 + (tid >> 4) * 128 + (((tid ^ (tid >> 4)) & 7) << 4);
    if (p0a) {
      cw0 = ldg_in4(gc + g * 1024 + w * 128 + t * 32); cw1 = ldg_in4(gc + g * 1024 + w * 128 + t * 32 + 16);
      xr0 = ldg_in4(gx + w * 1024 + lane * 16); xr1 = ldg_in4(gx + w * 1024 + 512 + lane * 16);
      xc = ldg_in1(gx + w * 1024 + (cta & 63) * 16 + lane * 4);
    } else {
#pragma unroll
      for (int i = 0; i < CPA_N; i++) asm volatile("cp.async.cg.shared.global [%0], [%1], 16;" ::"r"(dst + i * 2048), "l"(src + i * 16 * 8192) : "memory");
    }
    sa = ca = qp[0] = qp[1] = qp[2] = qp[3] = make_uint2(0, 0);
    if (hI == 1) { sa = ldg_rlx2(modi); ca = ldg_rlx2(modi + 2048); }
    if (jI == 1) {
#pragma unroll
      for (int i = 0; i < 4; i++) qp[i] = ldg_u64(qpi + i * 512);
    }
  }
  auto half_of = [&](int c, int k) { return ((lds1(hi + OFF_FM + (c >> 5) * 4) >> (c & 31)) ^ k) & 1; };
  auto inbox = [&](int c, int k, uint32_t bits, int pos, int off) { return gs->IN[0] + (uint32_t)(c * 16384 + k * 2048 + off + (((bits >> pos) & 1) << 10)); };
  auto front_unit = [&](int k, uint64_t pol) {
    tma2d(hi + OFF_R1 + ((k & 4) + 2 * (k & 1) + ((k >> 1) & 1)) * 8192, k < 4 ? &P.wq : &P.wuk, 128 * hI + 64 * (k & 1), 128 * jI + 64 * ((k >> 1) & 1), hi + BAR(k), pol);
  };
  if (tid == 256) {
    if (hi & 0xffffff) __trap();
    if (p0a) {
#pragma unroll
      for (int i = 0; i < 4; i++) mbar_init(hi + BAR(BAR_WA + i), 1);
      asm volatile("fence.mbarrier_init.release.cluster;" ::: "memory");
      uint64_t pol; asm volatile("createpolicy.fractional.L2::evict_first.b64 %0, 1.0;" : "=l"(pol));
#pragma unroll
      for (int i = 0; i < 4; i++) tma2d(hi + slot(8 + 2 * i), &P.wma, 8 * cta, 128 * i, hi + BAR(BAR_WA + i), pol);
    }
    asm volatile("prefetch.tensormap [%0];" ::"l"(&P.wq) : "memory");
    TLW(42);
  } else if (tid == 288) {
#pragma unroll
    for (int i = 0; i < BAR_WA; i++)
      mbar_init(hi + BAR(i), (i >= BAR_EMPTY && i < BAR_EMPTY + 4) ? 16 : (i >= BAR_P2E && i <= BAR_P7D) ? 8 : 1);
    asm volatile("fence.mbarrier_init.release.cluster;" ::: "memory");
  }
  __syncthreads();
  TL(0);

  if (w == 8) {
    uint32_t tnext = gtime32() + PACE_T0;
    if (p0a && lane < 4) mbar_expect(hi + BAR(BAR_WA) + 8 * lane, 16384);
    mbar_expect(hi + BAR(0) + 8 * lane, (lane < CPA_N / 2 && !p0a) ? 0 : 8192);
    if (p0a) tnext -= (CPA_N / 2) * PACE_DT;
    if (lane < BAR_EMPTY - 32) mbar_expect(hi + BAR(32) + 8 * lane, 8192);
    __syncwarp();
    const int h = hI, j = jI;
    if (lane == 0) {
      uint64_t pol; asm volatile("createpolicy.fractional.L2::evict_first.b64 %0, 1.0;" : "=l"(pol));
      auto pace = [&](int dt) { if (PACE_DT > 0) { while ((int)(gtime32() - tnext) < 0) {} tnext += dt; } };
      asm volatile("prefetch.tensormap [%0];" ::"l"(&P.wuk) : "memory");
      asm volatile("prefetch.tensormap [%0];" ::"l"(&P.wmod) : "memory");
      asm volatile("prefetch.tensormap [%0];" ::"l"(&P.ckv) : "memory");
#pragma unroll 1
      for (int k = p0a ? 0 : CPA_N / 2; k < 8; k++) { if (k >= WIN_PRE) mbar_wait(hi + BAR(0) + 8 * (k - WIN_PRE)); pace(PACE_DT); front_unit(k, pol); }
      bool go = false;
      const int row0 = bI * 4096 + (cta & 15) * 64;
#pragma unroll 1
      for (int n = 0; n < 24; n++) {
        if (n == 8) mbar_wait(hi + BAR(BAR_P2E));
        if (n == 23) mbar_wait(hi + BAR(BAR_EMPTY));
        if (!go) go = mbar_test(hi + BAR(BAR_GO));
        mbar_wait(hi + BAR(BAR_FULL) + 8 * (n - (go ? WIN_MID : WIN_PRE)));
        pace(n >= PACE_NM ? PACE_DTM : PACE_DT);
        tma2d(hi + slot(box_slot(n)), &P.ckv, (n & 7) * 64, row0 + (n >> 3) * 1024, hi + BAR(BAR_FULL) + 8 * n, pol);
      }
      asm volatile("prefetch.tensormap [%0];" ::"l"(&P.wuv) : "memory");
      asm volatile("prefetch.tensormap [%0];" ::"l"(&P.wo) : "memory");
      asm volatile("prefetch.tensormap [%0];" ::"l"(&P.w1) : "memory");
      asm volatile("prefetch.tensormap [%0];" ::"l"(&P.w2) : "memory");
      const int row1 = bI * 4096 + (24 + pI) * 64;
      tnext += rI * (PACE_DT / 2) - PACE_DT / 4;
#pragma unroll 1
      for (int n = 24 + rI; n < 40; n += 2) {
        const int c = n - 23;
        const int m = c >= 2 * WIN_END ? n - 2 * WIN_END : 23 - (2 * WIN_END - c) / 2;
        mbar_wait(hi + BAR(BAR_FULL) + 8 * m);
        if ((n & ~1) == WM0) { pace(PACE_DTE); tma2d_nohint(hi + OFF_WM, &P.wmod, 1024 + 16 * cta, 0, hi + BAR(BAR_FULL + U_WMOD)); }
        if ((n & ~1) == WM1) { pace(PACE_DTE); tma2d_nohint(hi + OFF_WM + 8192, &P.wmod, 1024 + 16 * cta, 256, hi + BAR(BAR_FULL + U_WMOD + 1)); }
        mbar_wait(hi + BAR(BAR_EMPTY) + ((n - 21) & ~7));
        pace(PACE_DTE);
        tma2d_both(hi + slot(n - 21), &P.ckv, (n & 7) * 64, row1 + (n >> 3) * 512, hi + BAR(BAR_FULL) + 8 * n, pol);
      }
      mbar_wait(hi + BAR(BAR_EMPTY + 2));
      tnext += PACE_GAP;
#pragma unroll 1
      for (int n = U_WUV; n < (cta < NFF ? NUNITS : U_W1); n++) {
        const int c = n - 39, u = n & 3;
        mbar_wait(hi + BAR(BAR_FULL) + 8 * (c >= WIN_TAIL ? n - WIN_TAIL : 39 - 2 * (WIN_TAIL - c)));
        if (n == U_WO) mbar_wait(hi + BAR(BAR_EMPTY + 3));
        const uint32_t bar = hi + BAR(BAR_FULL) + 8 * n, dst = hi + slot(n < U_WO ? n - 21 : n - 41);
        pace(PACE_DT2);
        if (n < U_W1) tma2d(dst, n < U_WO ? &P.wuv : &P.wo, 128 * (n < U_WO ? h : j) + 64 * (u >> 1), 128 * (n < U_WO ? j : h) + 64 * (u & 1), bar, pol);
        else if (n < U_W2) tma2d_nohint(dst, &P.w1, FCH * cta, 256 * (u & 1), bar);
        else tma3d(dst, &P.w2, 0, FCH * cta, 4 * (u & 1), bar, pol);
      }
    }
    return;
  }

  if (w == 11) {
    const uint4 z = make_uint4(0, 0, 0, 0);
    float d[4] = {0.f, 0.f, 0.f, 0.f};
    const uint32_t a[4] = {0u, 0u, 0u, 0u};
    auto pace = [&] {
      mma16816(d, a, 0u, 0u);
    };
    auto pace_until = [&](int bar) { do { pace(); __nanosleep(PACE_NS); } while (!mbar_test(hi + BAR(bar))); };
    pace();
    uint32_t f = 0, f2 = 0;
    {
      uint32_t* const p = ((lane & 2) ? gs->X3B + 4 * 2048 + cta * 8 : gs->IN[cta] + 4 * 2048 + 960) + ((lane & 1) << 10);
      if (lane < 8) stg4(p + (lane & 4), z);
      __syncwarp();
      uint32_t best = ~0u;
#pragma unroll 1
      for (int i = 0; i < 4 * NPROBE + (int)(hi & 1); i++) {
        uint32_t v = 0;
        const uint32_t c0 = clk32();
        if (lane == (i & 3)) asm volatile("atom.relaxed.gpu.global.exch.b32 %0, [%1], %2;" : "=r"(v) : "l"(p), "r"(i) : "memory");
        v = __shfl_sync(~0u, v, i & 3);
        const uint32_t dt = clk32() - c0 + (v >> 31);
        if (lane == (i & 3)) best = min(best, dt);
        pace();
      }
      const uint32_t m = __ballot_sync(~0u, best < __shfl_xor_sync(~0u, best, 1));
      f = (m >> 1) & 1; f2 = (m >> 3) & 1;
    }
    mbar_wait(hi + BAR(BAR_EPOCH));
    const uint32_t epoch = lds1(hi + OFF_EPOCH);
    const int par = epoch & 1;
    if (lane == 0) stg1(gs->FL[par] + cta, 1 + f);
    TLW(51);
    if (CLR_AT == 2) pace_until(BAR_GO);
    if (CLR_AT == 3) pace_until(BAR_P2E);
    backoff(CLR_D0);
#pragma unroll 1
    for (int i = 0; i < 16; i++) {
      const uint32_t c0 = clk32();
      uint32_t* p = gs->IN[cta] + (i >> 1) * 2048 + (((f ^ (i >> 1)) & 1) << 10) + (i & 1) * 512 + lane * 4;
#pragma unroll
      for (int q = 0; q < 4; q++) stg4(p + q * 128, z);
      if (i == 0 && lane < 16) stg4(gs->X3B + cta * 64 + lane * 4, z);
      if (CLR_AT != 2 && !mbar_test(hi + BAR(BAR_GO))) pace();
      wait_until(c0, CLR_CLK);
    }
    TLW(35);
    asm volatile("fence.acq_rel.gpu;" ::: "memory");
    __syncwarp();
    if (lane == 0) asm volatile("red.relaxed.gpu.global.add.u32 [%0], 1;" ::"l"(&gs->cnt) : "memory");
    TLW(36);
    mbar_wait(hi + BAR(BAR_GO));
    {
      uint32_t u[4];
      do {
#pragma unroll
        for (int i = 0; i < 4; i++) u[i] = ldg_rlx1(gs->FL[par] + 32 * i + lane);
      } while (!__all_sync(~0u, min(min(u[0], u[1]), min(u[2], u[3])) != 0));
      const uint4 m = make_uint4(__ballot_sync(~0u, u[0] == 2), __ballot_sync(~0u, u[1] == 2), __ballot_sync(~0u, u[2] == 2), __ballot_sync(~0u, u[3] == 2));
      if (lane == 0) sts4(hi + OFF_FM, m);
      __syncwarp();
      const uint2 m2 = lds2(hi + OFF_FM + 8 * rI);
      const uint32_t mh = (lds1(hi + OFF_FM + (hI >> 3) * 4) >> (4 * (hI & 7))) & 15;
#pragma unroll 1
      for (int v = 0; v < 8; v++) {
        const int sh = 8 * t + 2 * (v >> 2) + (bI >> 2);
        uint32_t fb = (((m2.x >> sh) & 0x11) | (((m2.y >> sh) & 0x11) << 1)) ^ ((bI & 1) ? 0x33 : 0);
        fb |= mh << 8;
        fb |= half_of(4 * (8 * jI + v) + (g >> 1), 0) << 12;
        fb |= half_of((16 * rI + 4 * (v & 3) + (lane >> 3)) * 4 + (lane & 2), 0) << 13;
        fb |= ((f2 ^ (v >> 2)) & 1) << 14;
        fb |= (((lds1(hi + OFF_FM + (v >> 1) * 4) >> (16 * (v & 1) + (g >> 1))) & 0x1111) ^ (cta >= 56 ? 0x1111 : 0)) << 16;
        sts1(hi + OFF_FB + (v * 32 + lane) * 4, fb);
      }
      __syncwarp();
      if (lane == 0) mbar_arrive(hi + BAR(BAR_FM));
    }
    if (lane == 0) stg1(gs->FL[par ^ 1] + cta, 0u);
#pragma unroll
    for (int i = 0; i < 4; i++) stg4(gs->QP + cta * 512 + (i * 32 + lane) * 4, z);
#pragma unroll
    for (int i = 0; i < 4; i++) stg4(gs->QX[par ^ 1] + cta * 512 + (i * 32 + lane) * 4, z);
    if (lane < 8) stg4(gs->MODA + cta * 32 + lane * 4, z);
    if (lane < 16) stg4(gs->MODB[par ^ 1] + cta * 64 + lane * 4, z);
    mbar_wait(hi + BAR(BAR_FULL + CNT_AT));
    while ((int)(ldg_rlx1(&gs->cnt) - (epoch + 1) * NCTA) < 0) __nanosleep(100);
    if (lane == 0) mbar_arrive(hi + BAR(BAR_CLR));
    TLW(54);
    mbar_wait(hi + BAR(BAR_FULL + U_WUV + 1));
    pace_until(BAR_P5D);
    if (cta < NFF) pace_until(BAR_P7D);
    if (d[0] != 0.f) __trap();
    return;
  }
  if (w == 10) {
    const int m0 = 16 * hI + 2 * jI;
    const int bo = lane & 7;
    const uint32_t epoch = __shfl_sync(~0u, epoch0, 0);
    if (lane == 0) { sts1(hi + OFF_EPOCH, epoch); mbar_arrive(hi + BAR(BAR_EPOCH)); }
    const int par = epoch & 1;
    const uint32_t* MOD = gs->MODB[par];
    PROBE_UNITS(-8, 16);
    PROBE_UNITS(16, 43);
    mbar_wait_b(hi + BAR(BAR_FULL + U_WUV + 2));
    const uint32_t xw0 = ldg_in1(gx + bo * 1024 + m0 * 2), xw1 = ldg_in1(gx + bo * 1024 + m0 * 2 + 16);
    const int mf = m0 + ((g >> 1) & 1) + 8 * (t >> 1), bf = 2 * (g & 1) + (t & 1);
    float ga[4];
    uint32_t gb2;
    {
      uint32_t u[4];
      int it = 0;
      while (true) {
#pragma unroll
        for (int i = 0; i < 4; i++) u[i] = ldg_rlx1(MOD + (m0 + (i & 1) + 8 * (i >> 1)) * 4 + (bo >> 1));
        gb2 = ldg_rlx1(MOD + (1536 + mf) * 4 + bf);
        if (min3(min3(u[0], u[1], u[2]), u[3], gb2) != 0) break;
        if (++it > SPIN_LIMIT) __trap();
      }
#pragma unroll
      for (int i = 0; i < 4; i++) ga[i] = (bo & 1) ? bf_hi(u[i]) : bf_lo(u[i]);
    }
    uint32_t x2a, x2b;
    mbar_wait_b(hi + BAR(BAR_FM));
    const uint32_t fo_ = half_of(cta, 0);
    {
      const uint32_t* const pi = hold(inbox(cta, 6, fo_, 0, (4 * (g >> 1) + t) * 8 + (g & 1) * 4));
      uint32_t* const po = hold(gs->X3B + (g >> 2) * 4096 + (cta >> 6) * 2048 + ((g >> 1) & 1) * 1024 + (cta & 63) * 16 + bo * 2);
      const uint32_t one = 0x3f80u << (8 * (g & 2)), s0 = g < 4 ? one : 0u, s1 = g < 4 ? 0u : one;
      const uint32_t e0 = hold32((g & 1) ? 0u : s0), e1 = hold32((g & 1) ? 0u : s1), o0 = hold32((g & 1) ? s0 : 0u), o1 = hold32((g & 1) ? s1 : 0u);
      const float xf[4] = {holdf(bf_lo(xw0)), holdf(bf_hi(xw0)), holdf(bf_lo(xw1)), holdf(bf_hi(xw1))};
#pragma unroll
      for (int i = 0; i < 4; i++) ga[i] = holdf(ga[i]);
      PROBE_UNITS(43, 48);
      mbar_wait_b(hi + BAR(BAR_P5D));
      backoff(D_X3A);
      float d[4][4];
      poll_vectors<4>(pi, pi + 256, [&](const uint4 (&v)[4]) {
#pragma unroll
        for (int i = 0; i < 4; i++) { d[i][0] = d[i][1] = d[i][2] = d[i][3] = 0.f; mma_v(d[i], v[i], (i & 2) ? o0 : e0, (i & 2) ? o1 : e1); }
      });
      TLW(37);
      float s[4] = {d[0][0] + d[1][0], d[2][1] + d[3][1], d[0][2] + d[1][2], d[2][3] + d[3][3]};
#pragma unroll
      for (int i = 0; i < 4; i++) s[i] += __shfl_xor_sync(~0u, s[i], 8);
#pragma unroll
      for (int i = 0; i < 4; i++) s[i] += __shfl_xor_sync(~0u, s[i], 16);
      x2a = pack_bf16(xf[0] + ga[0] * s[0], xf[1] + ga[1] * s[1]);
      x2b = pack_bf16(xf[2] + ga[2] * s[2], xf[3] + ga[3] * s[3]);
      stg_u64(po, x2a, x2b);
      mbar_wait(hi + BAR(BAR_P5D));
    }
    TLW(20);
    {
      const uint32_t a0 = __shfl_sync(~0u, x2a, 2 * bf), a1 = __shfl_sync(~0u, x2a, 2 * bf + 1);
      const uint32_t b0 = __shfl_sync(~0u, x2b, 2 * bf), b1 = __shfl_sync(~0u, x2b, 2 * bf + 1);
      const uint32_t y0 = (t & 2) ? b0 : a0, y1 = (t & 2) ? b1 : a1;
      const float r0 = holdf((g & 2) ? bf_hi(y0) : bf_lo(y0)), r1 = holdf((g & 2) ? bf_hi(y1) : bf_lo(y1)), gb0 = holdf(bf_lo(gb2)), gb1 = holdf(bf_hi(gb2));
      const uint32_t* const pi = hold(inbox(cta, 4, fo_, 0, (4 * (g >> 2) + t) * 16 + (g & 3) * 4));
      const uint32_t* const pj = hold(inbox(cta, 5, ~fo_, 0, (4 * (g >> 2) + t) * 16 + (g & 3) * 4));
      __nv_bfloat16* const fo = hold(gout + (2 * bf) * 512 + mf);
      const uint32_t one = (g & 1) ? 0x3f800000u : 0x00003f80u;
      const uint32_t s0 = hold32((g & 2) ? 0u : one), s1 = hold32((g & 2) ? one : 0u);
      if (cta < NFF) { mbar_wait_b(hi + BAR(BAR_P7D)); backoff(D_FIN); } else __nanosleep(1000);
      float d[4][4];
      poll_vectors<NFF / 8>(pi, pj, [&](const uint4 (&v)[NFF / 8]) {
#pragma unroll
        for (int i = 0; i < 4; i++) d[i][0] = d[i][1] = d[i][2] = d[i][3] = 0.f;
#pragma unroll
        for (int i = 0; i < NFF / 8; i++) mma_v(d[i & 3], v[i], s0, s1);
      });
      TLW(38);
      const bool up = t & 2;
      float v0 = up ? (d[0][2] + d[1][2]) + (d[2][2] + d[3][2]) : (d[0][0] + d[1][0]) + (d[2][0] + d[3][0]);
      float v1 = up ? (d[0][3] + d[1][3]) + (d[2][3] + d[3][3]) : (d[0][1] + d[1][1]) + (d[2][1] + d[3][1]);
      v0 += __shfl_xor_sync(~0u, v0, 16);
      v1 += __shfl_xor_sync(~0u, v1, 16);
      if (g < 4) {
        asm volatile("st.global.u16 [%0], %1;" ::"l"(fo), "h"(__bfloat16_as_ushort(__float2bfloat16(r0 + gb0 * v0))) : "memory");
        asm volatile("st.global.u16 [%0], %1;" ::"l"(fo + 512), "h"(__bfloat16_as_ushort(__float2bfloat16(r1 + gb1 * v1))) : "memory");
      }
    }
    TLW(23);
    if (cta == 0 && lane == 0) stg1(&gs->epoch, epoch + 1);
    return;
  }

  if (w == 9) {
    mbar_wait(hi + BAR(BAR_EPOCH));
    const int par = lds1(hi + OFF_EPOCH) & 1;
    {
      const uint32_t* px = gs->QX[par] + bI * 8192 + lane * 256 + 63;
      uint32_t x0 = ldg_rlx1(px), x1 = ldg_rlx1(px + 64), x2 = ldg_rlx1(px + 128), x3 = ldg_rlx1(px + 192);
      mbar_wait(hi + BAR(BAR_P2E));
      backoff(D_QX);
      uint32_t donemask = 0;
      while (true) {
        const uint32_t okm = __ballot_sync(~0u, x0 != 0 && x1 != 0 && x2 != 0 && x3 != 0);
        const uint32_t full = okm & (okm >> 1) & (okm >> 2) & (okm >> 3) & 0x11111111u;
        if (((full & ~donemask) >> lane) & 1) mbar_arrive(hi + BAR(BAR_QXG) + 8 * (lane >> 2));
        donemask |= full;
        if (donemask == 0x11111111u) break;
        if (x0 == 0) x0 = ldg_rlx1(px);
        if (x1 == 0) x1 = ldg_rlx1(px + 64);
        if (x2 == 0) x2 = ldg_rlx1(px + 128);
        if (x3 == 0) x3 = ldg_rlx1(px + 192);
      }
    }
    if (lane == 0) {
      mbar_expect(hi + BAR(BAR_XE), 16384 + 4096);
      mbar_wait(hi + BAR(BAR_P0D));
      mbar_wait(hi + BAR(BAR_EMPTY + XE_E));
      mbar_wait(hi + BAR(BAR_FULL + XE_AT));
      TLW(33);
      bulk_load(hi + OFF_XE, gs->XE + cta * 4096, 16384, hi + BAR(BAR_XE));
      bulk_load(hi + OFF_MLS, gs->MLE + hI * 1024, 4096, hi + BAR(BAR_XE));
    }
    return;
  }

  const int wg = w >> 2, wq = w & 3;
  if (p0a) {
    sts4(hi + OFF_R0 + w * 1024 + g * 128 + (((2 * t) ^ g) << 4), make_uint4(silu2(cw0.x), silu2(cw0.y), silu2(cw0.z), silu2(cw0.w)));
    sts4(hi + OFF_R0 + w * 1024 + g * 128 + (((2 * t + 1) ^ g) << 4), make_uint4(silu2(cw1.x), silu2(cw1.y), silu2(cw1.z), silu2(cw1.w)));
    asm volatile("fence.proxy.async.shared::cta;" ::: "memory");
  {
    float v[16];
    const uint32_t u[8] = {xr0.x, xr0.y, xr0.z, xr0.w, xr1.x, xr1.y, xr1.z, xr1.w};
#pragma unroll
    for (int i = 0; i < 8; i++) { v[2 * i] = bf_lo(u[i]); v[2 * i + 1] = bf_hi(u[i]); }
    float s = (((v[0] + v[1]) + (v[2] + v[3])) + ((v[4] + v[5]) + (v[6] + v[7]))) + (((v[8] + v[9]) + (v[10] + v[11])) + ((v[12] + v[13]) + (v[14] + v[15])));
#pragma unroll
    for (int o = 16; o; o >>= 1) s += __shfl_xor_sync(~0u, s, o);
    const float mu = s * (1.f / 512.f);
    float q0 = 0.f, q1 = 0.f;
#pragma unroll
    for (int i = 0; i < 8; i++) { const float a = v[2 * i] - mu, b = v[2 * i + 1] - mu; q0 += a * a; q1 += b * b; }
    float q = q0 + q1;
#pragma unroll
    for (int o = 16; o; o >>= 1) q += __shfl_xor_sync(~0u, q, o);
    const float rs = rsqrtf(q * (1.f / 512.f) + 1e-5f);
    asm volatile("st.shared.u16 [%0], %1;" ::"r"(hi + OFF_P0S + lane * 32 + w * 2), "h"(__bfloat16_as_ushort(__float2bfloat16((bf_lo(xc) - mu) * rs))) : "memory");
    asm volatile("st.shared.u16 [%0], %1;" ::"r"(hi + OFF_P0S + lane * 32 + 16 + w * 2), "h"(__bfloat16_as_ushort(__float2bfloat16((bf_hi(xc) - mu) * rs))) : "memory");
  }
    cbar();
    TL(1);
  }
  if (p0a && wg == 0) {
    uint32_t* const mo = gs->MODA + cta * 32 + wq * 64 + lane;
    const uint32_t xn0 = lds1(hi + OFF_P0S + wq * 256 + lane * 4), xn1 = lds1(hi + OFF_P0S + wq * 256 + 128 + lane * 4);
    float d[4] = {0.f, 0.f, 0.f, 0.f};
    asm volatile("" : "+f"(d[0]), "+f"(d[1]), "+f"(d[2]), "+f"(d[3]) :: "memory");
#pragma unroll 1
    for (int i = 0; i < 4; i++) {
      mbar_wait(hi + BAR(BAR_WA) + 8 * i);
      wg_fence();
#pragma unroll
      for (int ks = 0; ks < 8; ks++) wgmma_n8(d, dlo(slot(8)) + i * 1024 + ks * 128, dlo(OFF_R0) + i * 128 + (ks >> 2) * 64 + (ks & 3) * 2);
      wg_commit();
    }
    wg_wait<0>();
    asm volatile("" : "+f"(d[0]), "+f"(d[1]), "+f"(d[2]), "+f"(d[3]) :: "memory");
    uint32_t y0 = pack_bf16(d[0], d[1]), y1 = pack_bf16(d[2], d[3]);
    if (cta >= 64) { y0 = hmul2(xn0, hadd2(y0, ONE2)); y1 = hmul2(xn1, hadd2(y1, ONE2)); }
    stg1(mo, nz(y0));
    stg1(mo + 32, nz(y1));
    TL(3);
  }
  asm volatile("cp.async.wait_all;" ::: "memory");
  cbar();
  TL(2);
  {
    uint32_t* const qpo = pin(gs->QP + (cta * 256 + tid) * 2);
    uint32_t a[8][4];
    mbar_wait(hi + BAR(BAR_FULL + U_WQ) + 8 * wg); mbar_wait(hi + BAR(BAR_FULL + U_WQ + 2) + 8 * wg);
    load_a_t(a, hi + OFF_R1 + wg * 16384, wq, lane);
    mbar_wait(hi + BAR(BAR_FULL + U_WQ + MOD_AT));
    backoff(D_MOD);
    while (min(min(sa.x, sa.y), min(ca.x, ca.y)) == 0) { sa = ldg_rlx2(modi); ca = ldg_rlx2(modi + 2048); }
    TL(41);
    sts2(hi + OFF_BS + tid * 8, hadd2(ca.x, sa.x), hadd2(ca.y, sa.y));
    cbar();
    float d[4];
    mma128(d, a, hi + OFF_BS + lane * 16);
    stg_u64(qpo, pack_bf16(d[0], d[1]), pack_bf16(d[2], d[3]));
  }
  const uint32_t ckq = clk32();
  cw0 = ldg_in4(gc + g * 1024 + w * 128 + t * 32); cw1 = ldg_in4(gc + g * 1024 + w * 128 + t * 32 + 16);
  TL(6);
  mbar_wait(hi + BAR(BAR_EPOCH));
  const int par = lds1(hi + OFF_EPOCH) & 1;
  uint32_t* const QX = gs->QX[par];
  {
    uint32_t a[8][4];
    {
      const int mi = lane >> 3, r = lane & 7;
      const int row = 16 * w + 8 * (mi & 1) + r;
      mbar_wait(hi + BAR(BAR_FULL + U_WUK) + 16 * wg); mbar_wait(hi + BAR(BAR_FULL + U_WUK + 1) + 16 * wg);
#pragma unroll
      for (int ks = 0; ks < 8; ks++) {
        const int chunk = 2 * ks + (mi >> 1);
        ldsm4(a[ks], hi + OFF_R2 + (ks >> 2) * 16384 + row * 128 + (((chunk & 7) ^ r) << 4));
      }
    }
    TL(8);
    uint32_t* const qxo = pin(QX + ((lane >> 1) * 32 + hI) * 256 + (128 * jI + 16 * w + 8 * (lane & 1)) / 2);
    wait_until(ckq, D_QP);
    sum4_to_smem(qp, qpi, qpi + 1024, hi + OFF_BS2 + (16 * w + g) * 16 + t * 4);
    TL(7);
    cbar();
    float d[4];
    mma128(d, a, hi + OFF_BS2 + lane * 16);
    const float sc = 0.08838834764831845f * 1.4426950408889634f;
    const uint32_t stg = hi + OFF_P0S + 4096 + w * 256;
    stsm2t(stg + (lane & 7) * 32 + ((lane >> 3) & 1) * 16, pack_bf16(d[0] * sc, d[1] * sc), pack_bf16(d[2] * sc, d[3] * sc));
    __syncwarp();
    if (lane < 16) stg_u128(qxo, lds4(stg + lane * 16));
    if (lane == 0) mbar_arrive(hi + BAR(BAR_P2E));
  }
  TL(9);
  uint32_t cf[8] = {cw0.x, cw0.y, cw0.z, cw0.w, cw1.x, cw1.y, cw1.z, cw1.w};
#pragma unroll
  for (int i = 0; i < 8; i++) cf[i] = silu2(cf[i]);
  uint32_t fb = 0;
  {
    const uint32_t* qx = pin(QX + bI * 8192 + w * 1024 + lane * 4);
    mbar_wait(hi + BAR(BAR_QXG) + 8 * w);
    TL(4);
    uint4 v[8];
#pragma unroll
    for (int i = 0; i < 8; i++) v[i] = ldg_u128(qx + i * 128);
    cbar();
    while (true) {
      bool all = true;
#pragma unroll
      for (int i = 0; i < 8; i++) all = all && v[i].w != 0;
      if (all) break;
#pragma unroll
      for (int i = 0; i < 8; i++) if (v[i].w == 0) v[i] = ldg_u128(qx + i * 128);
    }
    TL(5);
#pragma unroll
    for (int i = 0; i < 8; i++) {
      const int hh = (4 * w + (i >> 1)) ^ (16 * rI), ch = 32 * (i & 1) + lane;
      sts4(hi + OFF_R0 + (ch >> 3) * 4096 + hh * 128 + (((ch & 7) ^ (hh & 7)) << 4), v[i]);
    }
    asm volatile("fence.proxy.async.shared::cta;" ::: "memory");
    cbar();
    if (tid == 0) mbar_arrive(hi + BAR(BAR_GO));
  }
  TL(10);

  uint32_t ck1;
  const uint32_t *px, *pm;
  uint32_t *x2o, *x2p;
  {
    float O32[4][16], O16[4][8];
    uint32_t ebar;
    asm("mapa.shared::cluster.u32 %0, %1, %2;" : "=r"(ebar) : "r"(hi + BAR(BAR_EMPTY)), "r"(rI ^ (lane & 1)));
#pragma unroll
    for (int i = 0; i < 16; i++) O32[0][i] = O32[1][i] = O32[2][i] = O32[3][i] = 0.f;
#pragma unroll
    for (int i = 0; i < 4; i++) tie(O32[i]);
    auto pv2 = [&](int T, int WG, auto& O, int mb, int k0, int k1) {
      const int n = 8 * T + 4 * WG + mb;
      const uint32_t da = dlo(SB) + (sizeof(O[0]) == 64 ? n : n - 21) * 512, db = (WG && mb && T == 2) ? dlo(SB) : da + 512, dp = dlo(OFF_PT) + (T & 1) * 256;
#pragma unroll
      for (int ks = k0; ks < k1; ks++) { wgmma_ss<1, 1>(O[mb], da + ks * 128, dp + ks * 2); wgmma_ss<1, 1>(O[mb + 1], db + ks * 128, dp + ks * 2); }
      wg_commit();
    };
    auto pv = [&](int T, int WG, auto& O) { wg_fence(); pv2(T, WG, O, 0, 0, 4); pv2(T, WG, O, 2, 0, 4); };
    auto release = [&](int T, auto& O) {
      wg_wait<0>();
#pragma unroll
      for (int i = 0; i < 4; i++) tie(O[i]);
      if (lane < 2) mbar_arrive_cluster(ebar + 8 * T);
      TL(T < 3 ? 24 + T : 32);
    };
    auto rescale = [&](auto& O) {
#pragma unroll
      for (int jn = 0; jn < (int)(sizeof(O[0]) / 16); jn++) {
        const float2 a = ldsf2(hi + OFF_ALPHA + (8 * jn + 2 * t) * 4);
#pragma unroll
        for (int mb = 0; mb < 4; mb++) { O[mb][4 * jn] *= a.x; O[mb][4 * jn + 1] *= a.y; O[mb][4 * jn + 2] *= a.x; O[mb][4 * jn + 3] *= a.y; }
      }
    };
    uint64_t oe[8];
    uint32_t* const x1e = hold(gs->XE + (((16 * (1 - rI) + 2 * t) * 4 + 2 * wg) * 64 + (cta >> 1)) * 64 + (wq * 8 + g) * 2);
    auto split_o = [&] {
#pragma unroll
      for (int i = 0; i < 8; i++) {
        const int jj = i >> 2, r = 8 + 4 * ((i >> 1) & 1) + (i & 1);
        oe[i] = pair64(pack_bf16(O32[2 * jj][r], O32[2 * jj][r + 2]), (pack_bf16(O32[2 * jj + 1][r], O32[2 * jj + 1][r + 2]) | 1u) ^ par);
      }
#pragma unroll
      for (int i = 0; i < 32; i++) asm volatile("mov.b32 %0, %1;" : "=f"(O16[i >> 3][i & 7]) : "f"(O32[i >> 3][i & 7]));
    };
    auto put_early = [&](int i) { stg_b64(x1e + ((8 * ((i >> 1) & 1) + (i & 1)) * 4 + (i >> 2)) * 4096, oe[i]); };
    auto p0b = [&] {
      const int mi = lane >> 3, r = lane & 7;
      const uint32_t abase = hi + OFF_WM + (64 * w + 16 * (r >> 1) + 2 * (mi >> 1) + (r & 1)) * 32 + (mi & 1) * 16;
      mbar_wait(hi + BAR(BAR_FULL + U_WMOD) + 8 * wg);
      float e0[4] = {0.f, 0.f, 0.f, 0.f}, e1[4] = {0.f, 0.f, 0.f, 0.f};
      uint32_t a[4][4];
#pragma unroll
      for (int ks = 0; ks < 4; ks++) ldsm4t(a[ks], abase + ks * 128);
#pragma unroll
      for (int ks = 0; ks < 4; ks++) mma16816((ks & 1) ? e1 : e0, a[ks], cf[2 * ks], cf[2 * ks + 1]);
      sts4f(hi + OFF_R0 + w * 4096 + 2048 + lane * 16, e0[0] + e1[0], e0[1] + e1[1], e0[2] + e1[2], e0[3] + e1[3]);
    };
    uint32_t* x1l[4];
    auto late_addr = [&] {
      mbar_wait(hi + BAR(BAR_FM));
      fb = lds1(hi + OFF_FB + tid * 4);
#pragma unroll
      for (int i = 0; i < 4; i++)
        x1l[i] = hold(inbox((16 * rI + 2 * t) * 4 + 2 * wg + (bI >> 2), bI & 3, fb, 4 * (i & 1) + (i >> 1), pI * 128 + (wq * 8 + g) * 2));
      px = hold(inbox((cta & ~1) + wg, wq, (fb >> (8 + (jI & 2) + wg)) ^ wq, 0, t * 128 + rI * 64 + 4 * g));
      pm = hold(inbox(cta & ~1, 6, fb, 8 + (jI & 2), 512 + (w * 8 + t) * 8));
      x2o = hold(inbox(4 * hI + (jI >> 1) + (~jI & 2), 7, ~fb, 8 + (jI >> 1) + (~jI & 2), (jI & 1) * 512 + tid * 2));
      x2p = hold(inbox(4 * hI + (jI >> 1) + (jI & 2), 7, ~fb, 8 + (jI >> 1) + (jI & 2), (jI & 1) * 512 + tid * 2));
    };
    auto put_late = [&](int jj) {
#pragma unroll
      for (int i = 0; i < 4; i++) {
        const int jn = i >> 1, e = i & 1, r = 4 * jn + e;
        stg_u64(x1l[i] + (8 * jn + e) * 4 * 16384 + jj * 64, pack_bf16(O16[2 * jj][r], O16[2 * jj][r + 2]), pack_bf16(O16[2 * jj + 1][r], O16[2 * jj + 1][r + 2]));
      }
    };
    auto last_products = [&](int WG, auto&& between) {
      wg_fence();
      pv2(4, WG, O16, 0, 0, 4);
      ck1 = clk32();
      pv2(4, WG, O16, 2, 0, PV_SPLIT);
      between();
      wg_wait<1>();
      tie(O16[0]); tie(O16[1]);
      TL(12);
      put_late(0);
      __syncwarp();
      if (PV_SPLIT < 4) { wg_fence(); pv2(4, WG, O16, 2, PV_SPLIT, 4); }
      wg_wait<0>();
      tie(O16[2]); tie(O16[3]);
      TL(50);
      put_late(1);
    };

    if (wg == 0) {
      float S32[16], S16[8];
      float m_run = -INFINITY;
      float mh[8];
#pragma unroll
      for (int i = 0; i < 16; i++) S32[i] = S16[i & 7] = mh[i & 7] = 0.f;
      const uint32_t ptl = hold32(hi + OFF_PT + (8 * (lane >> 4) + (lane & 7)) * 128 + (((2 * wq + ((lane >> 3) & 1)) ^ (lane & 7)) << 4));
      auto landed = [&](int T) { return __ballot_sync(~0u, mbar_test(hi + BAR(BAR_FULL + 8 * T) + 8 * (lane & 7))); };
      auto softmax = [&](int T, auto& O, auto& S) {
        constexpr int NJ = sizeof(S) / 16;
        wg_wait<0>();
        tie(S);
        if (NJ == 2) TL(T == 4 ? 11 : 52);
        bool over = T == 0;
#pragma unroll 1
        do {
          if (over) {
            float mx[2 * NJ];
#pragma unroll
            for (int jn = 0; jn < NJ; jn++) { mx[2 * jn] = fmaxf(S[4 * jn], S[4 * jn + 2]); mx[2 * jn + 1] = fmaxf(S[4 * jn + 1], S[4 * jn + 3]); }
            float a4[4], a2[2], a1;
            if constexpr (NJ == 4) {
              const bool up = lane & 16;
#pragma unroll
              for (int i = 0; i < 4; i++) { const float send = up ? mx[i] : mx[4 + i]; const float keep = up ? mx[4 + i] : mx[i]; a4[i] = fmaxf(keep, __shfl_xor_sync(~0u, send, 16)); }
            } else {
#pragma unroll
              for (int i = 0; i < 4; i++) { a4[i] = fmaxf(mx[i], __shfl_xor_sync(~0u, mx[i], 16)); if (lane & 16) a4[i] = -INFINITY; }
            }
            {
              const bool up = lane & 8;
#pragma unroll
              for (int i = 0; i < 2; i++) { const float send = up ? a4[i] : a4[2 + i]; const float keep = up ? a4[2 + i] : a4[i]; a2[i] = fmaxf(keep, __shfl_xor_sync(~0u, send, 8)); }
            }
            {
              const bool up = lane & 4;
              const float send = up ? a2[0] : a2[1]; const float keep = up ? a2[1] : a2[0];
              a1 = fmaxf(keep, __shfl_xor_sync(~0u, send, 4));
            }
            stsf(hi + OFF_RED + (wq * 32 + 8 * (g >> 1) + 2 * t + (g & 1)) * 4, a1);
            wg0bar();
            const float mt = fmaxf(fmaxf(ldsf(hi + OFF_RED + lane * 4), ldsf(hi + OFF_RED + 128 + lane * 4)),
                                   fmaxf(ldsf(hi + OFF_RED + 256 + lane * 4), ldsf(hi + OFF_RED + 384 + lane * 4)));
            const float m_new = fmaxf(m_run, ceilf(mt));
            if (wq == 0) { stsf(hi + OFF_MREF + lane * 4, m_new); stsf(hi + OFF_ALPHA + lane * 4, ex2(m_run - m_new)); }
            m_run = m_new;
#pragma unroll
            for (int i = 0; i < 2 * NJ; i++) mh[i] = __shfl_sync(~0u, m_new, 8 * (i >> 1) + 2 * t + (i & 1));
            if (T > 0) { wg0bar(); rescale(O); }
          }
          uint32_t pk[2 * NJ];
          float x[4 * NJ];
#pragma unroll
          for (int i = 0; i < 4 * NJ; i++) x[i] = S[i] - mh[2 * (i >> 2) + (i & 1)];
#pragma unroll
          for (int i = 0; i < 2 * NJ; i++) pk[i] = pack_bf16(ex2(x[2 * i]), ex2(x[2 * i + 1]));
#pragma unroll
          for (int hf = 0; hf < NJ / 2; hf++) stsm4t(ptl + (T & 1) * 4096 + hf * 2048, pk[4 * hf], pk[4 * hf + 1], pk[4 * hf + 2], pk[4 * hf + 3]);
          asm volatile("fence.proxy.async.shared::cta;" ::: "memory");
          if constexpr (NJ == 4) {
#pragma unroll
            for (int i = 0; i < 8; i++) x[i] = fmaxf(x[i], x[i + 8]);
          }
          over = cbar_or(fmaxf(fmaxf(fmaxf(x[0], x[1]), fmaxf(x[2], x[3])), fmaxf(fmaxf(x[4], x[5]), fmaxf(x[6], x[7]))) > 64.f);
        } while (__builtin_expect(over, 0));
        if (NJ == 2) TL(T == 4 ? 34 : 53);
      };
      uint32_t have = 0;
#pragma unroll 1
      for (int T = 0; T < 3; T++) {
        UNROLL(QK_UNROLL)
        for (int jj = 0; jj < 8; jj++) {
          const uint32_t da = dlo(SB) + box_slot(8 * T + jj) * 512, db = dlo(OFF_R0) + jj * 256;
          mbar_wait(hi + BAR(BAR_FULL) + 64 * T + 8 * jj);
          wg_fence();
          wgmma_ss_p(S32, da, db, jj);
#pragma unroll
          for (int ks = 1; ks < 4; ks++) wgmma_ss<0, 1>(S32, da + ks * 2, db + ks * 2);
          wg_commit();
        }
        softmax(T, O32, S32);
        pv(T, 0, O32);
        have = landed(3);
        release(T, O32);
      }
      split_o();
#pragma unroll
      for (int i = 0; i < 4; i++) x1l[i] = nullptr;
      px = pm = x2o = x2p = nullptr;
      p0b();
      TL(27);
#pragma unroll 1
      for (int T = 3;; T++) {
        sfor<0, 8>([&](auto jc) {
          constexpr int jj = decltype(jc)::value;
          const uint32_t da = dlo(SB) + (8 * T + jj - 21) * 512, db = dlo(OFF_R0) + jj * 256;
          if (!((have >> jj) & 1)) mbar_wait(hi + BAR(BAR_FULL) + 64 * T + 8 * jj);
          if (QK_FENCE || jj == 0) wg_fence();
          wgmma_ss<0, jj != 0>(S16, da, db);
#pragma unroll
          for (int ks = 1; ks < 4; ks++) wgmma_ss<0, 1>(S16, da + ks * 2, db + ks * 2);
          if (QK_FENCE || jj == 7) wg_commit();
          if (T == 3) {
#pragma unroll
            for (int i = jj * EARLY_PER; i < min(EARLY_N, (jj + 1) * EARLY_PER); i++) put_early(i);
          }
        });
        softmax(T, O16, S16);
        if (T == 4) break;
        pv(3, 0, O16);
        late_addr();
        have = landed(4);
        mbar_wait(hi + BAR(BAR_FM));
#pragma unroll
        for (int i = EARLY_N; i < 8; i++) put_early(i);
        release(3, O16);
      }
      last_products(0, [] {});
    } else {
      float ls[2] = {0.f, 0.f};
      const int hr = 4 * wq + (lane >> 3);
      const uint32_t ptl = hi + OFF_PT + (tid & 127) * 16;
      auto sum8 = [](const uint4& v) { return ((bf_lo(v.x) + bf_hi(v.x)) + (bf_lo(v.y) + bf_hi(v.y))) + ((bf_lo(v.z) + bf_hi(v.z)) + (bf_lo(v.w) + bf_hi(v.w))); };
      auto row_sum = [](float l) { l += __shfl_xor_sync(~0u, l, 1); l += __shfl_xor_sync(~0u, l, 2); return l + __shfl_xor_sync(~0u, l, 4); };
      auto get_p = [&](auto& O) {
        if (__builtin_expect(cbar_or(false), 0)) {
          cbar_or(false);
          rescale(O);
          ls[0] *= ldsf(hi + OFF_ALPHA + hr * 4);
          if (sizeof(O[0]) == 64) ls[1] *= ldsf(hi + OFF_ALPHA + 64 + hr * 4);
        }
      };
#pragma unroll 1
      for (int T = 0; T < 3; T++) {
        get_p(O32);
        pv(T, 1, O32);
        ls[0] += sum8(lds4(ptl + (T & 1) * 4096));
        ls[1] += sum8(lds4(ptl + (T & 1) * 4096 + 2048));
        release(T, O32);
      }
      split_o();
      {
        const float l0 = row_sum(ls[0]), l1 = row_sum(ls[1]);
        const int hl = hr + 8 * (lane & 2);
        const uint32_t m = lds1(hi + OFF_MREF + hl * 4), l = (__float_as_uint((lane & 2) ? l1 : l0) | 1u) ^ par;
        if (!(lane & 4)) stg4_b128(gs->MLE + ((hl ^ (16 * rI)) * 128 + cta) * 8 + (lane & 1) * 4, make_uint4(m, l, m, l));
#pragma unroll
        for (int i = 0; i < 8; i++) { put_early(i); if (i < 7) backoff(EARLY_GAP); }
      }
      if (!P0B_LATE) p0b();
      get_p(O16);
      pv(3, 1, O16);
      ls[0] += sum8(lds4(ptl + 4096));
      release(3, O16);
      if (P0B_LATE) p0b();
      asm volatile("bar.sync 3, 128;" ::: "memory");
      if (wq < 2) {
        if (tid == 128) mbar_arrive(hi + BAR(BAR_P0D));
        float2 v[8];
#pragma unroll
        for (int i = 0; i < 8; i++) v[i] = ldsf2(hi + OFF_R0 + i * 4096 + 2048 + lane * 16 + wq * 8);
        stg1(gs->MODB[par] + cta * 64 + wq * 32 + lane, nz(pack_bf16(((v[0].x + v[1].x) + (v[2].x + v[3].x)) + ((v[4].x + v[5].x) + (v[6].x + v[7].x)),
                                                                     ((v[0].y + v[1].y) + (v[2].y + v[3].y)) + ((v[4].y + v[5].y) + (v[6].y + v[7].y)))));
        TLW(31);
      }
      late_addr();
      uint32_t* const mlo = hold(inbox((16 * rI + hr) * 4 + (lane & 2), 6, fb, 13, 512 + (cta >> 1) * 8 + (lane & 1) * 4));
      mbar_wait(hi + BAR(BAR_CLR));
      get_p(O16);
      float lf;
      uint32_t mf;
      last_products(1, [&] { mf = lds1(hi + OFF_MREF + hr * 4); lf = ls[0] + sum8(lds4(ptl)); if (ML_FIRST) {
        const uint32_t l = nz(__float_as_uint(row_sum(lf)));
        if (!(lane & 4)) stg4_b128(mlo, make_uint4(mf, l, mf, l));
      } });
      if (!ML_FIRST) {
        const uint32_t l = nz(__float_as_uint(row_sum(lf)));
        if (!(lane & 4)) stg4_b128(mlo, make_uint4(mf, l, mf, l));
      }
    }
  }
  TL(13);

  uint32_t aw[8][4];
  {
    uint2 mle[4];
    uint4 ve[4];
    mbar_wait(hi + BAR(BAR_XE));
#pragma unroll
    for (int i = 0; i < 4; i++) mle[i] = lds2(hi + OFF_MLS + (w * 16 + 2 * t + 8 * (i & 1) + ((hI >> 4) ^ (i >> 1))) * 32);
#pragma unroll
    for (int i = 0; i < 4; i++) ve[i] = lds4(hi + OFF_XE + (w * 8 + t) * 256 + g * 16 + (i >> 1) * 1024 + (i & 1) * 128);
    wait_until(ck1, X1_D0);
    uint2 ml[2];
    uint4 v[4];
#pragma unroll
    for (int i = 0; i < 4; i++) v[i] = ldg_2u64(px + (i >> 1) * 512 + (i & 1) * 32);
#pragma unroll
    for (int i = 0; i < 2; i++) ml[i] = ldg_u64(pm + i * 32);
    TL(43);
#pragma unroll 1
    while (true) {
      uint32_t a = 1u, o = 0u;
#pragma unroll
      for (int i = 0; i < 4; i++) { a &= ve[i].y & ve[i].w & mle[i].y; o |= ve[i].y | ve[i].w | mle[i].y; }
      if (__all_sync(~0u, (par ? ~o : a) & 1)) break;
#pragma unroll
      for (int i = 0; i < 4; i++) {
        ve[i] = ldg_2u64(gs->XE + (cta * 64 + w * 8 + t) * 64 + 4 * g + (i >> 1) * 256 + (i & 1) * 32);
        mle[i] = ldg_u64(gs->MLE + (hI * 128 + w * 16 + 2 * t + 8 * (i & 1) + ((hI >> 4) ^ (i >> 1))) * 8);
      }
      TL(55);
    }
    float M = fmaxf(fmaxf(__uint_as_float(mle[0].x), __uint_as_float(mle[1].x)), fmaxf(__uint_as_float(mle[2].x), __uint_as_float(mle[3].x)));
    M = fmaxf(M, __shfl_xor_sync(~0u, M, 1)); M = fmaxf(M, __shfl_xor_sync(~0u, M, 2));
    uint32_t wb[4];
#pragma unroll
    for (int i = 0; i < 4; i++) wb[i] = pack_bf16(ex2(__uint_as_float(mle[i].x) - M), 0.f);
    float Ls = bf_lo(wb[2]) * __uint_as_float(mle[2].y) + bf_lo(wb[3]) * __uint_as_float(mle[3].y);
    float d0[4] = {0.f, 0.f, 0.f, 0.f}, d1[4] = {0.f, 0.f, 0.f, 0.f};
#pragma unroll
    for (int i = 0; i < 4; i++) mma_v((i & 2) ? d1 : d0, ve[i], shl_clamp(wb[2 + (i >> 1)], 16 * g - 64 * (i & 1)), shl_clamp(wb[2 + (i >> 1)], 16 * g - 64 * (i & 1) - 32));
    uint32_t sel[4][2];
#pragma unroll
    for (int i = 0; i < 4; i++) { sel[i][0] = pin32(shl_clamp(wb[i >> 1], 16 * g - 64 * (i & 1))); sel[i][1] = pin32(shl_clamp(wb[i >> 1], 16 * g - 64 * (i & 1) - 32)); }
    const uint32_t bso = hold32(hi + OFF_BS4 + w * 320 + (16 * (t >> 1) + 2 * g + (t & 1)) * 8), bsi = hold32(hi + OFF_BS4 + g * 320 + t * 16);
    const uint32_t lso = hold32(hi + OFF_BS4 + w * 320 + 256 + t * 4), lsi = hold32(hi + OFF_BS4 + t * 640 + 256);
    TL(14);
    {
      const int mi = lane >> 3, r = lane & 7;
      const uint32_t base = hi + OFF_WUV + wg * 16384 + (mi >> 1) * 8192 + ((r & 6) + 8 * (r & 1)) * 128;
      const int ch = 2 * wq + (mi & 1);
      mbar_wait(hi + BAR(BAR_FULL + U_WUV) + 16 * wg); mbar_wait(hi + BAR(BAR_FULL + U_WUV + 1) + 16 * wg);
#pragma unroll
      for (int ks = 0; ks < 8; ks++) ldsm4t(aw[ks], base + (ks >> 1) * 2048 + (ks & 1) * 128 + ((ch ^ ((r & 6) + (ks & 1))) << 4));
    }
    mbar_wait(hi + BAR(BAR_XE));
#pragma unroll
    for (int i = 0; i < 4; i++) tie(v[i]);
    tie(ml[0]); tie(ml[1]);
    TL(44);
    float e0[4], e1[4];
#pragma unroll 1
    while (true) {
      const bool valid = min(min3(min3(v[0].y, v[0].w, v[1].y), v[1].w, ml[0].y), min3(min3(v[2].y, v[2].w, v[3].y), v[3].w, ml[1].y)) != 0;
      const bool ok = __all_sync(~0u, valid && ml[0].x == mle[0].x && ml[1].x == mle[1].x);
#pragma unroll
      for (int i = 0; i < 4; i++) { e0[i] = d0[i]; e1[i] = d1[i]; }
      mma_v(e0, v[0], sel[0][0], sel[0][1]); mma_v(e1, v[2], sel[2][0], sel[2][1]);
      mma_v(e0, v[1], sel[1][0], sel[1][1]); mma_v(e1, v[3], sel[3][0], sel[3][1]);
      if (ok) break;
      if (__all_sync(~0u, valid)) {
        float M2 = fmaxf(M, fmaxf(__uint_as_float(ml[0].x), __uint_as_float(ml[1].x)));
        M2 = fmaxf(M2, __shfl_xor_sync(~0u, M2, 1)); M2 = fmaxf(M2, __shfl_xor_sync(~0u, M2, 2));
        const float f = ex2(M - M2);
        Ls *= f;
#pragma unroll
        for (int i = 0; i < 4; i++) { d0[i] *= f; d1[i] *= f; }
#pragma unroll
        for (int i = 0; i < 2; i++) { wb[i] = pack_bf16(ex2(__uint_as_float(ml[i].x) - M2), 0.f); mle[i].x = ml[i].x; }
#pragma unroll
        for (int i = 0; i < 4; i++) { sel[i][0] = shl_clamp(wb[i >> 1], 16 * g - 64 * (i & 1)); sel[i][1] = shl_clamp(wb[i >> 1], 16 * g - 64 * (i & 1) - 32); }
      }
#pragma unroll
      for (int i = 0; i < 4; i++) if (v[i].y == 0 || v[i].w == 0) v[i] = ldg_2u64(px + (i >> 1) * 512 + (i & 1) * 32);
#pragma unroll
      for (int i = 0; i < 2; i++) if (ml[i].y == 0) ml[i] = ldg_u64(pm + i * 32);
    }
    TL(15);
    stsf(lso, Ls + bf_lo(wb[0]) * __uint_as_float(ml[0].y) + bf_lo(wb[1]) * __uint_as_float(ml[1].y));
    sts2(bso, pack_bf16(e0[0] + e1[0], e0[1] + e1[1]), pack_bf16(e0[2] + e1[2], e0[3] + e1[3]));
    cbar();
    TL(16);
    float o[4][4] = {{0.f, 0.f, 0.f, 0.f}, {0.f, 0.f, 0.f, 0.f}, {0.f, 0.f, 0.f, 0.f}, {0.f, 0.f, 0.f, 0.f}};
    uint4 b[4];
#pragma unroll
    for (int kk = 0; kk < 4; kk++) b[kk] = lds4(bsi + kk * 64);
    const float4 la = ldsf4(lsi), lb = ldsf4(lsi + 320);
#pragma unroll
    for (int kk = 0; kk < 4; kk++) { mma16816(o[(2 * kk) & 3], aw[2 * kk], b[kk].x, b[kk].y); mma16816(o[(2 * kk + 1) & 3], aw[2 * kk + 1], b[kk].z, b[kk].w); }
    const float ia = rcp((la.x + la.y) + (la.z + la.w)), ib = rcp((lb.x + lb.y) + (lb.z + lb.w));
    const uint32_t y0 = pack_bf16(((o[0][0] + o[1][0]) + (o[2][0] + o[3][0])) * ia, ((o[0][1] + o[1][1]) + (o[2][1] + o[3][1])) * ib);
    const uint32_t y1 = pack_bf16(((o[0][2] + o[1][2]) + (o[2][2] + o[3][2])) * ia, ((o[0][3] + o[1][3]) + (o[2][3] + o[3][3])) * ib);
    stg_u64(x2o, y0, y1);
    stg_u64(x2p, y0, y1);
  }
  const uint32_t ck2 = clk32();
  TL(17);
  {
    uint32_t* const o = hold(inbox(4 * (8 * jI + w) + (g >> 1), 6, fb, 12, (g & 1) * 256 + hI * 8 + 2 * t));
    const uint32_t* const x2i = hold(inbox(cta & ~1, 7, ~fb, 8 + (jI & 2), tid * 2));
    const uint32_t* const x2j = hold(inbox(cta | 1, 7, ~fb, 8 + (jI | 1), tid * 2));
    const uint32_t bso = hold32(hi + OFF_BS5 + (16 * w + g) * 16 + t * 4), bsi = hold32(hi + OFF_BS5 + lane * 16);
    TL(45);
    wait_until(ck2, D_X2);
    uint2 v[4];
#pragma unroll
    for (int i = 0; i < 4; i++) v[i] = ldg_u64(((i & 2) ? x2j : x2i) + (i & 1) * 512);
    mbar_wait(hi + BAR(BAR_FULL + U_WO) + 16 * wg); mbar_wait(hi + BAR(BAR_FULL + U_WO + 1) + 16 * wg);
    load_a_t(aw, hi + OFF_WO + wg * 16384, wq, lane);
    mbar_wait(hi + BAR(BAR_XE));
#pragma unroll
    for (int i = 0; i < 4; i++) tie(v[i]);
    sum4_to_smem(v, x2i, x2j, bso);
    cbar();
    TL(18);
    float d[4];
    mma128(d, aw, bsi);
    stg_u64(o, pack_bf16(d[0], d[1]), pack_bf16(d[2], d[3]));
    if (lane == 0) mbar_arrive(hi + BAR(BAR_P5D));
  }
  const uint32_t ck3 = clk32();
  TL(19);
  if (cta < NFF) {
    const int mi = lane >> 3, r = lane & 7;
    uint32_t a1[4][4], a2[4][4];
    uint32_t bc[8], bs[8], mn;
    const uint32_t* const mbi = gs->MODB[par] + (512 + 64 * w) * 4 + lane;
    do {
      mn = 0xffffffffu;
#pragma unroll
      for (int i = 0; i < 8; i++) { bs[i] = ldg_rlx1(mbi + i * 32); bc[i] = ldg_rlx1(mbi + 2048 + i * 32); }
#pragma unroll
      for (int i = 0; i < 8; i++) mn = min3(mn, bs[i], bc[i]);
    } while (!__all_sync(~0u, mn != 0));
#pragma unroll
    for (int i = 0; i < 8; i++) { bs[i] = movm(bs[i]); bc[i] = hadd2(movm(bc[i]), ONE2); }
    mbar_wait(hi + BAR(BAR_FULL + U_W1) + 8 * wg);
#pragma unroll
    for (int ks = 0; ks < 4; ks++) ldsm4t(a1[ks], hi + OFF_W1 + (64 * w + 16 * ks + 8 * (mi >> 1) + r) * 32 + (mi & 1) * 16);
    {
      float u[4] = {0.f, 0.f, 0.f, 0.f}, vv[4] = {0.f, 0.f, 0.f, 0.f};
#pragma unroll
      for (int ks = 0; ks < 4; ks++) { mma16816(u, a1[ks], bc[2 * ks], bc[2 * ks + 1]); mma16816(vv, a1[ks], bs[2 * ks], bs[2 * ks + 1]); }
      sts4f(hi + OFF_REDU + tid * 16, u[0], u[1], u[2], u[3]);
      sts4f(hi + OFF_REDV + tid * 16, vv[0], vv[1], vv[2], vv[3]);
    }
    cbar();
    const int lp = (tid >> 2) & 31, kq = tid & 3;
    const int fo = (lp >> 2) + 8 * (kq >> 1), bo = 2 * (lp & 3) + (kq & 1);
    float U = 0.f, V = 0.f;
    if (tid < 128) {
#pragma unroll
      for (int i = 0; i < 8; i++) { U += ldsf(hi + OFF_REDU + i * 512 + tid * 4); V += ldsf(hi + OFF_REDV + i * 512 + tid * 4); }
    }
    const uint32_t* xb = hold(gs->X3B + ((cta >> 1) & 1) * 4096 + wg * 2048 + (((fb >> 14) & 1) << 10) + (16 * wq + t) * 16 + 2 * g);
    uint32_t* ox[4];
#pragma unroll
    for (int mb = 0; mb < 4; mb++) ox[mb] = hold(inbox(16 * w + 4 * mb + (g >> 1), 4 + (cta >= 56), fb, 16 + 4 * mb, (cta >= 56 ? cta - 56 : cta) * 16 + (g & 1) * 8 + 2 * t));
    const uint32_t gi = hold32(hi + OFF_REDG + tid * 4);
    const uint32_t h1o = hold32(hi + OFF_H1 + fo * 16 + bo * 2), sti = hold32(hi + OFF_REDS + bo * 64), sto = hold32(hi + OFF_REDS + g * 64 + w * 8);
    const bool w2ok = mbar_test(hi + BAR(BAR_FULL + U_W2) + 8 * wg);
    const uint32_t a2a = hi + OFF_W2 + w * 2048 + (8 * (mi >> 1) + r) * 128;
    if (w2ok) {
#pragma unroll
      for (int mb = 0; mb < 4; mb++) ldsm4t(a2[mb], a2a + (((2 * mb + (mi & 1)) ^ r) << 4));
    }
    TL(46);
    wait_until(ck3, D_X3B);
    float G[2][4], S[2][4];
    bool ok;
#pragma unroll 1
    do {
      uint2 x[4];
#pragma unroll
      for (int ks = 0; ks < 4; ks++) x[ks] = ldg_u64(xb + ks * 64);
      ok = __all_sync(~0u, min(min3(x[0].y, x[1].y, x[2].y), x[3].y) != 0);
#pragma unroll
      for (int i = 0; i < 4; i++) G[0][i] = G[1][i] = S[0][i] = S[1][i] = 0.f;
#pragma unroll
      for (int ks = 0; ks < 4; ks++) {
        const uint32_t s0[4] = {x[ks].x, ONE2, x[ks].y, ONE2};
        mma16816(S[ks & 1], s0, x[ks].x, x[ks].y);
        mma16816(G[ks & 1], a1[ks], hmul2(x[ks].x, bc[2 * ks]), hmul2(x[ks].y, bc[2 * ks + 1]));
      }
    } while (!ok);
    TL(21);
    if ((g >> 1) == t) sts2f(sto, (g & 1) ? S[0][3] + S[1][3] : S[0][2] + S[1][2], (g & 1) ? S[0][1] + S[1][1] : S[0][0] + S[1][0]);
    sts4f(hi + OFF_REDG + tid * 16, G[0][0] + G[1][0], G[0][1] + G[1][1], G[0][2] + G[1][2], G[0][3] + G[1][3]);
    cbar();
    TL(39);
    if (tid < 128) {
      float gv[8];
      float4 sv[4];
#pragma unroll
      for (int i = 0; i < 4; i++) sv[i] = ldsf4(sti + i * 16);
#pragma unroll
      for (int i = 0; i < 8; i++) gv[i] = ldsf(gi + i * 512);
      const float s1 = ((sv[0].x + sv[0].z) + (sv[1].x + sv[1].z)) + ((sv[2].x + sv[2].z) + (sv[3].x + sv[3].z));
      const float s2 = ((sv[0].y + sv[0].w) + (sv[1].y + sv[1].w)) + ((sv[2].y + sv[2].w) + (sv[3].y + sv[3].w));
      const float gs_ = ((gv[0] + gv[1]) + (gv[2] + gv[3])) + ((gv[4] + gv[5]) + (gv[6] + gv[7]));
      const float mu = s1 * (1.f / 512.f);
      const float rs = rsq(fmaxf(s2 * (1.f / 512.f) - mu * mu, 0.f) + 1e-5f);
      const float hv = fmaxf(rs * (gs_ - mu * U) + V, 0.f);
      asm volatile("st.shared.u16 [%0], %1;" ::"r"(h1o), "h"(__bfloat16_as_ushort(__float2bfloat16(hv))) : "memory");
    }
    if (!w2ok) {
      mbar_wait(hi + BAR(BAR_FULL + U_W2) + 8 * wg);
#pragma unroll
      for (int mb = 0; mb < 4; mb++) ldsm4t(a2[mb], a2a + (((2 * mb + (mi & 1)) ^ r) << 4));
    }
    cbar();
    TL(40);
    uint32_t b0, b1;
    ldsm2t(b0, b1, hi + OFF_H1 + (lane & 15) * 16);
#pragma unroll
    for (int mb = 0; mb < 4; mb++) {
      float o[4] = {0.f, 0.f, 0.f, 0.f};
      mma16816(o, a2[mb], b0, b1);
      stg_u64(ox[mb], pack_bf16(o[0], o[1]), pack_bf16(o[2], o[3]));
    }
    TL(22);
    if (lane == 0) mbar_arrive(hi + BAR(BAR_P7D));
  }
}

typedef CUresult (*EncodeTiledFn)(CUtensorMap*, CUtensorMapDataType, cuuint32_t, void*, const cuuint64_t*, const cuuint64_t*,
                                  const cuuint32_t*, const cuuint32_t*, CUtensorMapInterleave, CUtensorMapSwizzle,
                                  CUtensorMapL2promotion, CUtensorMapFloatOOBfill);

void make_map(EncodeTiledFn enc, CUtensorMap* m, const void* base, uint64_t cols, uint64_t rows, uint32_t bc, uint32_t br,
              CUtensorMapSwizzle sw, CUtensorMapL2promotion promo) {
  cuuint64_t dims[2] = {cols, rows};
  cuuint64_t strides[1] = {cols * 2};
  cuuint32_t box[2] = {bc, br};
  cuuint32_t es[2] = {1, 1};
  enc(m, CU_TENSOR_MAP_DATA_TYPE_BFLOAT16, 2, const_cast<void*>(base), dims, strides, box, es, CU_TENSOR_MAP_INTERLEAVE_NONE, sw, promo,
      CU_TENSOR_MAP_FLOAT_OOB_FILL_NONE);
}
void make_map3(EncodeTiledFn enc, CUtensorMap* m, const void* base, uint64_t rows, uint32_t br, uint32_t bb) {
  cuuint64_t dims[3] = {64, rows, 8};
  cuuint64_t strides[2] = {1024, 128};
  cuuint32_t box[3] = {64, br, bb};
  cuuint32_t es[3] = {1, 1, 1};
  enc(m, CU_TENSOR_MAP_DATA_TYPE_BFLOAT16, 3, const_cast<void*>(base), dims, strides, box, es, CU_TENSOR_MAP_INTERLEAVE_NONE,
      CU_TENSOR_MAP_SWIZZLE_128B, CU_TENSOR_MAP_L2_PROMOTION_NONE, CU_TENSOR_MAP_FLOAT_OOB_FILL_NONE);
}

}

extern "C" void kernel_launch(void* const* d_in, const int* in_sizes, int n_in, void* d_out, int out_size) {
  (void)in_sizes; (void)n_in; (void)out_size;
  static EncodeTiledFn enc = nullptr;
  static Scratch* scratch = nullptr;
  if (!enc) {
    void* sp = nullptr;
    cudaGetSymbolAddress(&sp, g_s);
    scratch = (Scratch*)(((uintptr_t)sp + 65535) & ~(uintptr_t)65535);
    void* fn = nullptr;
    cudaDriverEntryPointQueryResult q;
    cudaGetDriverEntryPoint("cuTensorMapEncodeTiled", &fn, cudaEnableDefault, &q);
    enc = (EncodeTiledFn)fn;
    cudaFuncSetAttribute(fused_decode_kernel, cudaFuncAttributeMaxDynamicSharedMemorySize, SMEM_BYTES);
  }
  Params P;
  make_map(enc, &P.ckv, d_in[1], 512, 8 * 4096, 64, 64, CU_TENSOR_MAP_SWIZZLE_128B, CU_TENSOR_MAP_L2_PROMOTION_NONE);
  make_map(enc, &P.wq, d_in[2], 4096, 512, 64, 64, CU_TENSOR_MAP_SWIZZLE_128B, CU_TENSOR_MAP_L2_PROMOTION_NONE);
  make_map(enc, &P.wuk, d_in[3], 4096, 512, 64, 64, CU_TENSOR_MAP_SWIZZLE_128B, CU_TENSOR_MAP_L2_PROMOTION_NONE);
  make_map(enc, &P.wuv, d_in[4], 4096, 512, 64, 64, CU_TENSOR_MAP_SWIZZLE_128B, CU_TENSOR_MAP_L2_PROMOTION_NONE);
  make_map(enc, &P.wo, d_in[5], 512, 4096, 64, 64, CU_TENSOR_MAP_SWIZZLE_128B, CU_TENSOR_MAP_L2_PROMOTION_NONE);
  make_map(enc, &P.w1, d_in[7], 1792, 512, FCH, 256, CU_TENSOR_MAP_SWIZZLE_NONE, PROMO);
  make_map3(enc, &P.w2, d_in[8], 1792, FCH, 4);
  make_map(enc, &P.wma, d_in[10], 3072, 512, 64, 128, CU_TENSOR_MAP_SWIZZLE_128B, CU_TENSOR_MAP_L2_PROMOTION_NONE);
  make_map(enc, &P.wmod, d_in[10], 3072, 512, 16, 256, CU_TENSOR_MAP_SWIZZLE_NONE, PROMO);
  fused_decode_kernel<<<NCTA, NTHREADS, SMEM_BYTES>>>((__nv_bfloat16*)d_out, scratch, (const uint8_t*)d_in[2], (const uint8_t*)d_in[0],
                                                      (const uint8_t*)d_in[9], P);
}
```

```cpp
#include <cuda_runtime.h>
#include <cuda.h>
#include <cuda_bf16.h>
#include <stdint.h>

namespace {

constexpr int NCTA = 128;
constexpr int NTHREADS = 384;
constexpr int FCH = 16;
constexpr int NFF = 1792 / FCH;

constexpr uint32_t SB = 1024;
__host__ __device__ constexpr uint32_t slot(int i) { return SB + i * 8192; }
constexpr uint32_t OFF_R1 = slot(16);
constexpr uint32_t OFF_R2 = slot(20);
constexpr uint32_t OFF_PT = slot(23);
constexpr uint32_t OFF_R0 = slot(24);
constexpr uint32_t OFF_MISC = SB + 229376;
constexpr uint32_t OFF_BARS = OFF_MISC;
constexpr uint32_t OFF_FM = OFF_MISC + 736;
constexpr uint32_t OFF_EPOCH = OFF_MISC + 768;
constexpr uint32_t OFF_TL = OFF_MISC + 784;
constexpr uint32_t OFF_BS = OFF_MISC + 1024;
constexpr uint32_t SMEM_BYTES = 229376 + 3072;
constexpr uint32_t OFF_P0S = OFF_R0 + 24576;
constexpr uint32_t OFF_BS2 = OFF_R0 + 30720;
constexpr uint32_t OFF_RED = OFF_BS;
constexpr uint32_t OFF_ALPHA = OFF_BS + 512;
constexpr uint32_t OFF_MREF = OFF_BS + 640;
constexpr uint32_t OFF_FB = OFF_BS + 1024;
__host__ __device__ constexpr int box_slot(int n) { return n < 23 ? n : n == 23 ? 0 : n - 21; }
constexpr uint32_t OFF_WM = slot(1);
constexpr uint32_t OFF_WUV = slot(19);
constexpr uint32_t OFF_XE = slot(1);
constexpr uint32_t OFF_BS4 = slot(0);
constexpr uint32_t OFF_BS5 = slot(0) + 4096;
constexpr uint32_t OFF_MLS = slot(0) + 4096;
constexpr uint32_t OFF_WO = slot(3);
constexpr uint32_t OFF_W1 = slot(7);
constexpr uint32_t OFF_W2 = slot(9);
constexpr uint32_t OFF_REDG = OFF_R0;
constexpr uint32_t OFF_REDS = OFF_R0 + 4096;
constexpr uint32_t OFF_REDU = OFF_R0 + 8192;
constexpr uint32_t OFF_REDV = OFF_R0 + 12288;
constexpr uint32_t OFF_H1 = OFF_R0 + 16384;

constexpr int BAR_FULL = 8;
constexpr int U_WQ = -8, U_WUK = -4, U_WUV = 40, U_WO = 44, U_W1 = 48, U_W2 = 50, NUNITS = 52, U_WMOD = 52;
constexpr int BAR_EMPTY = 62;
constexpr int BAR_GO = 66, BAR_CLR = 67, BAR_EPOCH = 68;
constexpr int BAR_P2E = 69, BAR_P5D = 70, BAR_P7D = 71;
constexpr int BAR_XE = 72;
constexpr int BAR_FM = 73;
constexpr int BAR_P0D = 74;
constexpr int BAR_WA = 75;
__host__ __device__ constexpr uint32_t BAR(int i) { return OFF_BARS + 8 * i; }
#define CPA_N 4
#define PACE_T0 672
#define PACE_DT 320
#define PACE_DTM 320
#define PACE_NM 10
#define PACE_DTE 330
#define WM0 24
#define WM1 32
#define PACE_GAP 150
#define PACE_DT2 390
#define D_FIN2 2000
#define PROMO CU_TENSOR_MAP_L2_PROMOTION_NONE
#define NPROBE 3
#define WIN_PRE 5
#define WIN_MID 8
#define WIN_END 8
#define WIN_TAIL 4
#define CLR_CLK 220
#define D_MOD 600
#define MOD_AT 3
#define D_QP 1600
#define D_QX 1400
#define QX_AT 5
#define QK_UNROLL 1
#define PV_SPLIT 3
#define XE_AT 37
#define CNT_AT 27
#define X1_D0 900
#define D_X2 200
#define D_X3A 400
#define D_X3B 0
#define D_FIN 600

struct Scratch {
  uint32_t MODA[1024 * 4];
  uint32_t QP[128 * 256 * 2];
  uint32_t MODB[2][2048 * 4];
  uint32_t FL[2][128];
  uint32_t QX[2][8 * 32 * 256];
  uint32_t XE[128 * 64 * 64];
  uint32_t MLE[32 * 128 * 8];
  uint32_t epoch;
  uint32_t pad[31];
  uint32_t cnt;
  alignas(65536) uint32_t X3B[16384];
  uint32_t IN[128][16384];
};
__device__ uint8_t g_s[sizeof(Scratch) + 65536];

#define TL(idx) do {} while (0)
#define TLW(idx) do {} while (0)
#define PROBE_UNITS(a, b) do {} while (0)

struct Params {
  CUtensorMap wma, wq, wuk, wmod, ckv, wuv, wo, w1, w2;
};

__device__ __forceinline__ void mbar_init(uint32_t bar, int cnt) { asm volatile("mbarrier.init.shared::cta.b64 [%0], %1;" ::"r"(bar), "r"(cnt)); }
__device__ __forceinline__ void mbar_expect(uint32_t bar, uint32_t bytes) { asm volatile("mbarrier.arrive.expect_tx.shared::cta.b64 _, [%0], %1;" ::"r"(bar), "r"(bytes) : "memory"); }
__device__ __forceinline__ void mbar_arrive(uint32_t bar) { asm volatile("mbarrier.arrive.shared::cta.b64 _, [%0];" ::"r"(bar) : "memory"); }
__device__ __forceinline__ void mbar_arrive_cluster(uint32_t bar) { asm volatile("mbarrier.arrive.shared::cluster.b64 _, [%0];" ::"r"(bar) : "memory"); }
__device__ __forceinline__ bool mbar_test(uint32_t bar) {
  uint32_t ok;
  asm volatile("{\n.reg .pred p;\nmbarrier.test_wait.parity.shared::cta.b64 p, [%1], 0;\nselp.u32 %0,1,0,p;\n}" : "=r"(ok) : "r"(bar) : "memory");
  return ok;
}
__device__ __forceinline__ uint32_t gtime32() { uint32_t c; asm volatile("mov.u32 %0, %%globaltimer_lo;" : "=r"(c) :: "memory"); return c; }
__device__ __forceinline__ uint32_t clk32() { uint32_t c; asm volatile("{\n.reg .u64 t;\nmov.u64 t, %%clock64;\ncvt.u32.u64 %0, t;\n}" : "=r"(c) :: "memory"); return c; }
__device__ __forceinline__ void wait_until(uint32_t c0, int clocks) { if (clocks > 0) while ((int)(clk32() - c0) < clocks) {} }
__device__ __forceinline__ void backoff(int clocks) { if (clocks > 0) wait_until(clk32(), clocks); }
__device__ __forceinline__ uint32_t pin32(uint32_t p) { asm volatile("" : "+r"(p)); return p; }
template <typename T> __device__ __forceinline__ T* pin(T* p) { asm volatile("" : "+l"(p)); return p; }
__device__ __forceinline__ uint32_t hold32(uint32_t p) { asm volatile("shfl.sync.bfly.b32 %0, %0, 0, 0x1f, 0xffffffff;" : "+r"(p) :: "memory"); return p; }
__device__ __forceinline__ float holdf(float p) { return __uint_as_float(hold32(__float_as_uint(p))); }
template <typename T> __device__ __forceinline__ T* hold(T* p) {
  asm volatile("{\n.reg .b32 a, b;\nmov.b64 {a, b}, %0;\nshfl.sync.bfly.b32 a, a, 0, 0x1f, 0xffffffff;\nshfl.sync.bfly.b32 b, b, 0, 0x1f, 0xffffffff;\nmov.b64 %0, {a, b};\n}" : "+l"(p) :: "memory");
  return p;
}
constexpr int SPIN_LIMIT = 1 << 22;
__device__ __forceinline__ void mbar_wait(uint32_t bar) {
  asm volatile("{\n.reg .pred p;\nMW_LOOP:\nmbarrier.try_wait.parity.shared::cta.b64 p, [%0], 0;\n@!p bra MW_LOOP;\n}" ::"r"(bar) : "memory");
}
__device__ __forceinline__ void mbar_wait_b(uint32_t bar) {
  asm volatile("{\n.reg .pred p;\n.reg .u32 c;\nmov.u32 c, 0;\n"
               "MW_LOOP:\nmbarrier.try_wait.parity.shared::cta.b64 p, [%0], 0;\n@p bra MW_DONE;\n"
               "add.u32 c, c, 1;\nsetp.lt.u32 p, c, 1048576;\n@p bra MW_LOOP;\ntrap;\nMW_DONE:\n}"
               ::"r"(bar) : "memory");
}
__device__ __forceinline__ void tma2d(uint32_t dst, const CUtensorMap* m, int c0, int c1, uint32_t bar, uint64_t pol) {
  asm volatile("cp.async.bulk.tensor.2d.shared::cluster.global.mbarrier::complete_tx::bytes.L2::cache_hint [%0], [%1, {%3,%4}], [%2], %5;"
               ::"r"(dst), "l"(m), "r"(bar), "r"(c0), "r"(c1), "l"(pol) : "memory");
}
__device__ __forceinline__ void tma2d_both(uint32_t dst, const CUtensorMap* m, int c0, int c1, uint32_t bar, uint64_t pol) {
  asm volatile("cp.async.bulk.tensor.2d.shared::cluster.global.mbarrier::complete_tx::bytes.multicast::cluster.L2::cache_hint [%0], [%1, {%3,%4}], [%2], %6, %5;"
               ::"r"(dst), "l"(m), "r"(bar), "r"(c0), "r"(c1), "l"(pol), "h"((uint16_t)3) : "memory");
}
__device__ __forceinline__ void tma3d(uint32_t dst, const CUtensorMap* m, int c0, int c1, int c2, uint32_t bar, uint64_t pol) {
  asm volatile("cp.async.bulk.tensor.3d.shared::cluster.global.mbarrier::complete_tx::bytes.L2::cache_hint [%0], [%1, {%3,%4,%5}], [%2], %6;"
               ::"r"(dst), "l"(m), "r"(bar), "r"(c0), "r"(c1), "r"(c2), "l"(pol) : "memory");
}
__device__ __forceinline__ void tma4d(uint32_t dst, const CUtensorMap* m, int c0, int c3, uint32_t bar, uint64_t pol) {
  asm volatile("cp.async.bulk.tensor.4d.shared::cluster.global.mbarrier::complete_tx::bytes.L2::cache_hint [%0], [%1, {%3,%6,%6,%4}], [%2], %5;"
               ::"r"(dst), "l"(m), "r"(bar), "r"(c0), "r"(c3), "l"(pol), "r"(0) : "memory");
}
__device__ __forceinline__ void tma2d_nohint(uint32_t dst, const CUtensorMap* m, int c0, int c1, uint32_t bar) {
  asm volatile("cp.async.bulk.tensor.2d.shared::cluster.global.mbarrier::complete_tx::bytes [%0], [%1, {%3,%4}], [%2];"
               ::"r"(dst), "l"(m), "r"(bar), "r"(c0), "r"(c1) : "memory");
}
__device__ __forceinline__ void bulk_load(uint32_t dst, const void* src, uint32_t bytes, uint32_t bar) {
  asm volatile("cp.async.bulk.shared::cluster.global.mbarrier::complete_tx::bytes [%0], [%1], %2, [%3];" ::"r"(dst), "l"(src), "r"(bytes), "r"(bar) : "memory");
}
__device__ __forceinline__ void cbar() { asm volatile("bar.sync 1, 256;" ::: "memory"); }
__device__ __forceinline__ void wg0bar() { asm volatile("bar.sync 2, 128;" ::: "memory"); }
__device__ __forceinline__ bool cbar_or(bool p) {
  uint32_t r;
  asm volatile("{\n.reg .pred p, q;\nsetp.ne.u32 p, %1, 0;\nbarrier.cta.red.or.aligned.pred q, 1, 256, p;\nselp.u32 %0, 1, 0, q;\n}" : "=r"(r) : "r"((uint32_t)p) : "memory");
  return r;
}

__device__ __forceinline__ uint32_t ldg_rlx1(const void* p) { uint32_t v; asm volatile("ld.relaxed.gpu.global.u32 %0, [%1];" : "=r"(v) : "l"(p) : "memory"); return v; }
__device__ __forceinline__ void stg4(void* p, uint4 v) { asm volatile("st.relaxed.gpu.global.v4.u32 [%0], {%1,%2,%3,%4};" ::"l"(p), "r"(v.x), "r"(v.y), "r"(v.z), "r"(v.w) : "memory"); }
__device__ __forceinline__ void stg1(void* p, uint32_t a) { asm volatile("st.relaxed.gpu.global.u32 [%0], %1;" ::"l"(p), "r"(a) : "memory"); }
__device__ __forceinline__ uint32_t nz(uint32_t w) { uint32_t r; asm("max.u32 %0, %1, 1;" : "=r"(r) : "r"(w)); return r; }
__device__ __forceinline__ uint32_t min3(uint32_t a, uint32_t b, uint32_t c) { return min(min(a, b), c); }

__device__ __forceinline__ uint32_t pack_bf16(float lo, float hi) { uint32_t r; asm("cvt.rn.bf16x2.f32 %0, %1, %2;" : "=r"(r) : "f"(hi), "f"(lo)); return r; }
__device__ __forceinline__ float bf_lo(uint32_t w) { return __uint_as_float(w << 16); }
__device__ __forceinline__ float bf_hi(uint32_t w) { return __uint_as_float(w & 0xffff0000u); }
__device__ __forceinline__ float ex2(float x) { float r; asm("ex2.approx.ftz.f32 %0, %1;" : "=f"(r) : "f"(x)); return r; }
__device__ __forceinline__ float rcp(float x) { float r; asm("rcp.approx.ftz.f32 %0, %1;" : "=f"(r) : "f"(x)); return r; }
__device__ __forceinline__ float rsq(float x) { float r; asm("rsqrt.approx.ftz.f32 %0, %1;" : "=f"(r) : "f"(x)); return r; }
__device__ __forceinline__ uint32_t silu2(uint32_t c) {
  const float a = bf_lo(c), b = bf_hi(c);
  return pack_bf16(__fdividef(a, 1.f + __expf(-a)), __fdividef(b, 1.f + __expf(-b)));
}
__device__ __forceinline__ uint32_t shl_clamp(uint32_t x, int s) { uint32_t r; asm("shl.b32 %0, %1, %2;" : "=r"(r) : "r"(x), "r"(s)); return r; }

__device__ __forceinline__ void ldsm4(uint32_t (&r)[4], uint32_t a) { asm volatile("ldmatrix.sync.aligned.m8n8.x4.shared.b16 {%0,%1,%2,%3}, [%4];" : "=r"(r[0]), "=r"(r[1]), "=r"(r[2]), "=r"(r[3]) : "r"(a) : "memory"); }
__device__ __forceinline__ void ldsm4t(uint32_t (&r)[4], uint32_t a) { asm volatile("ldmatrix.sync.aligned.m8n8.x4.trans.shared.b16 {%0,%1,%2,%3}, [%4];" : "=r"(r[0]), "=r"(r[1]), "=r"(r[2]), "=r"(r[3]) : "r"(a) : "memory"); }
__device__ __forceinline__ void ldsm2t(uint32_t& r0, uint32_t& r1, uint32_t a) { asm volatile("ldmatrix.sync.aligned.m8n8.x2.trans.shared.b16 {%0,%1}, [%2];" : "=r"(r0), "=r"(r1) : "r"(a) : "memory"); }
__device__ __forceinline__ void stsm4t(uint32_t a, uint32_t r0, uint32_t r1, uint32_t r2, uint32_t r3) { asm volatile("stmatrix.sync.aligned.m8n8.x4.trans.shared.b16 [%0], {%1,%2,%3,%4};" ::"r"(a), "r"(r0), "r"(r1), "r"(r2), "r"(r3) : "memory"); }
__device__ __forceinline__ void stsm2t(uint32_t a, uint32_t r0, uint32_t r1) { asm volatile("stmatrix.sync.aligned.m8n8.x2.trans.shared.b16 [%0], {%1,%2};" ::"r"(a), "r"(r0), "r"(r1) : "memory"); }
__device__ __forceinline__ void mma16816(float (&d)[4], const uint32_t (&a)[4], uint32_t b0, uint32_t b1) {
  asm volatile("mma.sync.aligned.m16n8k16.row.col.f32.bf16.bf16.f32 {%0,%1,%2,%3}, {%4,%5,%6,%7}, {%8,%9}, {%0,%1,%2,%3};"
               : "+f"(d[0]), "+f"(d[1]), "+f"(d[2]), "+f"(d[3]) : "r"(a[0]), "r"(a[1]), "r"(a[2]), "r"(a[3]), "r"(b0), "r"(b1));
}
__device__ __forceinline__ void mma_v(float (&d)[4], const uint4& a, uint32_t b0, uint32_t b1) {
  asm volatile("mma.sync.aligned.m16n8k16.row.col.f32.bf16.bf16.f32 {%0,%1,%2,%3}, {%4,%5,%6,%7}, {%8,%9}, {%0,%1,%2,%3};"
               : "+f"(d[0]), "+f"(d[1]), "+f"(d[2]), "+f"(d[3]) : "r"(a.x), "r"(a.y), "r"(a.z), "r"(a.w), "r"(b0), "r"(b1));
}
__device__ __forceinline__ void sts1(uint32_t a, uint32_t v) { asm volatile("st.shared.u32 [%0], %1;" ::"r"(a), "r"(v) : "memory"); }
__device__ __forceinline__ void sts2(uint32_t a, uint32_t x, uint32_t y) { asm volatile("st.shared.v2.u32 [%0], {%1,%2};" ::"r"(a), "r"(x), "r"(y) : "memory"); }
__device__ __forceinline__ void sts4(uint32_t a, uint4 v) { asm volatile("st.shared.v4.u32 [%0], {%1,%2,%3,%4};" ::"r"(a), "r"(v.x), "r"(v.y), "r"(v.z), "r"(v.w) : "memory"); }
__device__ __forceinline__ void sts4f(uint32_t a, float x, float y, float z, float w) { asm volatile("st.shared.v4.f32 [%0], {%1,%2,%3,%4};" ::"r"(a), "f"(x), "f"(y), "f"(z), "f"(w) : "memory"); }
__device__ __forceinline__ void sts2f(uint32_t a, float x, float y) { asm volatile("st.shared.v2.f32 [%0], {%1,%2};" ::"r"(a), "f"(x), "f"(y) : "memory"); }
__device__ __forceinline__ void stsf(uint32_t a, float v) { asm volatile("st.shared.f32 [%0], %1;" ::"r"(a), "f"(v) : "memory"); }
__device__ __forceinline__ uint32_t lds1(uint32_t a) { uint32_t v; asm volatile("ld.shared.u32 %0, [%1];" : "=r"(v) : "r"(a) : "memory"); return v; }
__device__ __forceinline__ uint2 lds2(uint32_t a) { uint2 v; asm volatile("ld.shared.v2.u32 {%0,%1}, [%2];" : "=r"(v.x), "=r"(v.y) : "r"(a) : "memory"); return v; }
__device__ __forceinline__ float ldsf(uint32_t a) { float v; asm volatile("ld.shared.f32 %0, [%1];" : "=f"(v) : "r"(a) : "memory"); return v; }
__device__ __forceinline__ float2 ldsf2(uint32_t a) { float2 v; asm volatile("ld.shared.v2.f32 {%0,%1}, [%2];" : "=f"(v.x), "=f"(v.y) : "r"(a) : "memory"); return v; }
__device__ __forceinline__ float4 ldsf4(uint32_t a) { float4 v; asm volatile("ld.shared.v4.f32 {%0,%1,%2,%3}, [%4];" : "=f"(v.x), "=f"(v.y), "=f"(v.z), "=f"(v.w) : "r"(a) : "memory"); return v; }
__device__ __forceinline__ uint4 lds4(uint32_t a) { uint4 v; asm volatile("ld.shared.v4.u32 {%0,%1,%2,%3}, [%4];" : "=r"(v.x), "=r"(v.y), "=r"(v.z), "=r"(v.w) : "r"(a) : "memory"); return v; }

__device__ __forceinline__ void wg_fence() { asm volatile("wgmma.fence.sync.aligned;" ::: "memory"); }
__device__ __forceinline__ void wg_commit() { asm volatile("wgmma.commit_group.sync.aligned;" ::: "memory"); }
template <int N> __device__ __forceinline__ void wg_wait() { asm volatile("wgmma.wait_group.sync.aligned %0;" ::"n"(N) : "memory"); }
__host__ __device__ constexpr uint32_t dlo(uint32_t addr) { return (addr >> 4) | 0x10000u; }
constexpr uint32_t ONE2 = 0x3f803f80u;
template <int TA, int ACC> __device__ __forceinline__ void wgmma_ss(float (&d)[16], uint32_t da, uint32_t db) {
  asm volatile("{\n.reg .b64 da, db;\nmov.b64 da, {%16, 0x40000040};\nmov.b64 db, {%17, 0x40000040};\n"
               "wgmma.mma_async.sync.aligned.m64n32k16.f32.bf16.bf16 {%0,%1,%2,%3,%4,%5,%6,%7,%8,%9,%10,%11,%12,%13,%14,%15}, da, db, %18, 1, 1, %19, 0;\n}"
               : "+f"(d[0]), "+f"(d[1]), "+f"(d[2]), "+f"(d[3]), "+f"(d[4]), "+f"(d[5]), "+f"(d[6]), "+f"(d[7]),
                 "+f"(d[8]), "+f"(d[9]), "+f"(d[10]), "+f"(d[11]), "+f"(d[12]), "+f"(d[13]), "+f"(d[14]), "+f"(d[15])
               : "r"(da), "r"(db), "n"(ACC), "n"(TA));
}
template <int TA, int ACC> __device__ __forceinline__ void wgmma_ss(float (&d)[8], uint32_t da, uint32_t db) {
  asm volatile("{\n.reg .b64 da, db;\nmov.b64 da, {%8, 0x40000040};\nmov.b64 db, {%9, 0x40000040};\n"
               "wgmma.mma_async.sync.aligned.m64n16k16.f32.bf16.bf16 {%0,%1,%2,%3,%4,%5,%6,%7}, da, db, %10, 1, 1, %11, 0;\n}"
               : "+f"(d[0]), "+f"(d[1]), "+f"(d[2]), "+f"(d[3]), "+f"(d[4]), "+f"(d[5]), "+f"(d[6]), "+f"(d[7])
               : "r"(da), "r"(db), "n"(ACC), "n"(TA));
}
__device__ __forceinline__ void wgmma_n8(float (&d)[4], uint32_t da, uint32_t db) {
  asm volatile("{\n.reg .b64 da, db;\nmov.b64 da, {%4, 0x40000040};\nmov.b64 db, {%5, 0x40000040};\n"
               "wgmma.mma_async.sync.aligned.m64n8k16.f32.bf16.bf16 {%0,%1,%2,%3}, da, db, 1, 1, 1, 1, 0;\n}"
               : "+f"(d[0]), "+f"(d[1]), "+f"(d[2]), "+f"(d[3]) : "r"(da), "r"(db));
}
__device__ __forceinline__ void wgmma_ss_p(float (&d)[16], uint32_t da, uint32_t db, int acc) {
  asm volatile("{\n.reg .pred p;\n.reg .b64 da, db;\nsetp.ne.b32 p, %18, 0;\nmov.b64 da, {%16, 0x40000040};\nmov.b64 db, {%17, 0x40000040};\n"
               "wgmma.mma_async.sync.aligned.m64n32k16.f32.bf16.bf16 {%0,%1,%2,%3,%4,%5,%6,%7,%8,%9,%10,%11,%12,%13,%14,%15}, da, db, p, 1, 1, 0, 0;\n}"
               : "+f"(d[0]), "+f"(d[1]), "+f"(d[2]), "+f"(d[3]), "+f"(d[4]), "+f"(d[5]), "+f"(d[6]), "+f"(d[7]),
                 "+f"(d[8]), "+f"(d[9]), "+f"(d[10]), "+f"(d[11]), "+f"(d[12]), "+f"(d[13]), "+f"(d[14]), "+f"(d[15])
               : "r"(da), "r"(db), "r"(acc));
}
__device__ __forceinline__ void wgmma_ss_p(float (&d)[8], uint32_t da, uint32_t db, int acc) {
  asm volatile("{\n.reg .pred p;\n.reg .b64 da, db;\nsetp.ne.b32 p, %10, 0;\nmov.b64 da, {%8, 0x40000040};\nmov.b64 db, {%9, 0x40000040};\n"
               "wgmma.mma_async.sync.aligned.m64n16k16.f32.bf16.bf16 {%0,%1,%2,%3,%4,%5,%6,%7}, da, db, p, 1, 1, 0, 0;\n}"
               : "+f"(d[0]), "+f"(d[1]), "+f"(d[2]), "+f"(d[3]), "+f"(d[4]), "+f"(d[5]), "+f"(d[6]), "+f"(d[7])
               : "r"(da), "r"(db), "r"(acc));
}
template <int K> __device__ __forceinline__ void tie(float (&d)[K]) {
#pragma unroll
  for (int i = 0; i < K; i += 8)
    asm volatile("" : "+f"(d[i]), "+f"(d[i + 1]), "+f"(d[i + 2]), "+f"(d[i + 3]), "+f"(d[i + 4]), "+f"(d[i + 5]), "+f"(d[i + 6]), "+f"(d[i + 7]) :: "memory");
}
template <bool C, typename A, typename B> __device__ __forceinline__ auto& pick(A& a, B& b) { if constexpr (C) return a; else return b; }
__device__ __forceinline__ void tie(uint4& v) { asm volatile("" : "+r"(v.x), "+r"(v.y), "+r"(v.z), "+r"(v.w) :: "memory"); }
__device__ __forceinline__ void tie(uint2& v) { asm volatile("" : "+r"(v.x), "+r"(v.y) :: "memory"); }
#define PRAGMA(x) _Pragma(#x)
#define UNROLL(n) PRAGMA(unroll n)
template <int I> struct IC { static constexpr int value = I; };
template <int B, int E, typename F> __device__ __forceinline__ void sfor(F&& f) { if constexpr (B < E) { f(IC<B>{}); sfor<B + 1, E>(f); } }

__device__ __forceinline__ uint2 ldg_u64(const void* p) {
  uint2 v; asm volatile("{\n.reg .b64 a;\nld.relaxed.gpu.global.b64 a, [%2];\nmov.b64 {%0,%1}, a;\n}" : "=r"(v.x), "=r"(v.y) : "l"(p) : "memory"); return v;
}
__device__ __forceinline__ uint4 ldg_2u64(const void* p) {
  uint4 v; asm volatile("{\n.reg .b64 a, b;\nld.relaxed.gpu.global.v2.b64 {a, b}, [%4];\nmov.b64 {%0,%1}, a;\nmov.b64 {%2,%3}, b;\n}" : "=r"(v.x), "=r"(v.y), "=r"(v.z), "=r"(v.w) : "l"(p) : "memory"); return v;
}
__device__ __forceinline__ uint4 ldg_u128(const void* p) {
  uint4 v; asm volatile("{\n.reg .b64 a, b;\n.reg .b128 q;\nld.relaxed.gpu.global.b128 q, [%4];\nmov.b128 {a, b}, q;\nmov.b64 {%0,%1}, a;\nmov.b64 {%2,%3}, b;\n}" : "=r"(v.x), "=r"(v.y), "=r"(v.z), "=r"(v.w) : "l"(p) : "memory"); return v;
}
__device__ __forceinline__ void stg_u64(void* p, uint32_t x, uint32_t y) {
  asm volatile("{\n.reg .b64 a;\nmov.b64 a, {%1,%2};\nst.relaxed.gpu.global.b64 [%0], a;\n}" ::"l"(p), "r"(x), "r"(nz(y)) : "memory");
}
__device__ __forceinline__ uint64_t pair64(uint32_t x, uint32_t y) { uint64_t a; asm("mov.b64 %0, {%1,%2};" : "=l"(a) : "r"(x), "r"(y)); return a; }
__device__ __forceinline__ void stg_b64(void* p, uint64_t a) { asm volatile("st.relaxed.gpu.global.b64 [%0], %1;" ::"l"(p), "l"(a) : "memory"); }
__device__ __forceinline__ void stg4_b128(void* p, uint4 v) {
  asm volatile("{\n.reg .b64 a, b;\n.reg .b128 q;\nmov.b64 a, {%1,%2};\nmov.b64 b, {%3,%4};\nmov.b128 q, {a, b};\nst.relaxed.gpu.global.b128 [%0], q;\n}" ::"l"(p), "r"(v.x), "r"(v.y), "r"(v.z), "r"(v.w) : "memory");
}
__device__ __forceinline__ void stg_u128(void* p, uint4 v) {
  asm volatile("{\n.reg .b64 a, b;\n.reg .b128 q;\nmov.b64 a, {%1,%2};\nmov.b64 b, {%3,%4};\nmov.b128 q, {a, b};\nst.relaxed.gpu.global.b128 [%0], q;\n}" ::"l"(p), "r"(v.x), "r"(v.y), "r"(v.z), "r"(nz(v.w)) : "memory");
}
__device__ __forceinline__ uint32_t hmul2(uint32_t a, uint32_t b) { uint32_t r; asm("mul.rn.bf16x2 %0, %1, %2;" : "=r"(r) : "r"(a), "r"(b)); return r; }
__device__ __forceinline__ uint32_t hadd2(uint32_t a, uint32_t b) { uint32_t r; asm("add.rn.bf16x2 %0, %1, %2;" : "=r"(r) : "r"(a), "r"(b)); return r; }
__device__ __forceinline__ uint32_t hfma2(uint32_t a, uint32_t b, uint32_t c) { uint32_t r; asm("fma.rn.bf16x2 %0, %1, %2, %3;" : "=r"(r) : "r"(a), "r"(b), "r"(c)); return r; }
__device__ __forceinline__ uint32_t movm(uint32_t a) { uint32_t d; asm volatile("movmatrix.sync.aligned.m8n8.trans.b16 %0, %1;" : "=r"(d) : "r"(a)); return d; }
__device__ __forceinline__ uint2 ldg_rlx2(const void* p) { uint2 v; asm volatile("ld.relaxed.gpu.global.v2.u32 {%0,%1}, [%2];" : "=r"(v.x), "=r"(v.y) : "l"(p) : "memory"); return v; }
__device__ __forceinline__ uint4 ldg_in4(const void* p) { uint4 v; asm volatile("ld.global.nc.v4.u32 {%0,%1,%2,%3}, [%4];" : "=r"(v.x), "=r"(v.y), "=r"(v.z), "=r"(v.w) : "l"(p) : "memory"); return v; }
__device__ __forceinline__ uint32_t ldg_in1(const void* p) { uint32_t v; asm volatile("ld.global.nc.u32 %0, [%1];" : "=r"(v) : "l"(p)); return v; }
__device__ __forceinline__ uint32_t ldg_inh(const void* p) { uint16_t v; asm volatile("ld.global.nc.u16 %0, [%1];" : "=h"(v) : "l"(p) : "memory"); return v; }

__device__ __forceinline__ void sum4_to_smem(uint2 (&v)[4], const uint32_t* x, const uint32_t* y, uint32_t dst) {
  uint32_t r0, r1;
#pragma unroll 1
  while (true) {
    const bool ok = __all_sync(~0u, min(min3(v[0].y, v[1].y, v[2].y), v[3].y) != 0);
    r0 = pack_bf16((bf_lo(v[0].x) + bf_lo(v[1].x)) + (bf_lo(v[2].x) + bf_lo(v[3].x)), (bf_hi(v[0].x) + bf_hi(v[1].x)) + (bf_hi(v[2].x) + bf_hi(v[3].x)));
    r1 = pack_bf16((bf_lo(v[0].y) + bf_lo(v[1].y)) + (bf_lo(v[2].y) + bf_lo(v[3].y)), (bf_hi(v[0].y) + bf_hi(v[1].y)) + (bf_hi(v[2].y) + bf_hi(v[3].y)));
    sts1(dst, r0);
    sts1(dst + 128, r1);
    if (ok) break;
#pragma unroll
    for (int i = 0; i < 4; i++) v[i] = ldg_u64(((i & 2) ? y : x) + (i & 1) * 512);
  }
}
__device__ __forceinline__ void load_a_t(uint32_t (&a)[8][4], uint32_t box, int wq, int lane) {
  const int mi = lane >> 3, r = lane & 7;
  const uint32_t base = box + (8 * (mi >> 1) + r) * 128 + (((2 * wq + (mi & 1)) ^ r) << 4);
#pragma unroll
  for (int ks = 0; ks < 8; ks++) ldsm4t(a[ks], base + ks * 2048);
}
__device__ __forceinline__ void mma128(float (&d)[4], const uint32_t (&a)[8][4], uint32_t bs) {
  float e[4][4] = {{0.f, 0.f, 0.f, 0.f}, {0.f, 0.f, 0.f, 0.f}, {0.f, 0.f, 0.f, 0.f}, {0.f, 0.f, 0.f, 0.f}};
  uint32_t b[4][4];
#pragma unroll
  for (int kk = 0; kk < 4; kk++) ldsm4t(b[kk], bs + 32 * kk * 16);
#pragma unroll
  for (int kk = 0; kk < 4; kk++) { mma16816(e[(2 * kk) & 3], a[2 * kk], b[kk][0], b[kk][1]); mma16816(e[(2 * kk + 1) & 3], a[2 * kk + 1], b[kk][2], b[kk][3]); }
#pragma unroll
  for (int i = 0; i < 4; i++) d[i] = (e[0][i] + e[1][i]) + (e[2][i] + e[3][i]);
}
template <int NL, typename F> __device__ __forceinline__ void poll_vectors(const uint32_t* p, const uint32_t* q, F&& f) {
  int it = 0;
  bool ok;
#pragma unroll 1
  do {
    if (++it > SPIN_LIMIT) __trap();
    uint4 v[NL];
#pragma unroll
    for (int i = 0; i < NL; i++) v[i] = ldg_2u64(i < NL / 2 ? p + i * 128 : q + (i - NL / 2) * 128);
    f(v);
    uint32_t m0 = min(v[0].y, v[0].w), m1 = min(v[1].y, v[1].w);
#pragma unroll
    for (int i = 2; i < NL; i += 2) { m0 = min3(m0, v[i].y, v[i].w); m1 = min3(m1, v[i + 1].y, v[i + 1].w); }
    ok = __all_sync(~0u, min(m0, m1) != 0);
  } while (!ok);
}

__global__ void __cluster_dims__(2, 1, 1) __launch_bounds__(NTHREADS, 1)
fused_decode_kernel(__nv_bfloat16* __restrict__ gout, Scratch* __restrict__ gs, const uint8_t* __restrict__ gwq,
                    const uint8_t* __restrict__ gx, const uint8_t* __restrict__ gc,
                    const __grid_constant__ Params P) {
  extern __shared__ __align__(1024) uint8_t smem_raw[];
  const uint32_t hi = pin32((uint32_t)__cvta_generic_to_shared(smem_raw) - SB);
  const int tid = threadIdx.x, lane = tid & 31;
  const int w = __shfl_sync(0xffffffffu, tid >> 5, 0);
  const int cta = blockIdx.x;
  const int g = lane >> 2, t = lane & 3;
  const int hI = cta >> 2, jI = cta & 3;
  const int bI = cta >> 4, pI = (cta >> 1) & 7, rI = cta & 1;

  uint32_t epoch0 = 0;
  if (tid == 320) epoch0 = ldg_rlx1(&gs->epoch);
  const bool p0a = (cta & 7) == 0;
  uint4 cw0, cw1, xr0, xr1;
  uint32_t xc;
  if (w < 8) {
    const uint8_t* src = gwq + (size_t)(128 * jI + (tid >> 4)) * 8192 + hI * 256 + (tid & 15) * 16;
    const uint32_t dst = hi + OFF_R1 + ((tid >> 3) & 1) * 16384 + (tid >> 4) * 128 + (((tid ^ (tid >> 4)) & 7) << 4);
    if (p0a) {
      cw0 = ldg_in4(gc + g * 1024 + w * 128 + t * 32); cw1 = ldg_in4(gc + g * 1024 + w * 128 + t * 32 + 16);
      xr0 = ldg_in4(gx + w * 1024 + lane * 16); xr1 = ldg_in4(gx + w * 1024 + 512 + lane * 16);
      xc = ldg_in1(gx + w * 1024 + (cta & 63) * 16 + lane * 4);
    } else {
#pragma unroll
      for (int i = 0; i < CPA_N; i++) asm volatile("cp.async.cg.shared.global [%0], [%1], 16;" ::"r"(dst + i * 2048), "l"(src + i * 16 * 8192) : "memory");
    }
  }
  auto half_of = [&](int c, int k) { return ((lds1(hi + OFF_FM + (c >> 5) * 4) >> (c & 31)) ^ k) & 1; };
  auto inbox = [&](int c, int k, uint32_t bits, int pos, int off) { return gs->IN[0] + (uint32_t)(c * 16384 + k * 2048 + off + (((bits >> pos) & 1) << 10)); };
  auto front_unit = [&](int k, uint64_t pol) {
    tma2d(hi + OFF_R1 + ((k & 4) + 2 * (k & 1) + ((k >> 1) & 1)) * 8192, k < 4 ? &P.wq : &P.wuk, 128 * hI + 64 * (k & 1), 128 * jI + 64 * ((k >> 1) & 1), hi + BAR(k), pol);
  };
  uint32_t tnext = 0;
  if (tid == 256) {
    tnext = gtime32() + PACE_T0;
    if (hi & 0xffffff) __trap();
    if (p0a) {
#pragma unroll
      for (int i = 0; i < 4; i++) mbar_init(hi + BAR(BAR_WA + i), 1);
      asm volatile("fence.mbarrier_init.release.cluster;" ::: "memory");
      uint64_t pol; asm volatile("createpolicy.fractional.L2::evict_first.b64 %0, 1.0;" : "=l"(pol));
#pragma unroll
      for (int i = 0; i < 4; i++) tma2d(hi + slot(8 + 2 * i), &P.wma, 8 * cta, 128 * i, hi + BAR(BAR_WA + i), pol);
    }
    asm volatile("prefetch.tensormap [%0];" ::"l"(&P.wq) : "memory");
    TLW(42);
  } else if (tid == 288) {
#pragma unroll
    for (int i = 0; i < BAR_WA; i++)
      mbar_init(hi + BAR(i), (i >= BAR_EMPTY && i < BAR_EMPTY + 4) ? 16 : (i >= BAR_P2E && i <= BAR_P7D) ? 8 : 1);
    asm volatile("fence.mbarrier_init.release.cluster;" ::: "memory");
  }
  __syncthreads();
  TL(0);

  if (w == 8) {
    if (p0a && lane < 4) mbar_expect(hi + BAR(BAR_WA) + 8 * lane, 16384);
    mbar_expect(hi + BAR(0) + 8 * lane, (lane < CPA_N / 2 && !p0a) ? 0 : 8192);
    if (p0a) tnext -= (CPA_N / 2) * PACE_DT;
    if (lane < BAR_EMPTY - 32) mbar_expect(hi + BAR(32) + 8 * lane, 8192);
    __syncwarp();
    const int h = hI, j = jI;
    if (lane == 0) {
      uint64_t pol; asm volatile("createpolicy.fractional.L2::evict_first.b64 %0, 1.0;" : "=l"(pol));
      auto pace = [&](int dt) { if (PACE_DT > 0) { while ((int)(gtime32() - tnext) < 0) {} tnext += dt; } };
      asm volatile("prefetch.tensormap [%0];" ::"l"(&P.wuk) : "memory");
      asm volatile("prefetch.tensormap [%0];" ::"l"(&P.wmod) : "memory");
      asm volatile("prefetch.tensormap [%0];" ::"l"(&P.ckv) : "memory");
#pragma unroll 1
      for (int k = p0a ? 0 : CPA_N / 2; k < 8; k++) { if (k >= WIN_PRE) mbar_wait(hi + BAR(0) + 8 * (k - WIN_PRE)); pace(PACE_DT); front_unit(k, pol); }
      bool go = false;
      const int row0 = bI * 4096 + (cta & 15) * 64;
#pragma unroll 1
      for (int n = 0; n < 24; n++) {
        if (n == 8) mbar_wait(hi + BAR(BAR_P2E));
        if (n == 23) mbar_wait(hi + BAR(BAR_EMPTY));
        if (!go) go = mbar_test(hi + BAR(BAR_GO));
        mbar_wait(hi + BAR(BAR_FULL) + 8 * (n - (go ? WIN_MID : WIN_PRE)));
        pace(n >= PACE_NM ? PACE_DTM : PACE_DT);
        tma2d(hi + slot(box_slot(n)), &P.ckv, (n & 7) * 64, row0 + (n >> 3) * 1024, hi + BAR(BAR_FULL) + 8 * n, pol);
      }
      asm volatile("prefetch.tensormap [%0];" ::"l"(&P.wuv) : "memory");
      asm volatile("prefetch.tensormap [%0];" ::"l"(&P.wo) : "memory");
      asm volatile("prefetch.tensormap [%0];" ::"l"(&P.w1) : "memory");
      asm volatile("prefetch.tensormap [%0];" ::"l"(&P.w2) : "memory");
      const int row1 = bI * 4096 + (24 + pI) * 64;
      tnext += rI * (PACE_DT / 2) - PACE_DT / 4;
#pragma unroll 1
      for (int n = 24 + rI; n < 40; n += 2) {
        const int c = n - 23;
        const int m = c >= 2 * WIN_END ? n - 2 * WIN_END : 23 - (2 * WIN_END - c) / 2;
        mbar_wait(hi + BAR(BAR_FULL) + 8 * m);
        if ((n & ~1) == WM0) { pace(PACE_DTE); tma2d_nohint(hi + OFF_WM, &P.wmod, 1024 + 16 * cta, 0, hi + BAR(BAR_FULL + U_WMOD)); }
        if ((n & ~1) == WM1) { pace(PACE_DTE); tma2d_nohint(hi + OFF_WM + 8192, &P.wmod, 1024 + 16 * cta, 256, hi + BAR(BAR_FULL + U_WMOD + 1)); }
        mbar_wait(hi + BAR(BAR_EMPTY) + ((n - 21) & ~7));
        pace(PACE_DTE);
        tma2d_both(hi + slot(n - 21), &P.ckv, (n & 7) * 64, row1 + (n >> 3) * 512, hi + BAR(BAR_FULL) + 8 * n, pol);
      }
      mbar_wait(hi + BAR(BAR_EMPTY + 2));
      tnext += PACE_GAP;
#pragma unroll 1
      for (int n = U_WUV; n < (cta < NFF ? NUNITS : U_W1); n++) {
        const int c = n - 39, u = n & 3;
        mbar_wait(hi + BAR(BAR_FULL) + 8 * (c >= WIN_TAIL ? n - WIN_TAIL : 39 - 2 * (WIN_TAIL - c)));
        if (n == U_WO) mbar_wait(hi + BAR(BAR_EMPTY + 3));
        const uint32_t bar = hi + BAR(BAR_FULL) + 8 * n, dst = hi + slot(n < U_WO ? n - 21 : n - 41);
        pace(PACE_DT2);
        if (n < U_WO) tma4d(dst, &P.wuv, 128 * h + 64 * (u >> 1), 8 * j + 4 * (u & 1), bar, pol);
        else if (n < U_W1) tma2d(dst, &P.wo, 128 * j + 64 * (u & 1), 128 * h + 64 * (u >> 1), bar, pol);
        else if (n < U_W2) tma2d_nohint(dst, &P.w1, FCH * cta, 256 * (u & 1), bar);
        else tma3d(dst, &P.w2, 0, FCH * cta, 4 * (u & 1), bar, pol);
      }
    }
    return;
  }

  if (w == 11) {
    const uint4 z = make_uint4(0, 0, 0, 0);
    uint32_t f = 0, f2 = 0;
    {
      uint32_t* const p = ((lane & 2) ? gs->X3B + 4 * 2048 + cta * 8 : gs->IN[cta] + 4 * 2048 + 960) + ((lane & 1) << 10);
      if (lane < 8) stg4(p + (lane & 4), z);
      __syncwarp();
      uint32_t best = ~0u;
#pragma unroll 1
      for (int i = 0; i < 4 * NPROBE + (int)(hi & 1); i++) {
        uint32_t v = 0;
        const uint32_t c0 = clk32();
        if (lane == (i & 3)) asm volatile("atom.relaxed.gpu.global.exch.b32 %0, [%1], %2;" : "=r"(v) : "l"(p), "r"(i) : "memory");
        v = __shfl_sync(~0u, v, i & 3);
        const uint32_t dt = clk32() - c0 + (v >> 31);
        if (lane == (i & 3)) best = min(best, dt);
      }
      const uint32_t m = __ballot_sync(~0u, best < __shfl_xor_sync(~0u, best, 1));
      f = (m >> 1) & 1; f2 = (m >> 3) & 1;
    }
    mbar_wait(hi + BAR(BAR_EPOCH));
    const uint32_t epoch = lds1(hi + OFF_EPOCH);
    const int par = epoch & 1;
    if (lane == 0) stg1(gs->FL[par] + cta, 1 + f);
    TLW(51);
    mbar_wait(hi + BAR(BAR_P2E));
#pragma unroll 1
    for (int i = 0; i < 16; i++) {
      const uint32_t c0 = clk32();
      uint32_t* p = gs->IN[cta] + (i >> 1) * 2048 + (((f ^ (i >> 1)) & 1) << 10) + (i & 1) * 512 + lane * 4;
#pragma unroll
      for (int q = 0; q < 4; q++) stg4(p + q * 128, z);
      if (i == 0 && lane < 16) stg4(gs->X3B + cta * 64 + lane * 4, z);
      wait_until(c0, CLR_CLK);
    }
    TLW(35);
    asm volatile("fence.acq_rel.gpu;" ::: "memory");
    __syncwarp();
    if (lane == 0) asm volatile("red.relaxed.gpu.global.add.u32 [%0], 1;" ::"l"(&gs->cnt) : "memory");
    TLW(36);
    mbar_wait(hi + BAR(BAR_GO));
    {
      uint32_t u[4];
      do {
#pragma unroll
        for (int i = 0; i < 4; i++) u[i] = ldg_rlx1(gs->FL[par] + 32 * i + lane);
      } while (!__all_sync(~0u, min(min(u[0], u[1]), min(u[2], u[3])) != 0));
      const uint4 m = make_uint4(__ballot_sync(~0u, u[0] == 2), __ballot_sync(~0u, u[1] == 2), __ballot_sync(~0u, u[2] == 2), __ballot_sync(~0u, u[3] == 2));
      if (lane == 0) sts4(hi + OFF_FM, m);
      __syncwarp();
      const uint2 m2 = lds2(hi + OFF_FM + 8 * rI);
      const uint32_t mh = (lds1(hi + OFF_FM + (hI >> 3) * 4) >> (4 * (hI & 7))) & 15;
#pragma unroll 1
      for (int v = 0; v < 8; v++) {
        const int sh = 8 * t + 2 * (v >> 2) + (bI >> 2);
        uint32_t fb = (((m2.x >> sh) & 0x11) | (((m2.y >> sh) & 0x11) << 1)) ^ ((bI & 1) ? 0x33 : 0);
        fb |= mh << 8;
        fb |= half_of(4 * (8 * jI + v) + (g >> 1), 0) << 12;
        fb |= half_of((16 * rI + 4 * (v & 3) + (lane >> 3)) * 4 + (lane & 2), 0) << 13;
        fb |= ((f2 ^ (v >> 2)) & 1) << 14;
        fb |= (((lds1(hi + OFF_FM + (v >> 1) * 4) >> (16 * (v & 1) + (g >> 1))) & 0x1111) ^ (cta >= 56 ? 0x1111 : 0)) << 16;
        sts1(hi + OFF_FB + (v * 32 + lane) * 4, fb);
      }
      __syncwarp();
      if (lane == 0) mbar_arrive(hi + BAR(BAR_FM));
    }
    if (lane == 0) stg1(gs->FL[par ^ 1] + cta, 0u);
#pragma unroll
    for (int i = 0; i < 4; i++) stg4(gs->QP + cta * 512 + (i * 32 + lane) * 4, z);
#pragma unroll
    for (int i = 0; i < 4; i++) stg4(gs->QX[par ^ 1] + cta * 512 + (i * 32 + lane) * 4, z);
    if (lane < 8) stg4(gs->MODA + cta * 32 + lane * 4, z);
    if (lane < 16) stg4(gs->MODB[par ^ 1] + cta * 64 + lane * 4, z);
    mbar_wait(hi + BAR(BAR_FULL + CNT_AT));
    while ((int)(ldg_rlx1(&gs->cnt) - (epoch + 1) * NCTA) < 0) __nanosleep(100);
    if (lane == 0) mbar_arrive(hi + BAR(BAR_CLR));
    TLW(54);
    return;
  }
  if (w == 10) {
    const int m0 = 16 * hI + 2 * jI;
    const int bo = lane & 7;
    const uint32_t epoch = __shfl_sync(~0u, epoch0, 0);
    if (lane == 0) { sts1(hi + OFF_EPOCH, epoch); mbar_arrive(hi + BAR(BAR_EPOCH)); }
    const int par = epoch & 1;
    const uint32_t* MOD = gs->MODB[par];
    PROBE_UNITS(-8, 16);
    PROBE_UNITS(16, 43);
    mbar_wait_b(hi + BAR(BAR_FULL + U_WUV + 2));
    const uint32_t xw0 = ldg_in1(gx + bo * 1024 + m0 * 2), xw1 = ldg_in1(gx + bo * 1024 + m0 * 2 + 16);
    const int mf = m0 + ((g >> 1) & 1) + 8 * (t >> 1), bf = 2 * (g & 1) + (t & 1);
    float ga[4];
    uint32_t gb2;
    {
      uint32_t u[4];
      int it = 0;
      while (true) {
#pragma unroll
        for (int i = 0; i < 4; i++) u[i] = ldg_rlx1(MOD + (m0 + (i & 1) + 8 * (i >> 1)) * 4 + (bo >> 1));
        gb2 = ldg_rlx1(MOD + (1536 + mf) * 4 + bf);
        if (min3(min3(u[0], u[1], u[2]), u[3], gb2) != 0) break;
        if (++it > SPIN_LIMIT) __trap();
      }
#pragma unroll
      for (int i = 0; i < 4; i++) ga[i] = (bo & 1) ? bf_hi(u[i]) : bf_lo(u[i]);
    }
    uint32_t x2a, x2b;
    mbar_wait_b(hi + BAR(BAR_FM));
    const uint32_t fo_ = half_of(cta, 0);
    {
      const uint32_t* const pi = hold(inbox(cta, 6, fo_, 0, (4 * (g >> 1) + t) * 8 + (g & 1) * 4));
      uint32_t* const po = hold(gs->X3B + (g >> 2) * 4096 + (cta >> 6) * 2048 + ((g >> 1) & 1) * 1024 + (cta & 63) * 16 + bo * 2);
      const uint32_t one = 0x3f80u << (8 * (g & 2)), s0 = g < 4 ? one : 0u, s1 = g < 4 ? 0u : one;
      const uint32_t e0 = hold32((g & 1) ? 0u : s0), e1 = hold32((g & 1) ? 0u : s1), o0 = hold32((g & 1) ? s0 : 0u), o1 = hold32((g & 1) ? s1 : 0u);
      const float xf[4] = {holdf(bf_lo(xw0)), holdf(bf_hi(xw0)), holdf(bf_lo(xw1)), holdf(bf_hi(xw1))};
#pragma unroll
      for (int i = 0; i < 4; i++) ga[i] = holdf(ga[i]);
      PROBE_UNITS(43, 48);
      mbar_wait_b(hi + BAR(BAR_P5D));
      backoff(D_X3A);
      float d[4][4];
      poll_vectors<4>(pi, pi + 256, [&](const uint4 (&v)[4]) {
#pragma unroll
        for (int i = 0; i < 4; i++) { d[i][0] = d[i][1] = d[i][2] = d[i][3] = 0.f; mma_v(d[i], v[i], (i & 2) ? o0 : e0, (i & 2) ? o1 : e1); }
      });
      TLW(37);
      float s[4] = {d[0][0] + d[1][0], d[2][1] + d[3][1], d[0][2] + d[1][2], d[2][3] + d[3][3]};
#pragma unroll
      for (int i = 0; i < 4; i++) s[i] += __shfl_xor_sync(~0u, s[i], 8);
#pragma unroll
      for (int i = 0; i < 4; i++) s[i] += __shfl_xor_sync(~0u, s[i], 16);
      x2a = pack_bf16(xf[0] + ga[0] * s[0], xf[1] + ga[1] * s[1]);
      x2b = pack_bf16(xf[2] + ga[2] * s[2], xf[3] + ga[3] * s[3]);
      stg_u64(po, x2a, x2b);
      mbar_wait(hi + BAR(BAR_P5D));
    }
    TLW(20);
    {
      const uint32_t a0 = __shfl_sync(~0u, x2a, 2 * bf), a1 = __shfl_sync(~0u, x2a, 2 * bf + 1);
      const uint32_t b0 = __shfl_sync(~0u, x2b, 2 * bf), b1 = __shfl_sync(~0u, x2b, 2 * bf + 1);
      const uint32_t y0 = (t & 2) ? b0 : a0, y1 = (t & 2) ? b1 : a1;
      const float r0 = holdf((g & 2) ? bf_hi(y0) : bf_lo(y0)), r1 = holdf((g & 2) ? bf_hi(y1) : bf_lo(y1)), gb0 = holdf(bf_lo(gb2)), gb1 = holdf(bf_hi(gb2));
      const uint32_t* const pi = hold(inbox(cta, 4, fo_, 0, (4 * (g >> 2) + t) * 16 + (g & 3) * 4));
      const uint32_t* const pj = hold(inbox(cta, 5, ~fo_, 0, (4 * (g >> 2) + t) * 16 + (g & 3) * 4));
      __nv_bfloat16* const fo = hold(gout + (2 * bf) * 512 + mf);
      const uint32_t one = (g & 1) ? 0x3f800000u : 0x00003f80u;
      const uint32_t s0 = hold32((g & 2) ? 0u : one), s1 = hold32((g & 2) ? one : 0u);
      if (cta < NFF) { mbar_wait_b(hi + BAR(BAR_P7D)); backoff(D_FIN); } else backoff(D_FIN2);
      float d[4][4];
      poll_vectors<NFF / 8>(pi, pj, [&](const uint4 (&v)[NFF / 8]) {
#pragma unroll
        for (int i = 0; i < 4; i++) d[i][0] = d[i][1] = d[i][2] = d[i][3] = 0.f;
#pragma unroll
        for (int i = 0; i < NFF / 8; i++) mma_v(d[i & 3], v[i], s0, s1);
      });
      TLW(38);
      const bool up = t & 2;
      float v0 = up ? (d[0][2] + d[1][2]) + (d[2][2] + d[3][2]) : (d[0][0] + d[1][0]) + (d[2][0] + d[3][0]);
      float v1 = up ? (d[0][3] + d[1][3]) + (d[2][3] + d[3][3]) : (d[0][1] + d[1][1]) + (d[2][1] + d[3][1]);
      v0 += __shfl_xor_sync(~0u, v0, 16);
      v1 += __shfl_xor_sync(~0u, v1, 16);
      if (g < 4) {
        asm volatile("st.global.u16 [%0], %1;" ::"l"(fo), "h"(__bfloat16_as_ushort(__float2bfloat16(r0 + gb0 * v0))) : "memory");
        asm volatile("st.global.u16 [%0], %1;" ::"l"(fo + 512), "h"(__bfloat16_as_ushort(__float2bfloat16(r1 + gb1 * v1))) : "memory");
      }
    }
    TLW(23);
    if (cta == 0 && lane == 0) stg1(&gs->epoch, epoch + 1);
    return;
  }

  if (w == 9) {
    if (lane == 0) {
      mbar_expect(hi + BAR(BAR_XE), 16384 + 4096);
      mbar_wait(hi + BAR(BAR_P0D));
      mbar_wait(hi + BAR(BAR_EMPTY + 3));
      mbar_wait(hi + BAR(BAR_FULL + XE_AT));
      TLW(33);
      bulk_load(hi + OFF_XE, gs->XE + cta * 4096, 16384, hi + BAR(BAR_XE));
      bulk_load(hi + OFF_MLS, gs->MLE + hI * 1024, 4096, hi + BAR(BAR_XE));
    }
    return;
  }

  const int wg = w >> 2, wq = w & 3;
  if (!p0a) {
    asm volatile("cp.async.wait_all;" ::: "memory");
    cw0 = ldg_in4(gc + g * 1024 + w * 128 + t * 32); cw1 = ldg_in4(gc + g * 1024 + w * 128 + t * 32 + 16);
  }
  uint32_t cf[8] = {cw0.x, cw0.y, cw0.z, cw0.w, cw1.x, cw1.y, cw1.z, cw1.w};
#pragma unroll
  for (int i = 0; i < 8; i++) cf[i] = silu2(cf[i]);
  if (p0a) {
    sts4(hi + OFF_R0 + w * 1024 + g * 128 + (((2 * t) ^ g) << 4), make_uint4(cf[0], cf[1], cf[2], cf[3]));
    sts4(hi + OFF_R0 + w * 1024 + g * 128 + (((2 * t + 1) ^ g) << 4), make_uint4(cf[4], cf[5], cf[6], cf[7]));
    asm volatile("fence.proxy.async.shared::cta;" ::: "memory");
  {
    float v[16];
    const uint32_t u[8] = {xr0.x, xr0.y, xr0.z, xr0.w, xr1.x, xr1.y, xr1.z, xr1.w};
#pragma unroll
    for (int i = 0; i < 8; i++) { v[2 * i] = bf_lo(u[i]); v[2 * i + 1] = bf_hi(u[i]); }
    float s = (((v[0] + v[1]) + (v[2] + v[3])) + ((v[4] + v[5]) + (v[6] + v[7]))) + (((v[8] + v[9]) + (v[10] + v[11])) + ((v[12] + v[13]) + (v[14] + v[15])));
#pragma unroll
    for (int o = 16; o; o >>= 1) s += __shfl_xor_sync(~0u, s, o);
    const float mu = s * (1.f / 512.f);
    float q0 = 0.f, q1 = 0.f;
#pragma unroll
    for (int i = 0; i < 8; i++) { const float a = v[2 * i] - mu, b = v[2 * i + 1] - mu; q0 += a * a; q1 += b * b; }
    float q = q0 + q1;
#pragma unroll
    for (int o = 16; o; o >>= 1) q += __shfl_xor_sync(~0u, q, o);
    const float rs = rsqrtf(q * (1.f / 512.f) + 1e-5f);
    asm volatile("st.shared.u16 [%0], %1;" ::"r"(hi + OFF_P0S + lane * 32 + w * 2), "h"(__bfloat16_as_ushort(__float2bfloat16((bf_lo(xc) - mu) * rs))) : "memory");
    asm volatile("st.shared.u16 [%0], %1;" ::"r"(hi + OFF_P0S + lane * 32 + 16 + w * 2), "h"(__bfloat16_as_ushort(__float2bfloat16((bf_hi(xc) - mu) * rs))) : "memory");
  }
    cbar();
    TL(1);
  }
  if (p0a && wg == 0) {
    uint32_t* const mo = gs->MODA + cta * 32 + wq * 64 + lane;
    const uint32_t xn0 = lds1(hi + OFF_P0S + wq * 256 + lane * 4), xn1 = lds1(hi + OFF_P0S + wq * 256 + 128 + lane * 4);
    float d[4] = {0.f, 0.f, 0.f, 0.f};
    asm volatile("" : "+f"(d[0]), "+f"(d[1]), "+f"(d[2]), "+f"(d[3]) :: "memory");
#pragma unroll 1
    for (int i = 0; i < 4; i++) {
      mbar_wait(hi + BAR(BAR_WA) + 8 * i);
      wg_fence();
#pragma unroll
      for (int ks = 0; ks < 8; ks++) wgmma_n8(d, dlo(slot(8)) + i * 1024 + ks * 128, dlo(OFF_R0) + i * 128 + (ks >> 2) * 64 + (ks & 3) * 2);
      wg_commit();
    }
    wg_wait<0>();
    asm volatile("" : "+f"(d[0]), "+f"(d[1]), "+f"(d[2]), "+f"(d[3]) :: "memory");
    uint32_t y0 = pack_bf16(d[0], d[1]), y1 = pack_bf16(d[2], d[3]);
    if (cta >= 64) { y0 = hmul2(xn0, hadd2(y0, ONE2)); y1 = hmul2(xn1, hadd2(y1, ONE2)); }
    stg1(mo, nz(y0));
    stg1(mo + 32, nz(y1));
    TL(3);
  }
  cbar();
  TL(2);
  {
    uint32_t* const qpo = pin(gs->QP + (cta * 256 + tid) * 2);
    const uint32_t* const modi = pin(gs->MODA + 512 * jI + tid * 2);
    uint32_t a[8][4];
    mbar_wait(hi + BAR(BAR_FULL + U_WQ) + 8 * wg); mbar_wait(hi + BAR(BAR_FULL + U_WQ + 2) + 8 * wg);
    load_a_t(a, hi + OFF_R1 + wg * 16384, wq, lane);
    mbar_wait(hi + BAR(BAR_FULL + U_WQ + MOD_AT));
    backoff(D_MOD);
    TL(48);
    uint2 sa, ca;
    do { sa = ldg_rlx2(modi); ca = ldg_rlx2(modi + 2048); } while (min(min(sa.x, sa.y), min(ca.x, ca.y)) == 0);
    TL(41);
    sts2(hi + OFF_BS + tid * 8, hadd2(ca.x, sa.x), hadd2(ca.y, sa.y));
    cbar();
    float d[4];
    mma128(d, a, hi + OFF_BS + lane * 16);
    stg_u64(qpo, pack_bf16(d[0], d[1]), pack_bf16(d[2], d[3]));
  }
  const uint32_t ckq = clk32();
  TL(6);
  mbar_wait(hi + BAR(BAR_EPOCH));
  const int par = lds1(hi + OFF_EPOCH) & 1;
  uint32_t* const QX = gs->QX[par];
  {
    uint32_t a[8][4];
    {
      const int mi = lane >> 3, r = lane & 7;
      const int row = 16 * w + 8 * (mi & 1) + r;
      mbar_wait(hi + BAR(BAR_FULL + U_WUK) + 16 * wg); mbar_wait(hi + BAR(BAR_FULL + U_WUK + 1) + 16 * wg);
#pragma unroll
      for (int ks = 0; ks < 8; ks++) {
        const int chunk = 2 * ks + (mi >> 1);
        ldsm4(a[ks], hi + OFF_R2 + (ks >> 2) * 16384 + row * 128 + (((chunk & 7) ^ r) << 4));
      }
    }
    TL(8);
    uint32_t* const qxo = pin(QX + ((lane >> 1) * 32 + hI) * 256 + (128 * jI + 16 * w + 8 * (lane & 1)) / 2);
    const uint32_t* const qpi = pin(gs->QP + (hI * 4 * 256 + tid) * 2);
    mbar_wait(hi + BAR(BAR_FULL - 1));
    wait_until(ckq, D_QP);
    TL(29);
    uint2 qp[4];
#pragma unroll
    for (int i = 0; i < 4; i++) qp[i] = ldg_u64(qpi + i * 512);
    sum4_to_smem(qp, qpi, qpi + 1024, hi + OFF_BS2 + (16 * w + g) * 16 + t * 4);
    TL(7);
    cbar();
    float d[4];
    mma128(d, a, hi + OFF_BS2 + lane * 16);
    const float sc = 0.08838834764831845f * 1.4426950408889634f;
    const uint32_t stg = hi + OFF_P0S + 4096 + w * 256;
    stsm2t(stg + (lane & 7) * 32 + ((lane >> 3) & 1) * 16, pack_bf16(d[0] * sc, d[1] * sc), pack_bf16(d[2] * sc, d[3] * sc));
    __syncwarp();
    if (lane < 16) stg_u128(qxo, lds4(stg + lane * 16));
    if (lane == 0) mbar_arrive(hi + BAR(BAR_P2E));
  }
  const uint32_t ckx = clk32();
  TL(9);
  uint32_t fb = 0;
  {
    const uint32_t* qx = pin(QX + bI * 8192 + w * 1024 + lane * 4);
    mbar_wait(hi + BAR(BAR_FULL + QX_AT));
    wait_until(ckx, D_QX);
    TL(4);
    uint4 v[8];
#pragma unroll
    for (int i = 0; i < 8; i++) v[i] = ldg_u128(qx + i * 128);
    cbar();
    while (true) {
      bool all = true;
#pragma unroll
      for (int i = 0; i < 8; i++) all = all && v[i].w != 0;
      if (all) break;
#pragma unroll
      for (int i = 0; i < 8; i++) if (v[i].w == 0) v[i] = ldg_u128(qx + i * 128);
    }
    TL(5);
#pragma unroll
    for (int i = 0; i < 8; i++) {
      const int hh = (4 * w + (i >> 1)) ^ (16 * rI), ch = 32 * (i & 1) + lane;
      sts4(hi + OFF_R0 + (ch >> 3) * 4096 + hh * 128 + (((ch & 7) ^ (hh & 7)) << 4), v[i]);
    }
    asm volatile("fence.proxy.async.shared::cta;" ::: "memory");
    cbar();
    if (tid == 0) mbar_arrive(hi + BAR(BAR_GO));
  }
  TL(10);

  uint32_t ck1;
  const uint32_t *px, *pm;
  uint32_t *x2o, *x2p;
  {
    float O32[4][16], O16[4][8];
    uint32_t ebar;
    asm("mapa.shared::cluster.u32 %0, %1, %2;" : "=r"(ebar) : "r"(hi + BAR(BAR_EMPTY)), "r"(rI ^ (lane & 1)));
#pragma unroll
    for (int i = 0; i < 16; i++) O32[0][i] = O32[1][i] = O32[2][i] = O32[3][i] = 0.f;
#pragma unroll
    for (int i = 0; i < 4; i++) tie(O32[i]);
    auto pv2 = [&](int T, int WG, auto& O, int mb, int k0, int k1) {
      const int n = 8 * T + 4 * WG + mb;
      const uint32_t da = dlo(SB) + (sizeof(O[0]) == 64 ? n : n - 21) * 512, db = (WG && mb && T == 2) ? dlo(SB) : da + 512, dp = dlo(OFF_PT) + (T & 1) * 256;
#pragma unroll
      for (int ks = k0; ks < k1; ks++) { wgmma_ss<1, 1>(O[mb], da + ks * 128, dp + ks * 2); wgmma_ss<1, 1>(O[mb + 1], db + ks * 128, dp + ks * 2); }
      wg_commit();
    };
    auto pv = [&](int T, int WG, auto& O) { wg_fence(); pv2(T, WG, O, 0, 0, 4); pv2(T, WG, O, 2, 0, 4); };
    auto release = [&](int T, auto& O) {
      wg_wait<0>();
#pragma unroll
      for (int i = 0; i < 4; i++) tie(O[i]);
      if (lane < 2) mbar_arrive_cluster(ebar + 8 * T);
      TL(T < 3 ? 24 + T : 32);
    };
    auto rescale = [&](auto& O) {
#pragma unroll
      for (int jn = 0; jn < (int)(sizeof(O[0]) / 16); jn++) {
        const float2 a = ldsf2(hi + OFF_ALPHA + (8 * jn + 2 * t) * 4);
#pragma unroll
        for (int mb = 0; mb < 4; mb++) { O[mb][4 * jn] *= a.x; O[mb][4 * jn + 1] *= a.y; O[mb][4 * jn + 2] *= a.x; O[mb][4 * jn + 3] *= a.y; }
      }
    };
    uint64_t oe[8];
    uint32_t* const x1e = hold(gs->XE + (((16 * (1 - rI) + 2 * t) * 4 + 2 * wg) * 64 + (cta >> 1)) * 64 + (((wq * 8 + g) * 2) ^ ((pI & 3) << 3)));
    auto split_o = [&] {
#pragma unroll
      for (int i = 0; i < 8; i++) {
        const int jj = i >> 2, r = 8 + 4 * ((i >> 1) & 1) + (i & 1);
        oe[i] = pair64(pack_bf16(O32[2 * jj][r], O32[2 * jj][r + 2]), (pack_bf16(O32[2 * jj + 1][r], O32[2 * jj + 1][r + 2]) | 1u) ^ par);
      }
#pragma unroll
      for (int i = 0; i < 32; i++) asm volatile("mov.b32 %0, %1;" : "=f"(O16[i >> 3][i & 7]) : "f"(O32[i >> 3][i & 7]));
    };
    auto put_early = [&](int i) { stg_b64(x1e + ((8 * ((i >> 1) & 1) + (i & 1)) * 4 + (i >> 2)) * 4096, oe[i]); };
    auto p0b = [&] {
      const int mi = lane >> 3, r = lane & 7;
      const uint32_t abase = hi + OFF_WM + (64 * w + 16 * (r >> 1) + 2 * (mi >> 1) + (r & 1)) * 32 + (mi & 1) * 16;
      mbar_wait(hi + BAR(BAR_FULL + U_WMOD) + 8 * wg);
      float e0[4] = {0.f, 0.f, 0.f, 0.f}, e1[4] = {0.f, 0.f, 0.f, 0.f};
      uint32_t a[4][4];
#pragma unroll
      for (int ks = 0; ks < 4; ks++) ldsm4t(a[ks], abase + ks * 128);
#pragma unroll
      for (int ks = 0; ks < 4; ks++) mma16816((ks & 1) ? e1 : e0, a[ks], cf[2 * ks], cf[2 * ks + 1]);
      sts4f(hi + OFF_R0 + w * 4096 + 2048 + lane * 16, e0[0] + e1[0], e0[1] + e1[1], e0[2] + e1[2], e0[3] + e1[3]);
    };
    uint32_t* x1l[4];
    auto late_addr = [&] {
      mbar_wait(hi + BAR(BAR_FM));
      fb = lds1(hi + OFF_FB + tid * 4);
#pragma unroll
      for (int i = 0; i < 4; i++)
        x1l[i] = hold(inbox((16 * rI + 2 * t) * 4 + 2 * wg + (bI >> 2), bI & 3, fb, 4 * (i & 1) + (i >> 1), pI * 128 + (wq * 8 + g) * 2));
      px = hold(inbox((cta & ~1) + wg, wq, (fb >> (8 + (jI & 2) + wg)) ^ wq, 0, t * 128 + rI * 64 + 4 * g));
      pm = hold(inbox(cta & ~1, 6, fb, 8 + (jI & 2), 512 + (w * 8 + t) * 8));
      x2o = hold(inbox(4 * hI + (jI >> 1) + (~jI & 2), 7, ~fb, 8 + (jI >> 1) + (~jI & 2), (jI & 1) * 512 + tid * 2));
      x2p = hold(inbox(4 * hI + (jI >> 1) + (jI & 2), 7, ~fb, 8 + (jI >> 1) + (jI & 2), (jI & 1) * 512 + tid * 2));
    };
    auto put_late = [&](int jj) {
#pragma unroll
      for (int i = 0; i < 4; i++) {
        const int jn = i >> 1, e = i & 1, r = 4 * jn + e;
        stg_u64(x1l[i] + (8 * jn + e) * 4 * 16384 + jj * 64, pack_bf16(O16[2 * jj][r], O16[2 * jj][r + 2]), pack_bf16(O16[2 * jj + 1][r], O16[2 * jj + 1][r + 2]));
      }
    };
    auto last_products = [&](int WG) {
      wg_fence();
      pv2(4, WG, O16, 0, 0, 4);
      ck1 = clk32();
      pv2(4, WG, O16, 2, 0, PV_SPLIT);
      wg_wait<1>();
      tie(O16[0]); tie(O16[1]);
      TL(12);
      put_late(0);
      __syncwarp();
      if (PV_SPLIT < 4) { wg_fence(); pv2(4, WG, O16, 2, PV_SPLIT, 4); }
      wg_wait<0>();
      tie(O16[2]); tie(O16[3]);
      TL(50);
      put_late(1);
    };

    if (wg == 0) {
      float S32[16], S16[8];
      float m_run = -INFINITY;
      float mh[8];
#pragma unroll
      for (int i = 0; i < 16; i++) S32[i] = S16[i & 7] = mh[i & 7] = 0.f;
      const uint32_t ptl = hold32(hi + OFF_PT + (8 * (lane >> 4) + (lane & 7)) * 128 + (((2 * wq + ((lane >> 3) & 1)) ^ (lane & 7)) << 4));
      auto landed = [&](int T) { return __ballot_sync(~0u, mbar_test(hi + BAR(BAR_FULL + 8 * T) + 8 * (lane & 7))); };
      auto softmax = [&](int T, auto& O, auto& S) {
        constexpr int NJ = sizeof(S) / 16;
        wg_wait<0>();
        tie(S);
        if (NJ == 2) TL(T == 4 ? 11 : 52);
        bool over = T == 0;
#pragma unroll 1
        do {
          if (over) {
            float mx[2 * NJ];
#pragma unroll
            for (int jn = 0; jn < NJ; jn++) { mx[2 * jn] = fmaxf(S[4 * jn], S[4 * jn + 2]); mx[2 * jn + 1] = fmaxf(S[4 * jn + 1], S[4 * jn + 3]); }
            float a4[4], a2[2], a1;
            if constexpr (NJ == 4) {
              const bool up = lane & 16;
#pragma unroll
              for (int i = 0; i < 4; i++) { const float send = up ? mx[i] : mx[4 + i]; const float keep = up ? mx[4 + i] : mx[i]; a4[i] = fmaxf(keep, __shfl_xor_sync(~0u, send, 16)); }
            } else {
#pragma unroll
              for (int i = 0; i < 4; i++) { a4[i] = fmaxf(mx[i], __shfl_xor_sync(~0u, mx[i], 16)); if (lane & 16) a4[i] = -INFINITY; }
            }
            {
              const bool up = lane & 8;
#pragma unroll
              for (int i = 0; i < 2; i++) { const float send = up ? a4[i] : a4[2 + i]; const float keep = up ? a4[2 + i] : a4[i]; a2[i] = fmaxf(keep, __shfl_xor_sync(~0u, send, 8)); }
            }
            {
              const bool up = lane & 4;
              const float send = up ? a2[0] : a2[1]; const float keep = up ? a2[1] : a2[0];
              a1 = fmaxf(keep, __shfl_xor_sync(~0u, send, 4));
            }
            stsf(hi + OFF_RED + (wq * 32 + 8 * (g >> 1) + 2 * t + (g & 1)) * 4, a1);
            wg0bar();
            const float mt = fmaxf(fmaxf(ldsf(hi + OFF_RED + lane * 4), ldsf(hi + OFF_RED + 128 + lane * 4)),
                                   fmaxf(ldsf(hi + OFF_RED + 256 + lane * 4), ldsf(hi + OFF_RED + 384 + lane * 4)));
            const float m_new = fmaxf(m_run, ceilf(mt));
            if (wq == 0) { stsf(hi + OFF_MREF + lane * 4, m_new); stsf(hi + OFF_ALPHA + lane * 4, ex2(m_run - m_new)); }
            m_run = m_new;
#pragma unroll
            for (int i = 0; i < 2 * NJ; i++) mh[i] = __shfl_sync(~0u, m_new, 8 * (i >> 1) + 2 * t + (i & 1));
            if (T > 0) { wg0bar(); rescale(O); }
          }
          uint32_t pk[2 * NJ];
          float x[4 * NJ];
#pragma unroll
          for (int i = 0; i < 4 * NJ; i++) x[i] = S[i] - mh[2 * (i >> 2) + (i & 1)];
#pragma unroll
          for (int i = 0; i < 2 * NJ; i++) pk[i] = pack_bf16(ex2(x[2 * i]), ex2(x[2 * i + 1]));
#pragma unroll
          for (int hf = 0; hf < NJ / 2; hf++) stsm4t(ptl + (T & 1) * 4096 + hf * 2048, pk[4 * hf], pk[4 * hf + 1], pk[4 * hf + 2], pk[4 * hf + 3]);
          asm volatile("fence.proxy.async.shared::cta;" ::: "memory");
          if constexpr (NJ == 4) {
#pragma unroll
            for (int i = 0; i < 8; i++) x[i] = fmaxf(x[i], x[i + 8]);
          }
          over = cbar_or(fmaxf(fmaxf(fmaxf(x[0], x[1]), fmaxf(x[2], x[3])), fmaxf(fmaxf(x[4], x[5]), fmaxf(x[6], x[7]))) > 64.f);
        } while (__builtin_expect(over, 0));
        if (NJ == 2) TL(T == 4 ? 34 : 53);
      };
      uint32_t have = 0;
#pragma unroll 1
      for (int T = 0; T < 3; T++) {
        UNROLL(QK_UNROLL)
        for (int jj = 0; jj < 8; jj++) {
          const uint32_t da = dlo(SB) + box_slot(8 * T + jj) * 512, db = dlo(OFF_R0) + jj * 256;
          mbar_wait(hi + BAR(BAR_FULL) + 64 * T + 8 * jj);
          wg_fence();
          wgmma_ss_p(S32, da, db, jj);
#pragma unroll
          for (int ks = 1; ks < 4; ks++) wgmma_ss<0, 1>(S32, da + ks * 2, db + ks * 2);
          wg_commit();
        }
        softmax(T, O32, S32);
        pv(T, 0, O32);
        have = landed(3);
        release(T, O32);
      }
      split_o();
#pragma unroll
      for (int i = 0; i < 4; i++) x1l[i] = nullptr;
      px = pm = x2o = x2p = nullptr;
      p0b();
      TL(27);
#pragma unroll 1
      for (int T = 3;; T++) {
        sfor<0, 8>([&](auto jc) {
          constexpr int jj = decltype(jc)::value;
          const uint32_t da = dlo(SB) + (8 * T + jj - 21) * 512, db = dlo(OFF_R0) + jj * 256;
          if (!((have >> jj) & 1)) mbar_wait(hi + BAR(BAR_FULL) + 64 * T + 8 * jj);
          wg_fence();
          wgmma_ss<0, jj != 0>(S16, da, db);
#pragma unroll
          for (int ks = 1; ks < 4; ks++) wgmma_ss<0, 1>(S16, da + ks * 2, db + ks * 2);
          wg_commit();
          if (T == 3) {
            put_early(jj);
          }
        });
        softmax(T, O16, S16);
        if (T == 4) break;
        pv(3, 0, O16);
        late_addr();
        have = landed(4);
        mbar_wait(hi + BAR(BAR_FM));
        release(3, O16);
      }
      last_products(0);
    } else {
      float ls[2] = {0.f, 0.f};
      const int hr = 4 * wq + (lane >> 3);
      const uint32_t ptl = hi + OFF_PT + (tid & 127) * 16;
      auto sum8 = [](const uint4& v) { return ((bf_lo(v.x) + bf_hi(v.x)) + (bf_lo(v.y) + bf_hi(v.y))) + ((bf_lo(v.z) + bf_hi(v.z)) + (bf_lo(v.w) + bf_hi(v.w))); };
      auto row_sum = [](float l) { l += __shfl_xor_sync(~0u, l, 1); l += __shfl_xor_sync(~0u, l, 2); return l + __shfl_xor_sync(~0u, l, 4); };
      auto get_p = [&](auto& O) {
        if (__builtin_expect(cbar_or(false), 0)) {
          cbar_or(false);
          rescale(O);
          ls[0] *= ldsf(hi + OFF_ALPHA + hr * 4);
          if (sizeof(O[0]) == 64) ls[1] *= ldsf(hi + OFF_ALPHA + 64 + hr * 4);
        }
      };
#pragma unroll 1
      for (int T = 0; T < 3; T++) {
        get_p(O32);
        pv(T, 1, O32);
        ls[0] += sum8(lds4(ptl + (T & 1) * 4096));
        ls[1] += sum8(lds4(ptl + (T & 1) * 4096 + 2048));
        release(T, O32);
      }
      split_o();
      {
        const float l0 = row_sum(ls[0]), l1 = row_sum(ls[1]);
        const int hl = hr + 8 * (lane & 2);
        const uint32_t m = lds1(hi + OFF_MREF + hl * 4), l = (__float_as_uint((lane & 2) ? l1 : l0) | 1u) ^ par;
        if (!(lane & 4)) stg4_b128(gs->MLE + ((hl ^ (16 * rI)) * 128 + cta) * 8 + (lane & 1) * 4, make_uint4(m, l, m, l));
#pragma unroll
        for (int i = 0; i < 8; i++) put_early(i);
      }
      get_p(O16);
      pv(3, 1, O16);
      ls[0] += sum8(lds4(ptl + 4096));
      release(3, O16);
      p0b();
      asm volatile("bar.sync 3, 128;" ::: "memory");
      if (wq < 2) {
        if (tid == 128) mbar_arrive(hi + BAR(BAR_P0D));
        float2 v[8];
#pragma unroll
        for (int i = 0; i < 8; i++) v[i] = ldsf2(hi + OFF_R0 + i * 4096 + 2048 + lane * 16 + wq * 8);
        stg1(gs->MODB[par] + cta * 64 + wq * 32 + lane, nz(pack_bf16(((v[0].x + v[1].x) + (v[2].x + v[3].x)) + ((v[4].x + v[5].x) + (v[6].x + v[7].x)),
                                                                     ((v[0].y + v[1].y) + (v[2].y + v[3].y)) + ((v[4].y + v[5].y) + (v[6].y + v[7].y)))));
        TLW(31);
      }
      late_addr();
      uint32_t* const mlo = hold(inbox((16 * rI + hr) * 4 + (lane & 2), 6, fb, 13, 512 + (cta >> 1) * 8 + (lane & 1) * 4));
      mbar_wait(hi + BAR(BAR_CLR));
      get_p(O16);
      {
        const uint32_t m = lds1(hi + OFF_MREF + hr * 4), l = nz(__float_as_uint(row_sum(ls[0] + sum8(lds4(ptl)))));
        if (!(lane & 4)) stg4_b128(mlo, make_uint4(m, l, m, l));
      }
      last_products(1);
    }
  }
  TL(13);

  uint32_t aw[8][4];
  {
    uint2 mle[4];
    uint4 ve[4];
    wait_until(ck1, X1_D0);
    uint2 ml[2];
    uint4 v[4];
#pragma unroll
    for (int i = 0; i < 4; i++) v[i] = ldg_2u64(px + (i >> 1) * 512 + (i & 1) * 32);
#pragma unroll
    for (int i = 0; i < 2; i++) ml[i] = ldg_u64(pm + i * 32);
    TL(43);
    mbar_wait(hi + BAR(BAR_XE));
#pragma unroll
    for (int i = 0; i < 4; i++) mle[i] = lds2(hi + OFF_MLS + (w * 16 + 2 * t + 8 * (i & 1) + ((hI >> 4) ^ (i >> 1))) * 32);
#pragma unroll
    for (int i = 0; i < 4; i++) ve[i] = lds4(hi + OFF_XE + (w * 8 + t) * 256 + (g ^ (2 * t)) * 16 + (i >> 1) * 1024 + (i & 1) * 128);
#pragma unroll 1
    while (true) {
      uint32_t a = 1u, o = 0u;
#pragma unroll
      for (int i = 0; i < 4; i++) { a &= ve[i].y & ve[i].w & mle[i].y; o |= ve[i].y | ve[i].w | mle[i].y; }
      if (__all_sync(~0u, (par ? ~o : a) & 1)) break;
#pragma unroll
      for (int i = 0; i < 4; i++) {
        ve[i] = ldg_2u64(gs->XE + (cta * 64 + w * 8 + t) * 64 + 4 * (g ^ (2 * t)) + (i >> 1) * 256 + (i & 1) * 32);
        mle[i] = ldg_u64(gs->MLE + (hI * 128 + w * 16 + 2 * t + 8 * (i & 1) + ((hI >> 4) ^ (i >> 1))) * 8);
      }
      TL(55);
    }
    float M = fmaxf(fmaxf(__uint_as_float(mle[0].x), __uint_as_float(mle[1].x)), fmaxf(__uint_as_float(mle[2].x), __uint_as_float(mle[3].x)));
    M = fmaxf(M, __shfl_xor_sync(~0u, M, 1)); M = fmaxf(M, __shfl_xor_sync(~0u, M, 2));
    uint32_t wb[4];
#pragma unroll
    for (int i = 0; i < 4; i++) wb[i] = pack_bf16(ex2(__uint_as_float(mle[i].x) - M), 0.f);
    float Ls = bf_lo(wb[2]) * __uint_as_float(mle[2].y) + bf_lo(wb[3]) * __uint_as_float(mle[3].y);
    float d0[4] = {0.f, 0.f, 0.f, 0.f}, d1[4] = {0.f, 0.f, 0.f, 0.f};
#pragma unroll
    for (int i = 0; i < 4; i++) mma_v((i & 2) ? d1 : d0, ve[i], shl_clamp(wb[2 + (i >> 1)], 16 * g - 64 * (i & 1)), shl_clamp(wb[2 + (i >> 1)], 16 * g - 64 * (i & 1) - 32));
    uint32_t sel[4][2];
#pragma unroll
    for (int i = 0; i < 4; i++) { sel[i][0] = pin32(shl_clamp(wb[i >> 1], 16 * g - 64 * (i & 1))); sel[i][1] = pin32(shl_clamp(wb[i >> 1], 16 * g - 64 * (i & 1) - 32)); }
    const uint32_t bso = hold32(hi + OFF_BS4 + w * 320 + (16 * (t >> 1) + 8 * (g >> 2) + 4 * (g & 1) + 2 * (t & 1) + ((g >> 1) & 1)) * 8), bsi = hold32(hi + OFF_BS4 + g * 320 + t * 16);
    const uint32_t lso = hold32(hi + OFF_BS4 + w * 320 + 256 + t * 4), lsi = hold32(hi + OFF_BS4 + t * 640 + 256);
    TL(14);
    {
      const int mi = lane >> 3, r = lane & 7;
      const uint32_t base = hi + OFF_WUV + wg * 16384 + (mi >> 1) * 8192 + r * 128 + (((2 * wq + (mi & 1)) ^ r) << 4);
      mbar_wait(hi + BAR(BAR_FULL + U_WUV) + 16 * wg); mbar_wait(hi + BAR(BAR_FULL + U_WUV + 1) + 16 * wg);
#pragma unroll
      for (int ks = 0; ks < 8; ks++) ldsm4t(aw[ks], base + ks * 1024);
    }
    mbar_wait(hi + BAR(BAR_XE));
#pragma unroll
    for (int i = 0; i < 4; i++) tie(v[i]);
    tie(ml[0]); tie(ml[1]);
    TL(44);
    float e0[4], e1[4];
#pragma unroll 1
    while (true) {
      const bool valid = min(min3(min3(v[0].y, v[0].w, v[1].y), v[1].w, ml[0].y), min3(min3(v[2].y, v[2].w, v[3].y), v[3].w, ml[1].y)) != 0;
      const bool ok = __all_sync(~0u, valid && ml[0].x == mle[0].x && ml[1].x == mle[1].x);
#pragma unroll
      for (int i = 0; i < 4; i++) { e0[i] = d0[i]; e1[i] = d1[i]; }
      mma_v(e0, v[0], sel[0][0], sel[0][1]); mma_v(e1, v[2], sel[2][0], sel[2][1]);
      mma_v(e0, v[1], sel[1][0], sel[1][1]); mma_v(e1, v[3], sel[3][0], sel[3][1]);
      if (ok) break;
      if (__all_sync(~0u, valid)) {
        float M2 = fmaxf(M, fmaxf(__uint_as_float(ml[0].x), __uint_as_float(ml[1].x)));
        M2 = fmaxf(M2, __shfl_xor_sync(~0u, M2, 1)); M2 = fmaxf(M2, __shfl_xor_sync(~0u, M2, 2));
        const float f = ex2(M - M2);
        Ls *= f;
#pragma unroll
        for (int i = 0; i < 4; i++) { d0[i] *= f; d1[i] *= f; }
#pragma unroll
        for (int i = 0; i < 2; i++) { wb[i] = pack_bf16(ex2(__uint_as_float(ml[i].x) - M2), 0.f); mle[i].x = ml[i].x; }
#pragma unroll
        for (int i = 0; i < 4; i++) { sel[i][0] = shl_clamp(wb[i >> 1], 16 * g - 64 * (i & 1)); sel[i][1] = shl_clamp(wb[i >> 1], 16 * g - 64 * (i & 1) - 32); }
      }
#pragma unroll
      for (int i = 0; i < 4; i++) if (v[i].y == 0 || v[i].w == 0) v[i] = ldg_2u64(px + (i >> 1) * 512 + (i & 1) * 32);
#pragma unroll
      for (int i = 0; i < 2; i++) if (ml[i].y == 0) ml[i] = ldg_u64(pm + i * 32);
    }
    TL(15);
    stsf(lso, Ls + bf_lo(wb[0]) * __uint_as_float(ml[0].y) + bf_lo(wb[1]) * __uint_as_float(ml[1].y));
    sts2(bso, pack_bf16(e0[0] + e1[0], e0[1] + e1[1]), pack_bf16(e0[2] + e1[2], e0[3] + e1[3]));
    cbar();
    TL(16);
    float o[4][4] = {{0.f, 0.f, 0.f, 0.f}, {0.f, 0.f, 0.f, 0.f}, {0.f, 0.f, 0.f, 0.f}, {0.f, 0.f, 0.f, 0.f}};
    uint4 b[4];
#pragma unroll
    for (int kk = 0; kk < 4; kk++) b[kk] = lds4(bsi + kk * 64);
    const float4 la = ldsf4(lsi), lb = ldsf4(lsi + 320);
#pragma unroll
    for (int kk = 0; kk < 4; kk++) { mma16816(o[(2 * kk) & 3], aw[2 * kk], b[kk].x, b[kk].y); mma16816(o[(2 * kk + 1) & 3], aw[2 * kk + 1], b[kk].z, b[kk].w); }
    const float ia = rcp((la.x + la.y) + (la.z + la.w)), ib = rcp((lb.x + lb.y) + (lb.z + lb.w));
    const uint32_t y0 = pack_bf16(((o[0][0] + o[1][0]) + (o[2][0] + o[3][0])) * ia, ((o[0][1] + o[1][1]) + (o[2][1] + o[3][1])) * ib);
    const uint32_t y1 = pack_bf16(((o[0][2] + o[1][2]) + (o[2][2] + o[3][2])) * ia, ((o[0][3] + o[1][3]) + (o[2][3] + o[3][3])) * ib);
    stg_u64(x2o, y0, y1);
    stg_u64(x2p, y0, y1);
  }
  const uint32_t ck2 = clk32();
  TL(17);
  {
    uint32_t* const o = hold(inbox(4 * (8 * jI + w) + (g >> 1), 6, fb, 12, (g & 1) * 256 + hI * 8 + 2 * t));
    const uint32_t* const x2i = hold(inbox(cta & ~1, 7, ~fb, 8 + (jI & 2), tid * 2));
    const uint32_t* const x2j = hold(inbox(cta | 1, 7, ~fb, 8 + (jI | 1), tid * 2));
    const uint32_t bso = hold32(hi + OFF_BS5 + (16 * w + g) * 16 + t * 4), bsi = hold32(hi + OFF_BS5 + lane * 16);
    const uint32_t wa = hold32(hi + OFF_WO + wg * 8192 + (8 * (lane >> 4) + (lane & 7)) * 128 + (((2 * wq + ((lane >> 3) & 1)) ^ (lane & 7)) << 4));
    TL(45);
    wait_until(ck2, D_X2);
    uint2 v[4];
#pragma unroll
    for (int i = 0; i < 4; i++) v[i] = ldg_u64(((i & 2) ? x2j : x2i) + (i & 1) * 512);
    mbar_wait(hi + BAR(BAR_FULL + U_WO) + 8 * wg);
#pragma unroll
    for (int ks = 0; ks < 4; ks++) ldsm4t(aw[ks], wa + ks * 2048);
    const bool wo_ok = mbar_test(hi + BAR(BAR_FULL + U_WO + 2) + 8 * wg);
    if (wo_ok) {
#pragma unroll
      for (int ks = 0; ks < 4; ks++) ldsm4t(aw[4 + ks], wa + 16384 + ks * 2048);
    }
    mbar_wait(hi + BAR(BAR_XE));
#pragma unroll
    for (int i = 0; i < 4; i++) tie(v[i]);
    sum4_to_smem(v, x2i, x2j, bso);
    cbar();
    TL(18);
    float e[4][4] = {{0.f, 0.f, 0.f, 0.f}, {0.f, 0.f, 0.f, 0.f}, {0.f, 0.f, 0.f, 0.f}, {0.f, 0.f, 0.f, 0.f}};
    uint32_t b[4][4];
#pragma unroll
    for (int kk = 0; kk < 4; kk++) ldsm4t(b[kk], bsi + kk * 512);
    if (!wo_ok) {
      mbar_wait(hi + BAR(BAR_FULL + U_WO + 2) + 8 * wg);
#pragma unroll
      for (int ks = 0; ks < 4; ks++) ldsm4t(aw[4 + ks], wa + 16384 + ks * 2048);
    }
#pragma unroll
    for (int ks = 0; ks < 8; ks++) mma16816(e[ks & 3], aw[ks], b[ks >> 1][2 * (ks & 1)], b[ks >> 1][2 * (ks & 1) + 1]);
    stg_u64(o, pack_bf16((e[0][0] + e[1][0]) + (e[2][0] + e[3][0]), (e[0][1] + e[1][1]) + (e[2][1] + e[3][1])),
            pack_bf16((e[0][2] + e[1][2]) + (e[2][2] + e[3][2]), (e[0][3] + e[1][3]) + (e[2][3] + e[3][3])));
    if (lane == 0) mbar_arrive(hi + BAR(BAR_P5D));
  }
  const uint32_t ck3 = clk32();
  TL(19);
  if (cta < NFF) {
    const int mi = lane >> 3, r = lane & 7;
    uint32_t a1[4][4], a2[4][4];
    uint32_t bc[8], bs[8], mn;
    const uint32_t* const mbi = gs->MODB[par] + (512 + 64 * w) * 4 + lane;
    do {
      mn = 0xffffffffu;
#pragma unroll
      for (int i = 0; i < 8; i++) { bs[i] = ldg_rlx1(mbi + i * 32); bc[i] = ldg_rlx1(mbi + 2048 + i * 32); }
#pragma unroll
      for (int i = 0; i < 8; i++) mn = min3(mn, bs[i], bc[i]);
    } while (!__all_sync(~0u, mn != 0));
#pragma unroll
    for (int i = 0; i < 8; i++) { bs[i] = movm(bs[i]); bc[i] = hadd2(movm(bc[i]), ONE2); }
    mbar_wait(hi + BAR(BAR_FULL + U_W1) + 8 * wg);
#pragma unroll
    for (int ks = 0; ks < 4; ks++) ldsm4t(a1[ks], hi + OFF_W1 + (64 * w + 16 * ks + 8 * (mi >> 1) + r) * 32 + (mi & 1) * 16);
    {
      float u[4] = {0.f, 0.f, 0.f, 0.f}, vv[4] = {0.f, 0.f, 0.f, 0.f};
#pragma unroll
      for (int ks = 0; ks < 4; ks++) { mma16816(u, a1[ks], bc[2 * ks], bc[2 * ks + 1]); mma16816(vv, a1[ks], bs[2 * ks], bs[2 * ks + 1]); }
      sts4f(hi + OFF_REDU + tid * 16, u[0], u[1], u[2], u[3]);
      sts4f(hi + OFF_REDV + tid * 16, vv[0], vv[1], vv[2], vv[3]);
    }
    cbar();
    const int lp = (tid >> 2) & 31, kq = tid & 3;
    const int fo = (lp >> 2) + 8 * (kq >> 1), bo = 2 * (lp & 3) + (kq & 1);
    float U = 0.f, V = 0.f;
    if (tid < 128) {
#pragma unroll
      for (int i = 0; i < 8; i++) { U += ldsf(hi + OFF_REDU + i * 512 + tid * 4); V += ldsf(hi + OFF_REDV + i * 512 + tid * 4); }
    }
    const uint32_t* xb = hold(gs->X3B + ((cta >> 1) & 1) * 4096 + wg * 2048 + (((fb >> 14) & 1) << 10) + (16 * wq + t) * 16 + 2 * g);
    uint32_t* ox[4];
#pragma unroll
    for (int mb = 0; mb < 4; mb++) ox[mb] = hold(inbox(16 * w + 4 * mb + (g >> 1), 4 + (cta >= 56), fb, 16 + 4 * mb, (cta >= 56 ? cta - 56 : cta) * 16 + (g & 1) * 8 + 2 * t));
    const uint32_t gi = hold32(hi + OFF_REDG + tid * 4);
    const uint32_t h1o = hold32(hi + OFF_H1 + fo * 16 + bo * 2), sti = hold32(hi + OFF_REDS + bo * 64), sto = hold32(hi + OFF_REDS + g * 64 + w * 8);
    const bool w2ok = mbar_test(hi + BAR(BAR_FULL + U_W2) + 8 * wg);
    const uint32_t a2a = hi + OFF_W2 + w * 2048 + (8 * (mi >> 1) + r) * 128;
    if (w2ok) {
#pragma unroll
      for (int mb = 0; mb < 4; mb++) ldsm4t(a2[mb], a2a + (((2 * mb + (mi & 1)) ^ r) << 4));
    }
    TL(46);
    wait_until(ck3, D_X3B);
    float G[2][4], S[2][4];
    bool ok;
#pragma unroll 1
    do {
      uint2 x[4];
#pragma unroll
      for (int ks = 0; ks < 4; ks++) x[ks] = ldg_u64(xb + ks * 64);
      ok = __all_sync(~0u, min(min3(x[0].y, x[1].y, x[2].y), x[3].y) != 0);
#pragma unroll
      for (int i = 0; i < 4; i++) G[0][i] = G[1][i] = S[0][i] = S[1][i] = 0.f;
#pragma unroll
      for (int ks = 0; ks < 4; ks++) {
        const uint32_t s0[4] = {x[ks].x, ONE2, x[ks].y, ONE2};
        mma16816(S[ks & 1], s0, x[ks].x, x[ks].y);
        mma16816(G[ks & 1], a1[ks], hmul2(x[ks].x, bc[2 * ks]), hmul2(x[ks].y, bc[2 * ks + 1]));
      }
    } while (!ok);
    TL(21);
    if ((g >> 1) == t) sts2f(sto, (g & 1) ? S[0][3] + S[1][3] : S[0][2] + S[1][2], (g & 1) ? S[0][1] + S[1][1] : S[0][0] + S[1][0]);
    sts4f(hi + OFF_REDG + tid * 16, G[0][0] + G[1][0], G[0][1] + G[1][1], G[0][2] + G[1][2], G[0][3] + G[1][3]);
    cbar();
    TL(39);
    if (tid < 128) {
      float gv[8];
      float4 sv[4];
#pragma unroll
      for (int i = 0; i < 4; i++) sv[i] = ldsf4(sti + i * 16);
#pragma unroll
      for (int i = 0; i < 8; i++) gv[i] = ldsf(gi + i * 512);
      const float s1 = ((sv[0].x + sv[0].z) + (sv[1].x + sv[1].z)) + ((sv[2].x + sv[2].z) + (sv[3].x + sv[3].z));
      const float s2 = ((sv[0].y + sv[0].w) + (sv[1].y + sv[1].w)) + ((sv[2].y + sv[2].w) + (sv[3].y + sv[3].w));
      const float gs_ = ((gv[0] + gv[1]) + (gv[2] + gv[3])) + ((gv[4] + gv[5]) + (gv[6] + gv[7]));
      const float mu = s1 * (1.f / 512.f);
      const float rs = rsq(fmaxf(s2 * (1.f / 512.f) - mu * mu, 0.f) + 1e-5f);
      const float hv = fmaxf(rs * (gs_ - mu * U) + V, 0.f);
      asm volatile("st.shared.u16 [%0], %1;" ::"r"(h1o), "h"(__bfloat16_as_ushort(__float2bfloat16(hv))) : "memory");
    }
    if (!w2ok) {
      mbar_wait(hi + BAR(BAR_FULL + U_W2) + 8 * wg);
#pragma unroll
      for (int mb = 0; mb < 4; mb++) ldsm4t(a2[mb], a2a + (((2 * mb + (mi & 1)) ^ r) << 4));
    }
    cbar();
    TL(40);
    uint32_t b0, b1;
    ldsm2t(b0, b1, hi + OFF_H1 + (lane & 15) * 16);
#pragma unroll
    for (int mb = 0; mb < 4; mb++) {
      float o[4] = {0.f, 0.f, 0.f, 0.f};
      mma16816(o, a2[mb], b0, b1);
      stg_u64(ox[mb], pack_bf16(o[0], o[1]), pack_bf16(o[2], o[3]));
    }
    TL(22);
    if (lane == 0) mbar_arrive(hi + BAR(BAR_P7D));
  }
}

typedef CUresult (*EncodeTiledFn)(CUtensorMap*, CUtensorMapDataType, cuuint32_t, void*, const cuuint64_t*, const cuuint64_t*,
                                  const cuuint32_t*, const cuuint32_t*, CUtensorMapInterleave, CUtensorMapSwizzle,
                                  CUtensorMapL2promotion, CUtensorMapFloatOOBfill);

void make_map(EncodeTiledFn enc, CUtensorMap* m, const void* base, uint64_t cols, uint64_t rows, uint32_t bc, uint32_t br,
              CUtensorMapSwizzle sw, CUtensorMapL2promotion promo) {
  cuuint64_t dims[2] = {cols, rows};
  cuuint64_t strides[1] = {cols * 2};
  cuuint32_t box[2] = {bc, br};
  cuuint32_t es[2] = {1, 1};
  enc(m, CU_TENSOR_MAP_DATA_TYPE_BFLOAT16, 2, const_cast<void*>(base), dims, strides, box, es, CU_TENSOR_MAP_INTERLEAVE_NONE, sw, promo,
      CU_TENSOR_MAP_FLOAT_OOB_FILL_NONE);
}
void make_map3(EncodeTiledFn enc, CUtensorMap* m, const void* base, uint64_t rows, uint32_t br, uint32_t bb) {
  cuuint64_t dims[3] = {64, rows, 8};
  cuuint64_t strides[2] = {1024, 128};
  cuuint32_t box[3] = {64, br, bb};
  cuuint32_t es[3] = {1, 1, 1};
  enc(m, CU_TENSOR_MAP_DATA_TYPE_BFLOAT16, 3, const_cast<void*>(base), dims, strides, box, es, CU_TENSOR_MAP_INTERLEAVE_NONE,
      CU_TENSOR_MAP_SWIZZLE_128B, CU_TENSOR_MAP_L2_PROMOTION_NONE, CU_TENSOR_MAP_FLOAT_OOB_FILL_NONE);
}

}

extern "C" void kernel_launch(void* const* d_in, const int* in_sizes, int n_in, void* d_out, int out_size) {
  (void)in_sizes; (void)n_in; (void)out_size;
  static EncodeTiledFn enc = nullptr;
  static Scratch* scratch = nullptr;
  if (!enc) {
    void* sp = nullptr;
    cudaGetSymbolAddress(&sp, g_s);
    scratch = (Scratch*)(((uintptr_t)sp + 65535) & ~(uintptr_t)65535);
    void* fn = nullptr;
    cudaDriverEntryPointQueryResult q;
    cudaGetDriverEntryPoint("cuTensorMapEncodeTiled", &fn, cudaEnableDefault, &q);
    enc = (EncodeTiledFn)fn;
    cudaFuncSetAttribute(fused_decode_kernel, cudaFuncAttributeMaxDynamicSharedMemorySize, SMEM_BYTES);
  }
  Params P;
  make_map(enc, &P.ckv, d_in[1], 512, 8 * 4096, 64, 64, CU_TENSOR_MAP_SWIZZLE_128B, CU_TENSOR_MAP_L2_PROMOTION_NONE);
  make_map(enc, &P.wq, d_in[2], 4096, 512, 64, 64, CU_TENSOR_MAP_SWIZZLE_128B, CU_TENSOR_MAP_L2_PROMOTION_NONE);
  make_map(enc, &P.wuk, d_in[3], 4096, 512, 64, 64, CU_TENSOR_MAP_SWIZZLE_128B, CU_TENSOR_MAP_L2_PROMOTION_NONE);
  {
    cuuint64_t dims[4] = {4096, 2, 8, 32};
    cuuint64_t strides[3] = {8 * 8192, 8192, 16 * 8192};
    cuuint32_t box[4] = {64, 2, 8, 4};
    cuuint32_t es[4] = {1, 1, 1, 1};
    enc(&P.wuv, CU_TENSOR_MAP_DATA_TYPE_BFLOAT16, 4, d_in[4], dims, strides, box, es, CU_TENSOR_MAP_INTERLEAVE_NONE, CU_TENSOR_MAP_SWIZZLE_128B,
        CU_TENSOR_MAP_L2_PROMOTION_NONE, CU_TENSOR_MAP_FLOAT_OOB_FILL_NONE);
  }
  make_map(enc, &P.wo, d_in[5], 512, 4096, 64, 64, CU_TENSOR_MAP_SWIZZLE_128B, CU_TENSOR_MAP_L2_PROMOTION_NONE);
  make_map(enc, &P.w1, d_in[7], 1792, 512, FCH, 256, CU_TENSOR_MAP_SWIZZLE_NONE, PROMO);
  make_map3(enc, &P.w2, d_in[8], 1792, FCH, 4);
  make_map(enc, &P.wma, d_in[10], 3072, 512, 64, 128, CU_TENSOR_MAP_SWIZZLE_128B, CU_TENSOR_MAP_L2_PROMOTION_NONE);
  make_map(enc, &P.wmod, d_in[10], 3072, 512, 16, 256, CU_TENSOR_MAP_SWIZZLE_NONE, PROMO);
  fused_decode_kernel<<<NCTA, NTHREADS, SMEM_BYTES>>>((__nv_bfloat16*)d_out, scratch, (const uint8_t*)d_in[2], (const uint8_t*)d_in[0],
                                                      (const uint8_t*)d_in[9], P);
}
```

```cpp
#include <cuda_runtime.h>
#include <cuda.h>
#include <cuda_bf16.h>
#include <stdint.h>

namespace {

constexpr int NCTA = 128;
constexpr int NTHREADS = 384;
constexpr int FCH = 16;
constexpr int NFF = 1792 / FCH;

constexpr uint32_t SB = 1024;
__host__ __device__ constexpr uint32_t slot(int i) { return SB + i * 8192; }
constexpr uint32_t OFF_R1 = slot(16);
constexpr uint32_t OFF_R2 = slot(20);
constexpr uint32_t OFF_PT = slot(23);
constexpr uint32_t OFF_R0 = slot(24);
constexpr uint32_t OFF_MISC = SB + 229376;
constexpr uint32_t OFF_BARS = OFF_MISC;
constexpr uint32_t OFF_FM = OFF_MISC + 736;
constexpr uint32_t OFF_EPOCH = OFF_MISC + 768;
constexpr uint32_t OFF_TL = OFF_MISC + 784;
constexpr uint32_t OFF_BS = OFF_MISC + 1024;
constexpr uint32_t SMEM_BYTES = 229376 + 3072;
constexpr uint32_t OFF_P0S = OFF_R0 + 24576;
constexpr uint32_t OFF_BS2 = OFF_R0 + 30720;
constexpr uint32_t OFF_RED = OFF_BS;
constexpr uint32_t OFF_ALPHA = OFF_BS + 512;
constexpr uint32_t OFF_MREF = OFF_BS + 640;
constexpr uint32_t OFF_FB = OFF_BS + 1024;
__host__ __device__ constexpr int box_slot(int n) { return n < 23 ? n : n == 23 ? 0 : n - 21; }
constexpr uint32_t OFF_WM = slot(1);
constexpr uint32_t OFF_WUV = slot(19);
constexpr uint32_t OFF_XE = slot(1);
constexpr uint32_t OFF_BS4 = slot(0);
constexpr uint32_t OFF_BS5 = slot(0) + 4096;
constexpr uint32_t OFF_MLS = slot(0) + 4096;
constexpr uint32_t OFF_WO = slot(3);
constexpr uint32_t OFF_W1 = slot(7);
constexpr uint32_t OFF_W2 = slot(11);
constexpr uint32_t OFF_REDG = OFF_R0;
constexpr uint32_t OFF_REDS = OFF_R0 + 4096;
constexpr uint32_t OFF_REDU = OFF_R0 + 8192;
constexpr uint32_t OFF_REDV = OFF_R0 + 12288;
constexpr uint32_t OFF_H1 = OFF_R0 + 16384;

constexpr int BAR_FULL = 8;
constexpr int U_WQ = -8, U_WUK = -4, U_WUV = 40, U_WO = 44, U_W1 = 48, U_W2 = 50, NUNITS = 52, U_WMOD = 52;
constexpr int BAR_EMPTY = 62;
constexpr int BAR_GO = 66, BAR_CLR = 67, BAR_EPOCH = 68;
constexpr int BAR_P2E = 69, BAR_P5D = 70, BAR_P7D = 71, BAR_X1W = 75;
constexpr int BAR_XE = 72;
constexpr int BAR_FM = 73;
constexpr int BAR_P0D = 74;
constexpr int BAR_WA = 76;
__host__ __device__ constexpr uint32_t BAR(int i) { return OFF_BARS + 8 * i; }
#define CPA_N 4
#define PACE_T0 608
#define PACE_DT 320
#define PACE_DTM 320
#define PACE_NM 10
#define PACE_DTE 330
#define WM0 24
#define WM1 34
#define PACE_GAP 150
#define PACE_DT2 340
#define D_FIN2 2000
#define PACE_DT3 400
#define PACE_DT4 440
#define PACE_GAP3 300
#define PACE_GAP4 0
#define PROMO CU_TENSOR_MAP_L2_PROMOTION_NONE
#define NPROBE 3
#define WIN_PRE 5
#define WIN_MID 8
#define WIN_END 6
#define WIN_TAIL 4
#define CLR_CLK 220
#define D_MOD 600
#define MOD_AT 3
#define D_QP 1600
#define D_QX 1400
#define QX_AT 5
#define QK_UNROLL 8
#define PV_SPLIT 3
#define XE_AT 36
#define CNT_AT 27
#define X1_D0 900
#define D_X2 300
#define D_X3A 400
#define D_X3B 1300
#define D_FIN 450

struct Scratch {
  uint32_t MODA[1024 * 4];
  uint32_t QP[128 * 256 * 2];
  uint32_t MODB[2][2048 * 4];
  uint32_t FL[2][128];
  uint32_t QX[2][8 * 32 * 256];
  uint32_t XE[128 * 64 * 64];
  uint32_t MLE[32 * 128 * 8];
  uint32_t epoch;
  uint32_t pad[31];
  uint32_t cnt;
  alignas(65536) uint32_t X3B[16384];
  uint32_t IN[128][16384];
};
__device__ uint8_t g_s[sizeof(Scratch) + 65536];

#define TL(idx) do {} while (0)
#define TLW(idx) do {} while (0)
#define PROBE_UNITS(a, b) do {} while (0)

struct Params {
  CUtensorMap wma, wq, wuk, wmod, ckv, wuv, wo, w1, w2;
};

__device__ __forceinline__ void mbar_init(uint32_t bar, int cnt) { asm volatile("mbarrier.init.shared::cta.b64 [%0], %1;" ::"r"(bar), "r"(cnt)); }
__device__ __forceinline__ void mbar_expect(uint32_t bar, uint32_t bytes) { asm volatile("mbarrier.arrive.expect_tx.shared::cta.b64 _, [%0], %1;" ::"r"(bar), "r"(bytes) : "memory"); }
__device__ __forceinline__ void mbar_arrive(uint32_t bar) { asm volatile("mbarrier.arrive.shared::cta.b64 _, [%0];" ::"r"(bar) : "memory"); }
__device__ __forceinline__ void mbar_arrive_cluster(uint32_t bar) { asm volatile("mbarrier.arrive.shared::cluster.b64 _, [%0];" ::"r"(bar) : "memory"); }
__device__ __forceinline__ bool mbar_test(uint32_t bar) {
  uint32_t ok;
  asm volatile("{\n.reg .pred p;\nmbarrier.test_wait.parity.shared::cta.b64 p, [%1], 0;\nselp.u32 %0,1,0,p;\n}" : "=r"(ok) : "r"(bar) : "memory");
  return ok;
}
__device__ __forceinline__ uint32_t gtime32() { uint32_t c; asm volatile("mov.u32 %0, %%globaltimer_lo;" : "=r"(c) :: "memory"); return c; }
__device__ __forceinline__ uint32_t clk32() { uint32_t c; asm volatile("{\n.reg .u64 t;\nmov.u64 t, %%clock64;\ncvt.u32.u64 %0, t;\n}" : "=r"(c) :: "memory"); return c; }
__device__ __forceinline__ void wait_until(uint32_t c0, int clocks) { if (clocks > 0) while ((int)(clk32() - c0) < clocks) {} }
__device__ __forceinline__ void backoff(int clocks) { if (clocks > 0) wait_until(clk32(), clocks); }
__device__ __forceinline__ uint32_t pin32(uint32_t p) { asm volatile("" : "+r"(p)); return p; }
template <typename T> __device__ __forceinline__ T* pin(T* p) { asm volatile("" : "+l"(p)); return p; }
__device__ __forceinline__ uint32_t hold32(uint32_t p) { asm volatile("shfl.sync.bfly.b32 %0, %0, 0, 0x1f, 0xffffffff;" : "+r"(p) :: "memory"); return p; }
__device__ __forceinline__ float holdf(float p) { return __uint_as_float(hold32(__float_as_uint(p))); }
template <typename T> __device__ __forceinline__ T* hold(T* p) {
  asm volatile("{\n.reg .b32 a, b;\nmov.b64 {a, b}, %0;\nshfl.sync.bfly.b32 a, a, 0, 0x1f, 0xffffffff;\nshfl.sync.bfly.b32 b, b, 0, 0x1f, 0xffffffff;\nmov.b64 %0, {a, b};\n}" : "+l"(p) :: "memory");
  return p;
}
constexpr int SPIN_LIMIT = 1 << 22;
__device__ __forceinline__ void mbar_wait(uint32_t bar) {
  asm volatile("{\n.reg .pred p;\nMW_LOOP:\nmbarrier.try_wait.parity.shared::cta.b64 p, [%0], 0;\n@!p bra MW_LOOP;\n}" ::"r"(bar) : "memory");
}
__device__ __forceinline__ void mbar_wait_b(uint32_t bar) {
  asm volatile("{\n.reg .pred p;\n.reg .u32 c;\nmov.u32 c, 0;\n"
               "MW_LOOP:\nmbarrier.try_wait.parity.shared::cta.b64 p, [%0], 0;\n@p bra MW_DONE;\n"
               "add.u32 c, c, 1;\nsetp.lt.u32 p, c, 1048576;\n@p bra MW_LOOP;\ntrap;\nMW_DONE:\n}"
               ::"r"(bar) : "memory");
}
__device__ __forceinline__ void tma2d(uint32_t dst, const CUtensorMap* m, int c0, int c1, uint32_t bar, uint64_t pol) {
  asm volatile("cp.async.bulk.tensor.2d.shared::cluster.global.mbarrier::complete_tx::bytes.L2::cache_hint [%0], [%1, {%3,%4}], [%2], %5;"
               ::"r"(dst), "l"(m), "r"(bar), "r"(c0), "r"(c1), "l"(pol) : "memory");
}
__device__ __forceinline__ void tma2d_both(uint32_t dst, const CUtensorMap* m, int c0, int c1, uint32_t bar, uint64_t pol) {
  asm volatile("cp.async.bulk.tensor.2d.shared::cluster.global.mbarrier::complete_tx::bytes.multicast::cluster.L2::cache_hint [%0], [%1, {%3,%4}], [%2], %6, %5;"
               ::"r"(dst), "l"(m), "r"(bar), "r"(c0), "r"(c1), "l"(pol), "h"((uint16_t)3) : "memory");
}
__device__ __forceinline__ void tma3d(uint32_t dst, const CUtensorMap* m, int c0, int c1, int c2, uint32_t bar, uint64_t pol) {
  asm volatile("cp.async.bulk.tensor.3d.shared::cluster.global.mbarrier::complete_tx::bytes.L2::cache_hint [%0], [%1, {%3,%4,%5}], [%2], %6;"
               ::"r"(dst), "l"(m), "r"(bar), "r"(c0), "r"(c1), "r"(c2), "l"(pol) : "memory");
}
__device__ __forceinline__ void tma4d(uint32_t dst, const CUtensorMap* m, int c0, int c3, uint32_t bar, uint64_t pol) {
  asm volatile("cp.async.bulk.tensor.4d.shared::cluster.global.mbarrier::complete_tx::bytes.L2::cache_hint [%0], [%1, {%3,%6,%6,%4}], [%2], %5;"
               ::"r"(dst), "l"(m), "r"(bar), "r"(c0), "r"(c3), "l"(pol), "r"(0) : "memory");
}
__device__ __forceinline__ void bulk_load(uint32_t dst, const void* src, uint32_t bytes, uint32_t bar) {
  asm volatile("cp.async.bulk.shared::cluster.global.mbarrier::complete_tx::bytes [%0], [%1], %2, [%3];" ::"r"(dst), "l"(src), "r"(bytes), "r"(bar) : "memory");
}
__device__ __forceinline__ void cbar() { asm volatile("bar.sync 1, 256;" ::: "memory"); }
__device__ __forceinline__ void wg0bar() { asm volatile("bar.sync 2, 128;" ::: "memory"); }
__device__ __forceinline__ bool cbar_or(bool p) {
  uint32_t r;
  asm volatile("{\n.reg .pred p, q;\nsetp.ne.u32 p, %1, 0;\nbarrier.cta.red.or.aligned.pred q, 1, 256, p;\nselp.u32 %0, 1, 0, q;\n}" : "=r"(r) : "r"((uint32_t)p) : "memory");
  return r;
}

__device__ __forceinline__ uint32_t ldg_rlx1(const void* p) { uint32_t v; asm volatile("ld.relaxed.gpu.global.u32 %0, [%1];" : "=r"(v) : "l"(p) : "memory"); return v; }
__device__ __forceinline__ void stg4(void* p, uint4 v) { asm volatile("st.relaxed.gpu.global.v4.u32 [%0], {%1,%2,%3,%4};" ::"l"(p), "r"(v.x), "r"(v.y), "r"(v.z), "r"(v.w) : "memory"); }
__device__ __forceinline__ void stg1(void* p, uint32_t a) { asm volatile("st.relaxed.gpu.global.u32 [%0], %1;" ::"l"(p), "r"(a) : "memory"); }
__device__ __forceinline__ uint32_t nz(uint32_t w) { uint32_t r; asm("max.u32 %0, %1, 1;" : "=r"(r) : "r"(w)); return r; }
__device__ __forceinline__ uint32_t min3(uint32_t a, uint32_t b, uint32_t c) { return min(min(a, b), c); }

__device__ __forceinline__ uint32_t pack_bf16(float lo, float hi) { uint32_t r; asm("cvt.rn.bf16x2.f32 %0, %1, %2;" : "=r"(r) : "f"(hi), "f"(lo)); return r; }
__device__ __forceinline__ float bf_lo(uint32_t w) { return __uint_as_float(w << 16); }
__device__ __forceinline__ float bf_hi(uint32_t w) { return __uint_as_float(w & 0xffff0000u); }
__device__ __forceinline__ float ex2(float x) { float r; asm("ex2.approx.ftz.f32 %0, %1;" : "=f"(r) : "f"(x)); return r; }
__device__ __forceinline__ float rcp(float x) { float r; asm("rcp.approx.ftz.f32 %0, %1;" : "=f"(r) : "f"(x)); return r; }
__device__ __forceinline__ float rsq(float x) { float r; asm("rsqrt.approx.ftz.f32 %0, %1;" : "=f"(r) : "f"(x)); return r; }
__device__ __forceinline__ uint32_t silu2(uint32_t c) {
  const float a = bf_lo(c), b = bf_hi(c);
  return pack_bf16(__fdividef(a, 1.f + __expf(-a)), __fdividef(b, 1.f + __expf(-b)));
}
__device__ __forceinline__ uint32_t shl_clamp(uint32_t x, int s) { uint32_t r; asm("shl.b32 %0, %1, %2;" : "=r"(r) : "r"(x), "r"(s)); return r; }

__device__ __forceinline__ void ldsm4(uint32_t (&r)[4], uint32_t a) { asm volatile("ldmatrix.sync.aligned.m8n8.x4.shared.b16 {%0,%1,%2,%3}, [%4];" : "=r"(r[0]), "=r"(r[1]), "=r"(r[2]), "=r"(r[3]) : "r"(a) : "memory"); }
__device__ __forceinline__ void ldsm4t(uint32_t (&r)[4], uint32_t a) { asm volatile("ldmatrix.sync.aligned.m8n8.x4.trans.shared.b16 {%0,%1,%2,%3}, [%4];" : "=r"(r[0]), "=r"(r[1]), "=r"(r[2]), "=r"(r[3]) : "r"(a) : "memory"); }
__device__ __forceinline__ void ldsm2t(uint32_t& r0, uint32_t& r1, uint32_t a) { asm volatile("ldmatrix.sync.aligned.m8n8.x2.trans.shared.b16 {%0,%1}, [%2];" : "=r"(r0), "=r"(r1) : "r"(a) : "memory"); }
__device__ __forceinline__ void stsm4t(uint32_t a, uint32_t r0, uint32_t r1, uint32_t r2, uint32_t r3) { asm volatile("stmatrix.sync.aligned.m8n8.x4.trans.shared.b16 [%0], {%1,%2,%3,%4};" ::"r"(a), "r"(r0), "r"(r1), "r"(r2), "r"(r3) : "memory"); }
__device__ __forceinline__ void stsm2t(uint32_t a, uint32_t r0, uint32_t r1) { asm volatile("stmatrix.sync.aligned.m8n8.x2.trans.shared.b16 [%0], {%1,%2};" ::"r"(a), "r"(r0), "r"(r1) : "memory"); }
__device__ __forceinline__ void mma16816(float (&d)[4], const uint32_t (&a)[4], uint32_t b0, uint32_t b1) {
  asm volatile("mma.sync.aligned.m16n8k16.row.col.f32.bf16.bf16.f32 {%0,%1,%2,%3}, {%4,%5,%6,%7}, {%8,%9}, {%0,%1,%2,%3};"
               : "+f"(d[0]), "+f"(d[1]), "+f"(d[2]), "+f"(d[3]) : "r"(a[0]), "r"(a[1]), "r"(a[2]), "r"(a[3]), "r"(b0), "r"(b1));
}
__device__ __forceinline__ void mma_v(float (&d)[4], const uint4& a, uint32_t b0, uint32_t b1) {
  asm volatile("mma.sync.aligned.m16n8k16.row.col.f32.bf16.bf16.f32 {%0,%1,%2,%3}, {%4,%5,%6,%7}, {%8,%9}, {%0,%1,%2,%3};"
               : "+f"(d[0]), "+f"(d[1]), "+f"(d[2]), "+f"(d[3]) : "r"(a.x), "r"(a.y), "r"(a.z), "r"(a.w), "r"(b0), "r"(b1));
}
__device__ __forceinline__ void sts1(uint32_t a, uint32_t v) { asm volatile("st.shared.u32 [%0], %1;" ::"r"(a), "r"(v) : "memory"); }
__device__ __forceinline__ void sts2(uint32_t a, uint32_t x, uint32_t y) { asm volatile("st.shared.v2.u32 [%0], {%1,%2};" ::"r"(a), "r"(x), "r"(y) : "memory"); }
__device__ __forceinline__ void sts4(uint32_t a, uint4 v) { asm volatile("st.shared.v4.u32 [%0], {%1,%2,%3,%4};" ::"r"(a), "r"(v.x), "r"(v.y), "r"(v.z), "r"(v.w) : "memory"); }
__device__ __forceinline__ void sts4f(uint32_t a, float x, float y, float z, float w) { asm volatile("st.shared.v4.f32 [%0], {%1,%2,%3,%4};" ::"r"(a), "f"(x), "f"(y), "f"(z), "f"(w) : "memory"); }
__device__ __forceinline__ void sts2f(uint32_t a, float x, float y) { asm volatile("st.shared.v2.f32 [%0], {%1,%2};" ::"r"(a), "f"(x), "f"(y) : "memory"); }
__device__ __forceinline__ void stsf(uint32_t a, float v) { asm volatile("st.shared.f32 [%0], %1;" ::"r"(a), "f"(v) : "memory"); }
__device__ __forceinline__ uint32_t lds1(uint32_t a) { uint32_t v; asm volatile("ld.shared.u32 %0, [%1];" : "=r"(v) : "r"(a) : "memory"); return v; }
__device__ __forceinline__ uint2 lds2(uint32_t a) { uint2 v; asm volatile("ld.shared.v2.u32 {%0,%1}, [%2];" : "=r"(v.x), "=r"(v.y) : "r"(a) : "memory"); return v; }
__device__ __forceinline__ float ldsf(uint32_t a) { float v; asm volatile("ld.shared.f32 %0, [%1];" : "=f"(v) : "r"(a) : "memory"); return v; }
__device__ __forceinline__ float2 ldsf2(uint32_t a) { float2 v; asm volatile("ld.shared.v2.f32 {%0,%1}, [%2];" : "=f"(v.x), "=f"(v.y) : "r"(a) : "memory"); return v; }
__device__ __forceinline__ float4 ldsf4(uint32_t a) { float4 v; asm volatile("ld.shared.v4.f32 {%0,%1,%2,%3}, [%4];" : "=f"(v.x), "=f"(v.y), "=f"(v.z), "=f"(v.w) : "r"(a) : "memory"); return v; }
__device__ __forceinline__ uint4 lds4(uint32_t a) { uint4 v; asm volatile("ld.shared.v4.u32 {%0,%1,%2,%3}, [%4];" : "=r"(v.x), "=r"(v.y), "=r"(v.z), "=r"(v.w) : "r"(a) : "memory"); return v; }

__device__ __forceinline__ void wg_fence() { asm volatile("wgmma.fence.sync.aligned;" ::: "memory"); }
__device__ __forceinline__ void wg_commit() { asm volatile("wgmma.commit_group.sync.aligned;" ::: "memory"); }
template <int N> __device__ __forceinline__ void wg_wait() { asm volatile("wgmma.wait_group.sync.aligned %0;" ::"n"(N) : "memory"); }
__host__ __device__ constexpr uint32_t dlo(uint32_t addr) { return (addr >> 4) | 0x10000u; }
constexpr uint32_t ONE2 = 0x3f803f80u;
template <int TA, int ACC> __device__ __forceinline__ void wgmma_ss(float (&d)[16], uint32_t da, uint32_t db) {
  asm volatile("{\n.reg .b64 da, db;\nmov.b64 da, {%16, 0x40000040};\nmov.b64 db, {%17, 0x40000040};\n"
               "wgmma.mma_async.sync.aligned.m64n32k16.f32.bf16.bf16 {%0,%1,%2,%3,%4,%5,%6,%7,%8,%9,%10,%11,%12,%13,%14,%15}, da, db, %18, 1, 1, %19, 0;\n}"
               : "+f"(d[0]), "+f"(d[1]), "+f"(d[2]), "+f"(d[3]), "+f"(d[4]), "+f"(d[5]), "+f"(d[6]), "+f"(d[7]),
                 "+f"(d[8]), "+f"(d[9]), "+f"(d[10]), "+f"(d[11]), "+f"(d[12]), "+f"(d[13]), "+f"(d[14]), "+f"(d[15])
               : "r"(da), "r"(db), "n"(ACC), "n"(TA));
}
template <int TA, int ACC> __device__ __forceinline__ void wgmma_ss(float (&d)[8], uint32_t da, uint32_t db) {
  asm volatile("{\n.reg .b64 da, db;\nmov.b64 da, {%8, 0x40000040};\nmov.b64 db, {%9, 0x40000040};\n"
               "wgmma.mma_async.sync.aligned.m64n16k16.f32.bf16.bf16 {%0,%1,%2,%3,%4,%5,%6,%7}, da, db, %10, 1, 1, %11, 0;\n}"
               : "+f"(d[0]), "+f"(d[1]), "+f"(d[2]), "+f"(d[3]), "+f"(d[4]), "+f"(d[5]), "+f"(d[6]), "+f"(d[7])
               : "r"(da), "r"(db), "n"(ACC), "n"(TA));
}
__device__ __forceinline__ void wgmma_n8(float (&d)[4], uint32_t da, uint32_t db) {
  asm volatile("{\n.reg .b64 da, db;\nmov.b64 da, {%4, 0x40000040};\nmov.b64 db, {%5, 0x40000040};\n"
               "wgmma.mma_async.sync.aligned.m64n8k16.f32.bf16.bf16 {%0,%1,%2,%3}, da, db, 1, 1, 1, 1, 0;\n}"
               : "+f"(d[0]), "+f"(d[1]), "+f"(d[2]), "+f"(d[3]) : "r"(da), "r"(db));
}
__device__ __forceinline__ void wgmma_ss_p(float (&d)[16], uint32_t da, uint32_t db, int acc) {
  asm volatile("{\n.reg .pred p;\n.reg .b64 da, db;\nsetp.ne.b32 p, %18, 0;\nmov.b64 da, {%16, 0x40000040};\nmov.b64 db, {%17, 0x40000040};\n"
               "wgmma.mma_async.sync.aligned.m64n32k16.f32.bf16.bf16 {%0,%1,%2,%3,%4,%5,%6,%7,%8,%9,%10,%11,%12,%13,%14,%15}, da, db, p, 1, 1, 0, 0;\n}"
               : "+f"(d[0]), "+f"(d[1]), "+f"(d[2]), "+f"(d[3]), "+f"(d[4]), "+f"(d[5]), "+f"(d[6]), "+f"(d[7]),
                 "+f"(d[8]), "+f"(d[9]), "+f"(d[10]), "+f"(d[11]), "+f"(d[12]), "+f"(d[13]), "+f"(d[14]), "+f"(d[15])
               : "r"(da), "r"(db), "r"(acc));
}
__device__ __forceinline__ void wgmma_ss_p(float (&d)[8], uint32_t da, uint32_t db, int acc) {
  asm volatile("{\n.reg .pred p;\n.reg .b64 da, db;\nsetp.ne.b32 p, %10, 0;\nmov.b64 da, {%8, 0x40000040};\nmov.b64 db, {%9, 0x40000040};\n"
               "wgmma.mma_async.sync.aligned.m64n16k16.f32.bf16.bf16 {%0,%1,%2,%3,%4,%5,%6,%7}, da, db, p, 1, 1, 0, 0;\n}"
               : "+f"(d[0]), "+f"(d[1]), "+f"(d[2]), "+f"(d[3]), "+f"(d[4]), "+f"(d[5]), "+f"(d[6]), "+f"(d[7])
               : "r"(da), "r"(db), "r"(acc));
}
template <int K> __device__ __forceinline__ void tie(float (&d)[K]) {
#pragma unroll
  for (int i = 0; i < K; i += 8)
    asm volatile("" : "+f"(d[i]), "+f"(d[i + 1]), "+f"(d[i + 2]), "+f"(d[i + 3]), "+f"(d[i + 4]), "+f"(d[i + 5]), "+f"(d[i + 6]), "+f"(d[i + 7]) :: "memory");
}
template <bool C, typename A, typename B> __device__ __forceinline__ auto& pick(A& a, B& b) { if constexpr (C) return a; else return b; }
__device__ __forceinline__ void tie(uint4& v) { asm volatile("" : "+r"(v.x), "+r"(v.y), "+r"(v.z), "+r"(v.w) :: "memory"); }
__device__ __forceinline__ void tie(uint2& v) { asm volatile("" : "+r"(v.x), "+r"(v.y) :: "memory"); }
#define PRAGMA(x) _Pragma(#x)
#define UNROLL(n) PRAGMA(unroll n)
template <int I> struct IC { static constexpr int value = I; };
template <int B, int E, typename F> __device__ __forceinline__ void sfor(F&& f) { if constexpr (B < E) { f(IC<B>{}); sfor<B + 1, E>(f); } }

__device__ __forceinline__ uint2 ldg_u64(const void* p) {
  uint2 v; asm volatile("{\n.reg .b64 a;\nld.relaxed.gpu.global.b64 a, [%2];\nmov.b64 {%0,%1}, a;\n}" : "=r"(v.x), "=r"(v.y) : "l"(p) : "memory"); return v;
}
__device__ __forceinline__ uint4 ldg_2u64(const void* p) {
  uint4 v; asm volatile("{\n.reg .b64 a, b;\nld.relaxed.gpu.global.v2.b64 {a, b}, [%4];\nmov.b64 {%0,%1}, a;\nmov.b64 {%2,%3}, b;\n}" : "=r"(v.x), "=r"(v.y), "=r"(v.z), "=r"(v.w) : "l"(p) : "memory"); return v;
}
__device__ __forceinline__ uint4 ldg_u128(const void* p) {
  uint4 v; asm volatile("{\n.reg .b64 a, b;\n.reg .b128 q;\nld.relaxed.gpu.global.b128 q, [%4];\nmov.b128 {a, b}, q;\nmov.b64 {%0,%1}, a;\nmov.b64 {%2,%3}, b;\n}" : "=r"(v.x), "=r"(v.y), "=r"(v.z), "=r"(v.w) : "l"(p) : "memory"); return v;
}
__device__ __forceinline__ void stg_u64(void* p, uint32_t x, uint32_t y) {
  asm volatile("{\n.reg .b64 a;\nmov.b64 a, {%1,%2};\nst.relaxed.gpu.global.b64 [%0], a;\n}" ::"l"(p), "r"(x), "r"(nz(y)) : "memory");
}
__device__ __forceinline__ uint64_t pair64(uint32_t x, uint32_t y) { uint64_t a; asm("mov.b64 %0, {%1,%2};" : "=l"(a) : "r"(x), "r"(y)); return a; }
__device__ __forceinline__ void stg_b64(void* p, uint64_t a) { asm volatile("st.relaxed.gpu.global.b64 [%0], %1;" ::"l"(p), "l"(a) : "memory"); }
__device__ __forceinline__ void stg4_b128(void* p, uint4 v) {
  asm volatile("{\n.reg .b64 a, b;\n.reg .b128 q;\nmov.b64 a, {%1,%2};\nmov.b64 b, {%3,%4};\nmov.b128 q, {a, b};\nst.relaxed.gpu.global.b128 [%0], q;\n}" ::"l"(p), "r"(v.x), "r"(v.y), "r"(v.z), "r"(v.w) : "memory");
}
__device__ __forceinline__ void stg_u128(void* p, uint4 v) {
  asm volatile("{\n.reg .b64 a, b;\n.reg .b128 q;\nmov.b64 a, {%1,%2};\nmov.b64 b, {%3,%4};\nmov.b128 q, {a, b};\nst.relaxed.gpu.global.b128 [%0], q;\n}" ::"l"(p), "r"(v.x), "r"(v.y), "r"(v.z), "r"(nz(v.w)) : "memory");
}
__device__ __forceinline__ uint32_t hmul2(uint32_t a, uint32_t b) { uint32_t r; asm("mul.rn.bf16x2 %0, %1, %2;" : "=r"(r) : "r"(a), "r"(b)); return r; }
__device__ __forceinline__ uint32_t hadd2(uint32_t a, uint32_t b) { uint32_t r; asm("add.rn.bf16x2 %0, %1, %2;" : "=r"(r) : "r"(a), "r"(b)); return r; }
__device__ __forceinline__ uint32_t hfma2(uint32_t a, uint32_t b, uint32_t c) { uint32_t r; asm("fma.rn.bf16x2 %0, %1, %2, %3;" : "=r"(r) : "r"(a), "r"(b), "r"(c)); return r; }
__device__ __forceinline__ uint32_t movm(uint32_t a) { uint32_t d; asm volatile("movmatrix.sync.aligned.m8n8.trans.b16 %0, %1;" : "=r"(d) : "r"(a)); return d; }
__device__ __forceinline__ uint2 ldg_rlx2(const void* p) { uint2 v; asm volatile("ld.relaxed.gpu.global.v2.u32 {%0,%1}, [%2];" : "=r"(v.x), "=r"(v.y) : "l"(p) : "memory"); return v; }
__device__ __forceinline__ uint4 ldg_in4(const void* p) { uint4 v; asm volatile("ld.global.nc.v4.u32 {%0,%1,%2,%3}, [%4];" : "=r"(v.x), "=r"(v.y), "=r"(v.z), "=r"(v.w) : "l"(p) : "memory"); return v; }
__device__ __forceinline__ uint32_t ldg_in1(const void* p) { uint32_t v; asm volatile("ld.global.nc.u32 %0, [%1];" : "=r"(v) : "l"(p)); return v; }
__device__ __forceinline__ uint32_t ldg_inh(const void* p) { uint16_t v; asm volatile("ld.global.nc.u16 %0, [%1];" : "=h"(v) : "l"(p) : "memory"); return v; }

__device__ __forceinline__ void sum4_to_smem(uint2 (&v)[4], const uint32_t* x, const uint32_t* y, uint32_t dst) {
  uint32_t r0, r1;
#pragma unroll 1
  while (true) {
    const bool ok = __all_sync(~0u, min(min3(v[0].y, v[1].y, v[2].y), v[3].y) != 0);
    r0 = pack_bf16((bf_lo(v[0].x) + bf_lo(v[1].x)) + (bf_lo(v[2].x) + bf_lo(v[3].x)), (bf_hi(v[0].x) + bf_hi(v[1].x)) + (bf_hi(v[2].x) + bf_hi(v[3].x)));
    r1 = pack_bf16((bf_lo(v[0].y) + bf_lo(v[1].y)) + (bf_lo(v[2].y) + bf_lo(v[3].y)), (bf_hi(v[0].y) + bf_hi(v[1].y)) + (bf_hi(v[2].y) + bf_hi(v[3].y)));
    sts1(dst, r0);
    sts1(dst + 128, r1);
    if (ok) break;
#pragma unroll
    for (int i = 0; i < 4; i++) v[i] = ldg_u64(((i & 2) ? y : x) + (i & 1) * 512);
  }
}
__device__ __forceinline__ void load_a_t(uint32_t (&a)[8][4], uint32_t box, int wq, int lane) {
  const int mi = lane >> 3, r = lane & 7;
  const uint32_t base = box + (8 * (mi >> 1) + r) * 128 + (((2 * wq + (mi & 1)) ^ r) << 4);
#pragma unroll
  for (int ks = 0; ks < 8; ks++) ldsm4t(a[ks], base + ks * 2048);
}
__device__ __forceinline__ void mma128(float (&d)[4], const uint32_t (&a)[8][4], uint32_t bs) {
  float e[4][4] = {{0.f, 0.f, 0.f, 0.f}, {0.f, 0.f, 0.f, 0.f}, {0.f, 0.f, 0.f, 0.f}, {0.f, 0.f, 0.f, 0.f}};
  uint32_t b[4][4];
#pragma unroll
  for (int kk = 0; kk < 4; kk++) ldsm4t(b[kk], bs + 32 * kk * 16);
#pragma unroll
  for (int kk = 0; kk < 4; kk++) { mma16816(e[(2 * kk) & 3], a[2 * kk], b[kk][0], b[kk][1]); mma16816(e[(2 * kk + 1) & 3], a[2 * kk + 1], b[kk][2], b[kk][3]); }
#pragma unroll
  for (int i = 0; i < 4; i++) d[i] = (e[0][i] + e[1][i]) + (e[2][i] + e[3][i]);
}
template <int NL, typename F> __device__ __forceinline__ void poll_vectors(const uint32_t* p, const uint32_t* q, F&& f) {
  int it = 0;
  bool ok;
  uint4 v[NL];
#pragma unroll
  for (int i = 0; i < NL; i++) v[i] = make_uint4(0, 0, 0, 0);
#pragma unroll 1
  do {
    if (++it > SPIN_LIMIT) __trap();
#pragma unroll
    for (int i = 0; i < NL; i++) if (NL <= 4 || min(v[i].y, v[i].w) == 0) v[i] = ldg_2u64(i < NL / 2 ? p + i * 128 : q + (i - NL / 2) * 128);
    f(v);
    uint32_t m0 = min(v[0].y, v[0].w), m1 = min(v[1].y, v[1].w);
#pragma unroll
    for (int i = 2; i < NL; i += 2) { m0 = min3(m0, v[i].y, v[i].w); m1 = min3(m1, v[i + 1].y, v[i + 1].w); }
    ok = __all_sync(~0u, min(m0, m1) != 0);
  } while (!ok);
}

__global__ void __cluster_dims__(2, 1, 1) __launch_bounds__(NTHREADS, 1)
fused_decode_kernel(__nv_bfloat16* __restrict__ gout, Scratch* __restrict__ gs, const uint8_t* __restrict__ gwq,
                    const uint8_t* __restrict__ gx, const uint8_t* __restrict__ gc,
                    const __grid_constant__ Params P) {
  extern __shared__ __align__(1024) uint8_t smem_raw[];
  const uint32_t hi = pin32((uint32_t)__cvta_generic_to_shared(smem_raw) - SB);
  const int tid = threadIdx.x, lane = tid & 31;
  const int w = __shfl_sync(0xffffffffu, tid >> 5, 0);
  const int cta = blockIdx.x;
  const int g = lane >> 2, t = lane & 3;
  const int hI = cta >> 2, jI = cta & 3;
  const int bI = cta >> 4, pI = (cta >> 1) & 7, rI = cta & 1;

  uint32_t epoch0 = 0;
  if (tid == 320) epoch0 = ldg_rlx1(&gs->epoch);
  const bool p0a = (cta & 7) == 0;
  uint4 cw0, cw1, xr0, xr1;
  uint32_t xc;
  if (w < 8) {
    const uint8_t* src = gwq + (size_t)(128 * jI + (tid >> 4)) * 8192 + hI * 256 + (tid & 15) * 16;
    const uint32_t dst = hi + OFF_R1 + ((tid >> 3) & 1) * 16384 + (tid >> 4) * 128 + (((tid ^ (tid >> 4)) & 7) << 4);
    if (p0a) {
      cw0 = ldg_in4(gc + g * 1024 + w * 128 + t * 32); cw1 = ldg_in4(gc + g * 1024 + w * 128 + t * 32 + 16);
      xr0 = ldg_in4(gx + w * 1024 + lane * 16); xr1 = ldg_in4(gx + w * 1024 + 512 + lane * 16);
      xc = ldg_in1(gx + w * 1024 + (cta & 63) * 16 + lane * 4);
    } else {
#pragma unroll
      for (int i = 0; i < CPA_N; i++) asm volatile("cp.async.cg.shared.global [%0], [%1], 16;" ::"r"(dst + i * 2048), "l"(src + i * 16 * 8192) : "memory");
    }
  }
  auto half_of = [&](int c, int k) { return ((lds1(hi + OFF_FM + (c >> 5) * 4) >> (c & 31)) ^ k) & 1; };
  auto inbox = [&](int c, int k, uint32_t bits, int pos, int off) { return gs->IN[0] + (uint32_t)(c * 16384 + k * 2048 + off + (((bits >> pos) & 1) << 10)); };
  auto front_unit = [&](int k, uint64_t pol) {
    tma2d(hi + OFF_R1 + ((k & 4) + 2 * (k & 1) + ((k >> 1) & 1)) * 8192, k < 4 ? &P.wq : &P.wuk, 128 * hI + 64 * (k & 1), 128 * jI + 64 * ((k >> 1) & 1), hi + BAR(k), pol);
  };
  uint32_t tnext = 0;
  if (tid == 256) {
    tnext = gtime32() + PACE_T0;
    if (hi & 0xffffff) __trap();
    if (p0a) {
#pragma unroll
      for (int i = 0; i < 4; i++) mbar_init(hi + BAR(BAR_WA + i), 1);
      asm volatile("fence.mbarrier_init.release.cluster;" ::: "memory");
      uint64_t pol; asm volatile("createpolicy.fractional.L2::evict_first.b64 %0, 1.0;" : "=l"(pol));
#pragma unroll
      for (int i = 0; i < 4; i++) tma2d(hi + slot(8 + 2 * i), &P.wma, 8 * cta, 128 * i, hi + BAR(BAR_WA + i), pol);
    }
    asm volatile("prefetch.tensormap [%0];" ::"l"(&P.wq) : "memory");
    TLW(42);
  } else if (tid == 288) {
#pragma unroll
    for (int i = 0; i < BAR_WA; i++)
      mbar_init(hi + BAR(i), (i >= BAR_EMPTY && i < BAR_EMPTY + 4) ? 16 : ((i >= BAR_P2E && i <= BAR_P7D) || i == BAR_X1W) ? 8 : 1);
    asm volatile("fence.mbarrier_init.release.cluster;" ::: "memory");
  }
  __syncthreads();
  TL(0);

  if (w == 8) {
    if (p0a && lane < 4) mbar_expect(hi + BAR(BAR_WA) + 8 * lane, 16384);
    mbar_expect(hi + BAR(0) + 8 * lane, (lane < CPA_N / 2 && !p0a) ? 0 : 8192);
    if (p0a) tnext -= (CPA_N / 2) * PACE_DT;
    if (lane < BAR_EMPTY - 32) mbar_expect(hi + BAR(32) + 8 * lane, ((32 + lane - BAR_FULL) & ~5) == U_W1 ? 16384 : 8192);
    __syncwarp();
    const int h = hI, j = jI;
    if (lane == 0) {
      uint64_t pol; asm volatile("createpolicy.fractional.L2::evict_first.b64 %0, 1.0;" : "=l"(pol));
      auto pace = [&](int dt) { if (PACE_DT > 0) { while ((int)(gtime32() - tnext) < 0) {} tnext += dt; } };
      asm volatile("prefetch.tensormap [%0];" ::"l"(&P.wuk) : "memory");
      asm volatile("prefetch.tensormap [%0];" ::"l"(&P.wmod) : "memory");
      asm volatile("prefetch.tensormap [%0];" ::"l"(&P.ckv) : "memory");
#pragma unroll 1
      for (int k = p0a ? 0 : CPA_N / 2; k < 8; k++) { if (k >= WIN_PRE) mbar_wait(hi + BAR(0) + 8 * (k - WIN_PRE)); pace(PACE_DT); front_unit(k, pol); }
      bool go = false;
      const int row0 = bI * 4096 + (cta & 15) * 64;
#pragma unroll 1
      for (int n = 0; n < 24; n++) {
        if (n == 8) mbar_wait(hi + BAR(BAR_P2E));
        if (n == 23) mbar_wait(hi + BAR(BAR_EMPTY));
        if (!go) go = mbar_test(hi + BAR(BAR_GO));
        mbar_wait(hi + BAR(BAR_FULL) + 8 * (n - (go ? WIN_MID : WIN_PRE)));
        pace(n >= PACE_NM ? PACE_DTM : PACE_DT);
        tma2d(hi + slot(box_slot(n)), &P.ckv, (n & 7) * 64, row0 + (n >> 3) * 1024, hi + BAR(BAR_FULL) + 8 * n, pol);
      }
      asm volatile("prefetch.tensormap [%0];" ::"l"(&P.wuv) : "memory");
      asm volatile("prefetch.tensormap [%0];" ::"l"(&P.wo) : "memory");
      asm volatile("prefetch.tensormap [%0];" ::"l"(&P.w1) : "memory");
      asm volatile("prefetch.tensormap [%0];" ::"l"(&P.w2) : "memory");
      const int row1 = bI * 4096 + (24 + pI) * 64;
      tnext += rI * (PACE_DT / 2) - PACE_DT / 4;
#pragma unroll 1
      for (int n = 24 + rI; n < 40; n += 2) {
        const int c = n - 23;
        const int m = c >= 2 * WIN_END ? n - 2 * WIN_END : 23 - (2 * WIN_END - c) / 2;
        mbar_wait(hi + BAR(BAR_FULL) + 8 * m);
        if ((n & ~1) == WM0 || (n & ~1) == WM1) {
          const int u = (n & ~1) == WM1;
          if (u) mbar_wait(hi + BAR(BAR_EMPTY + 2));
          pace(PACE_DTE);
          tma2d_both(hi + OFF_WM + (20 * u + rI) * 8192, &P.wmod, 1024 + 16 * (cta & ~1), 256 * u + 128 * rI, hi + BAR(BAR_FULL + U_WMOD) + 8 * u, pol);
        }
        mbar_wait(hi + BAR(BAR_EMPTY) + ((n - 21) & ~7));
        pace(PACE_DTE);
        tma2d_both(hi + slot(n - 21), &P.ckv, (n & 7) * 64, row1 + (n >> 3) * 512, hi + BAR(BAR_FULL) + 8 * n, pol);
      }
      mbar_wait(hi + BAR(BAR_EMPTY + 2));
      tnext += PACE_GAP;
#pragma unroll 1
      for (int n = U_WUV; n < (cta < NFF ? NUNITS : U_W1); n++) {
        const int c = n - 39, u = n & 3;
        mbar_wait(hi + BAR(BAR_FULL) + 8 * (c >= WIN_TAIL ? n - WIN_TAIL : 39 - 2 * (WIN_TAIL - c)));
        if (n == U_WUV + 2) mbar_wait(hi + BAR(BAR_P0D));
        if (n == U_WO) mbar_wait(hi + BAR(BAR_EMPTY + 3));
        if (n == U_W2) mbar_wait(hi + BAR(BAR_X1W));
        const uint32_t bar = hi + BAR(BAR_FULL) + 8 * n, dst = hi + slot(n < U_WO ? n - 21 : n < U_W1 ? n - 41 : n < U_W2 ? 2 * n - 89 + rI : n - 39);
        if (n == U_WO) tnext += PACE_GAP3;
        if (n == U_W1) tnext += PACE_GAP4;
        pace(n < U_WO ? PACE_DT2 : n < U_W1 ? PACE_DT3 : PACE_DT4);
        if (n < U_WO) tma4d(dst, &P.wuv, 128 * h + 64 * (u >> 1), 8 * j + 4 * (u & 1), bar, pol);
        else if (n < U_W1) tma2d(dst, &P.wo, 128 * j + 64 * (u & 1), 128 * h + 64 * (u >> 1), bar, pol);
        else if (n < U_W2) tma2d_both(dst, &P.w1, FCH * (cta & ~1), 256 * (u & 1) + 128 * rI, bar, pol);
        else tma3d(dst, &P.w2, 0, FCH * cta, 4 * (u & 1), bar, pol);
      }
    }
    return;
  }

  if (w == 11) {
    const uint4 z = make_uint4(0, 0, 0, 0);
    uint32_t f = 0, f2 = 0;
    {
      uint32_t* const p = ((lane & 2) ? gs->X3B + 4 * 2048 + cta * 8 : gs->IN[cta] + 4 * 2048 + 960) + ((lane & 1) << 10);
      if (lane < 8) stg4(p + (lane & 4), z);
      __syncwarp();
      uint32_t best = ~0u;
#pragma unroll 1
      for (int i = 0; i < 4 * NPROBE + (int)(hi & 1); i++) {
        uint32_t v = 0;
        const uint32_t c0 = clk32();
        if (lane == (i & 3)) asm volatile("atom.relaxed.gpu.global.exch.b32 %0, [%1], %2;" : "=r"(v) : "l"(p), "r"(i) : "memory");
        v = __shfl_sync(~0u, v, i & 3);
        const uint32_t dt = clk32() - c0 + (v >> 31);
        if (lane == (i & 3)) best = min(best, dt);
      }
      const uint32_t m = __ballot_sync(~0u, best < __shfl_xor_sync(~0u, best, 1));
      f = (m >> 1) & 1; f2 = (m >> 3) & 1;
    }
    mbar_wait(hi + BAR(BAR_EPOCH));
    const uint32_t epoch = lds1(hi + OFF_EPOCH);
    const int par = epoch & 1;
    if (lane == 0) stg1(gs->FL[par] + cta, 1 + f);
    TLW(51);
    mbar_wait(hi + BAR(BAR_P2E));
#pragma unroll 1
    for (int i = 0; i < 16; i++) {
      const uint32_t c0 = clk32();
      uint32_t* p = gs->IN[cta] + (i >> 1) * 2048 + (((f ^ (i >> 1)) & 1) << 10) + (i & 1) * 512 + lane * 4;
#pragma unroll
      for (int q = 0; q < 4; q++) stg4(p + q * 128, z);
      if (i == 0 && lane < 16) stg4(gs->X3B + cta * 64 + lane * 4, z);
      wait_until(c0, CLR_CLK);
    }
    TLW(35);
    {
      uint32_t u[4];
      do {
#pragma unroll
        for (int i = 0; i < 4; i++) u[i] = ldg_rlx1(gs->FL[par] + 32 * i + lane);
      } while (!__all_sync(~0u, min(min(u[0], u[1]), min(u[2], u[3])) != 0));
      const uint4 m = make_uint4(__ballot_sync(~0u, u[0] == 2), __ballot_sync(~0u, u[1] == 2), __ballot_sync(~0u, u[2] == 2), __ballot_sync(~0u, u[3] == 2));
      if (lane == 0) sts4(hi + OFF_FM, m);
      __syncwarp();
      const uint2 m2 = lds2(hi + OFF_FM + 8 * rI);
      const uint32_t mh = (lds1(hi + OFF_FM + (hI >> 3) * 4) >> (4 * (hI & 7))) & 15;
#pragma unroll 1
      for (int v = 0; v < 8; v++) {
        const int sh = 8 * t + 2 * (v >> 2) + (bI >> 2);
        uint32_t fb = (((m2.x >> sh) & 0x11) | (((m2.y >> sh) & 0x11) << 1)) ^ ((bI & 1) ? 0x33 : 0);
        fb |= mh << 8;
        fb |= half_of(4 * (8 * jI + v) + (g >> 1), 0) << 12;
        fb |= half_of((16 * rI + 4 * (v & 3) + (lane >> 3)) * 4 + (lane & 2), 0) << 13;
        fb |= ((f2 ^ (v >> 2)) & 1) << 14;
        fb |= (((lds1(hi + OFF_FM + (v >> 1) * 4) >> (16 * (v & 1) + (g >> 1))) & 0x1111) ^ (cta >= 56 ? 0x1111 : 0)) << 16;
        sts1(hi + OFF_FB + (v * 32 + lane) * 4, fb);
      }
      __syncwarp();
      if (lane == 0) mbar_arrive(hi + BAR(BAR_FM));
    }
    asm volatile("fence.acq_rel.gpu;" ::: "memory");
    __syncwarp();
    if (lane == 0) asm volatile("red.relaxed.gpu.global.add.u32 [%0], 1;" ::"l"(&gs->cnt) : "memory");
    TLW(36);
    mbar_wait(hi + BAR(BAR_GO));
    if (lane == 0) stg1(gs->FL[par ^ 1] + cta, 0u);
#pragma unroll
    for (int i = 0; i < 4; i++) stg4(gs->QP + cta * 512 + (i * 32 + lane) * 4, z);
#pragma unroll
    for (int i = 0; i < 4; i++) stg4(gs->QX[par ^ 1] + cta * 512 + (i * 32 + lane) * 4, z);
    if (lane < 8) stg4(gs->MODA + cta * 32 + lane * 4, z);
    if (lane < 16) stg4(gs->MODB[par ^ 1] + cta * 64 + lane * 4, z);
    mbar_wait(hi + BAR(BAR_FULL + CNT_AT));
    while ((int)(ldg_rlx1(&gs->cnt) - (epoch + 1) * NCTA) < 0) __nanosleep(100);
    if (lane == 0) mbar_arrive(hi + BAR(BAR_CLR));
    TLW(54);
    return;
  }
  if (w == 10) {
    const int m0 = 16 * hI + 2 * jI;
    const int bo = lane & 7;
    const uint32_t epoch = __shfl_sync(~0u, epoch0, 0);
    if (lane == 0) { sts1(hi + OFF_EPOCH, epoch); mbar_arrive(hi + BAR(BAR_EPOCH)); }
    const int par = epoch & 1;
    const uint32_t* MOD = gs->MODB[par];
    PROBE_UNITS(-8, 16);
    PROBE_UNITS(16, 43);
    mbar_wait_b(hi + BAR(BAR_FULL + U_WUV + 2));
    const uint32_t xw0 = ldg_in1(gx + bo * 1024 + m0 * 2), xw1 = ldg_in1(gx + bo * 1024 + m0 * 2 + 16);
    const int mf = m0 + ((g >> 1) & 1) + 8 * (t >> 1), bf = 2 * (g & 1) + (t & 1);
    float ga[4];
    uint32_t gb2;
    {
      uint32_t u[4];
      int it = 0;
      while (true) {
#pragma unroll
        for (int i = 0; i < 4; i++) u[i] = ldg_rlx1(MOD + (m0 + (i & 1) + 8 * (i >> 1)) * 4 + (bo >> 1));
        gb2 = ldg_rlx1(MOD + (1536 + mf) * 4 + bf);
        if (min3(min3(u[0], u[1], u[2]), u[3], gb2) != 0) break;
        if (++it > SPIN_LIMIT) __trap();
      }
#pragma unroll
      for (int i = 0; i < 4; i++) ga[i] = (bo & 1) ? bf_hi(u[i]) : bf_lo(u[i]);
    }
    uint32_t x2a, x2b;
    mbar_wait_b(hi + BAR(BAR_FM));
    const uint32_t fo_ = half_of(cta, 0);
    {
      const uint32_t* const pi = hold(inbox(cta, 6, fo_, 0, (4 * (g >> 1) + t) * 8 + (g & 1) * 4));
      uint32_t* const po = hold(gs->X3B + (g >> 2) * 4096 + (cta >> 6) * 2048 + ((g >> 1) & 1) * 1024 + (cta & 63) * 16 + bo * 2);
      const uint32_t one = 0x3f80u << (8 * (g & 2)), s0 = g < 4 ? one : 0u, s1 = g < 4 ? 0u : one;
      const uint32_t e0 = hold32((g & 1) ? 0u : s0), e1 = hold32((g & 1) ? 0u : s1), o0 = hold32((g & 1) ? s0 : 0u), o1 = hold32((g & 1) ? s1 : 0u);
      const float xf[4] = {holdf(bf_lo(xw0)), holdf(bf_hi(xw0)), holdf(bf_lo(xw1)), holdf(bf_hi(xw1))};
#pragma unroll
      for (int i = 0; i < 4; i++) ga[i] = holdf(ga[i]);
      PROBE_UNITS(43, 48);
      mbar_wait_b(hi + BAR(BAR_P5D));
      backoff(D_X3A);
      float d[4][4];
      poll_vectors<4>(pi, pi + 256, [&](const uint4 (&v)[4]) {
#pragma unroll
        for (int i = 0; i < 4; i++) { d[i][0] = d[i][1] = d[i][2] = d[i][3] = 0.f; mma_v(d[i], v[i], (i & 2) ? o0 : e0, (i & 2) ? o1 : e1); }
      });
      TLW(37);
      float s[4] = {d[0][0] + d[1][0], d[2][1] + d[3][1], d[0][2] + d[1][2], d[2][3] + d[3][3]};
#pragma unroll
      for (int i = 0; i < 4; i++) s[i] += __shfl_xor_sync(~0u, s[i], 8);
#pragma unroll
      for (int i = 0; i < 4; i++) s[i] += __shfl_xor_sync(~0u, s[i], 16);
      x2a = pack_bf16(xf[0] + ga[0] * s[0], xf[1] + ga[1] * s[1]);
      x2b = pack_bf16(xf[2] + ga[2] * s[2], xf[3] + ga[3] * s[3]);
      stg_u64(po, x2a, x2b);
      mbar_wait(hi + BAR(BAR_P5D));
    }
    TLW(20);
    {
      const uint32_t a0 = __shfl_sync(~0u, x2a, 2 * bf), a1 = __shfl_sync(~0u, x2a, 2 * bf + 1);
      const uint32_t b0 = __shfl_sync(~0u, x2b, 2 * bf), b1 = __shfl_sync(~0u, x2b, 2 * bf + 1);
      const uint32_t y0 = (t & 2) ? b0 : a0, y1 = (t & 2) ? b1 : a1;
      const float r0 = holdf((g & 2) ? bf_hi(y0) : bf_lo(y0)), r1 = holdf((g & 2) ? bf_hi(y1) : bf_lo(y1)), gb0 = holdf(bf_lo(gb2)), gb1 = holdf(bf_hi(gb2));
      const uint32_t* const pi = hold(inbox(cta, 4, fo_, 0, (4 * (g >> 2) + t) * 16 + (g & 3) * 4));
      const uint32_t* const pj = hold(inbox(cta, 5, ~fo_, 0, (4 * (g >> 2) + t) * 16 + (g & 3) * 4));
      __nv_bfloat16* const fo = hold(gout + (2 * bf) * 512 + mf);
      const uint32_t one = (g & 1) ? 0x3f800000u : 0x00003f80u;
      const uint32_t s0 = hold32((g & 2) ? 0u : one), s1 = hold32((g & 2) ? one : 0u);
      if (cta < NFF) { mbar_wait_b(hi + BAR(BAR_P7D)); backoff(D_FIN); } else backoff(D_FIN2);
      float d[4][4];
      poll_vectors<NFF / 8>(pi, pj, [&](const uint4 (&v)[NFF / 8]) {
#pragma unroll
        for (int i = 0; i < 4; i++) d[i][0] = d[i][1] = d[i][2] = d[i][3] = 0.f;
#pragma unroll
        for (int i = 0; i < NFF / 8; i++) mma_v(d[i & 3], v[i], s0, s1);
      });
      TLW(38);
      const bool up = t & 2;
      float v0 = up ? (d[0][2] + d[1][2]) + (d[2][2] + d[3][2]) : (d[0][0] + d[1][0]) + (d[2][0] + d[3][0]);
      float v1 = up ? (d[0][3] + d[1][3]) + (d[2][3] + d[3][3]) : (d[0][1] + d[1][1]) + (d[2][1] + d[3][1]);
      v0 += __shfl_xor_sync(~0u, v0, 16);
      v1 += __shfl_xor_sync(~0u, v1, 16);
      if (g < 4) {
        asm volatile("st.global.u16 [%0], %1;" ::"l"(fo), "h"(__bfloat16_as_ushort(__float2bfloat16(r0 + gb0 * v0))) : "memory");
        asm volatile("st.global.u16 [%0], %1;" ::"l"(fo + 512), "h"(__bfloat16_as_ushort(__float2bfloat16(r1 + gb1 * v1))) : "memory");
      }
    }
    TLW(23);
    if (cta == 0 && lane == 0) stg1(&gs->epoch, epoch + 1);
    return;
  }

  if (w == 9) {
    if (lane == 0) {
      mbar_expect(hi + BAR(BAR_XE), 16384 + 4096);
      mbar_wait(hi + BAR(BAR_EMPTY + 3));
      mbar_wait(hi + BAR(BAR_FULL + XE_AT));
      TLW(33);
      bulk_load(hi + OFF_XE, gs->XE + cta * 4096, 16384, hi + BAR(BAR_XE));
      bulk_load(hi + OFF_MLS, gs->MLE + hI * 1024, 4096, hi + BAR(BAR_XE));
    }
    return;
  }

  const int wg = w >> 2, wq = w & 3;
  if (!p0a) {
    asm volatile("cp.async.wait_all;" ::: "memory");
    cw0 = ldg_in4(gc + g * 1024 + w * 128 + t * 32); cw1 = ldg_in4(gc + g * 1024 + w * 128 + t * 32 + 16);
  }
  uint32_t cf[8] = {cw0.x, cw0.y, cw0.z, cw0.w, cw1.x, cw1.y, cw1.z, cw1.w};
#pragma unroll
  for (int i = 0; i < 8; i++) cf[i] = silu2(cf[i]);
  if (p0a) {
    sts4(hi + OFF_R0 + w * 1024 + g * 128 + (((2 * t) ^ g) << 4), make_uint4(cf[0], cf[1], cf[2], cf[3]));
    sts4(hi + OFF_R0 + w * 1024 + g * 128 + (((2 * t + 1) ^ g) << 4), make_uint4(cf[4], cf[5], cf[6], cf[7]));
    asm volatile("fence.proxy.async.shared::cta;" ::: "memory");
  {
    float v[16];
    const uint32_t u[8] = {xr0.x, xr0.y, xr0.z, xr0.w, xr1.x, xr1.y, xr1.z, xr1.w};
#pragma unroll
    for (int i = 0; i < 8; i++) { v[2 * i] = bf_lo(u[i]); v[2 * i + 1] = bf_hi(u[i]); }
    float s = (((v[0] + v[1]) + (v[2] + v[3])) + ((v[4] + v[5]) + (v[6] + v[7]))) + (((v[8] + v[9]) + (v[10] + v[11])) + ((v[12] + v[13]) + (v[14] + v[15])));
#pragma unroll
    for (int o = 16; o; o >>= 1) s += __shfl_xor_sync(~0u, s, o);
    const float mu = s * (1.f / 512.f);
    float q0 = 0.f, q1 = 0.f;
#pragma unroll
    for (int i = 0; i < 8; i++) { const float a = v[2 * i] - mu, b = v[2 * i + 1] - mu; q0 += a * a; q1 += b * b; }
    float q = q0 + q1;
#pragma unroll
    for (int o = 16; o; o >>= 1) q += __shfl_xor_sync(~0u, q, o);
    const float rs = rsqrtf(q * (1.f / 512.f) + 1e-5f);
    asm volatile("st.shared.u16 [%0], %1;" ::"r"(hi + OFF_P0S + lane * 32 + w * 2), "h"(__bfloat16_as_ushort(__float2bfloat16((bf_lo(xc) - mu) * rs))) : "memory");
    asm volatile("st.shared.u16 [%0], %1;" ::"r"(hi + OFF_P0S + lane * 32 + 16 + w * 2), "h"(__bfloat16_as_ushort(__float2bfloat16((bf_hi(xc) - mu) * rs))) : "memory");
  }
    cbar();
    TL(1);
  }
  if (p0a && wg == 0) {
    uint32_t* const mo = gs->MODA + cta * 32 + wq * 64 + lane;
    const uint32_t xn0 = lds1(hi + OFF_P0S + wq * 256 + lane * 4), xn1 = lds1(hi + OFF_P0S + wq * 256 + 128 + lane * 4);
    float d[4] = {0.f, 0.f, 0.f, 0.f};
    asm volatile("" : "+f"(d[0]), "+f"(d[1]), "+f"(d[2]), "+f"(d[3]) :: "memory");
#pragma unroll 1
    for (int i = 0; i < 4; i++) {
      mbar_wait(hi + BAR(BAR_WA) + 8 * i);
      wg_fence();
#pragma unroll
      for (int ks = 0; ks < 8; ks++) wgmma_n8(d, dlo(slot(8)) + i * 1024 + ks * 128, dlo(OFF_R0) + i * 128 + (ks >> 2) * 64 + (ks & 3) * 2);
      wg_commit();
    }
    wg_wait<0>();
    asm volatile("" : "+f"(d[0]), "+f"(d[1]), "+f"(d[2]), "+f"(d[3]) :: "memory");
    uint32_t y0 = pack_bf16(d[0], d[1]), y1 = pack_bf16(d[2], d[3]);
    if (cta >= 64) { y0 = hmul2(xn0, hadd2(y0, ONE2)); y1 = hmul2(xn1, hadd2(y1, ONE2)); }
    stg1(mo, nz(y0));
    stg1(mo + 32, nz(y1));
    TL(3);
  }
  cbar();
  TL(2);
  {
    uint32_t* const qpo = pin(gs->QP + (cta * 256 + tid) * 2);
    const uint32_t* const modi = pin(gs->MODA + 512 * jI + tid * 2);
    uint32_t a[8][4];
    mbar_wait(hi + BAR(BAR_FULL + U_WQ) + 8 * wg); mbar_wait(hi + BAR(BAR_FULL + U_WQ + 2) + 8 * wg);
    load_a_t(a, hi + OFF_R1 + wg * 16384, wq, lane);
    mbar_wait(hi + BAR(BAR_FULL + U_WQ + MOD_AT));
    backoff(D_MOD);
    TL(48);
    uint2 sa, ca;
    do { sa = ldg_rlx2(modi); ca = ldg_rlx2(modi + 2048); } while (min(min(sa.x, sa.y), min(ca.x, ca.y)) == 0);
    TL(41);
    sts2(hi + OFF_BS + tid * 8, hadd2(ca.x, sa.x), hadd2(ca.y, sa.y));
    cbar();
    float d[4];
    mma128(d, a, hi + OFF_BS + lane * 16);
    stg_u64(qpo, pack_bf16(d[0], d[1]), pack_bf16(d[2], d[3]));
  }
  const uint32_t ckq = clk32();
  TL(6);
  mbar_wait(hi + BAR(BAR_EPOCH));
  const int par = lds1(hi + OFF_EPOCH) & 1;
  uint32_t* const QX = gs->QX[par];
  {
    uint32_t a[8][4];
    {
      const int mi = lane >> 3, r = lane & 7;
      const int row = 16 * w + 8 * (mi & 1) + r;
      mbar_wait(hi + BAR(BAR_FULL + U_WUK) + 16 * wg); mbar_wait(hi + BAR(BAR_FULL + U_WUK + 1) + 16 * wg);
#pragma unroll
      for (int ks = 0; ks < 8; ks++) {
        const int chunk = 2 * ks + (mi >> 1);
        ldsm4(a[ks], hi + OFF_R2 + (ks >> 2) * 16384 + row * 128 + (((chunk & 7) ^ r) << 4));
      }
    }
    TL(8);
    uint32_t* const qxo = pin(QX + ((lane >> 1) * 32 + hI) * 256 + (128 * jI + 16 * w + 8 * (lane & 1)) / 2);
    const uint32_t* const qpi = pin(gs->QP + (hI * 4 * 256 + tid) * 2);
    mbar_wait(hi + BAR(BAR_FULL - 1));
    wait_until(ckq, D_QP);
    TL(29);
    uint2 qp[4];
#pragma unroll
    for (int i = 0; i < 4; i++) qp[i] = ldg_u64(qpi + i * 512);
    sum4_to_smem(qp, qpi, qpi + 1024, hi + OFF_BS2 + (16 * w + g) * 16 + t * 4);
    TL(7);
    cbar();
    float d[4];
    mma128(d, a, hi + OFF_BS2 + lane * 16);
    const float sc = 0.08838834764831845f * 1.4426950408889634f;
    const uint32_t stg = hi + OFF_P0S + 4096 + w * 256;
    stsm2t(stg + (lane & 7) * 32 + ((lane >> 3) & 1) * 16, pack_bf16(d[0] * sc, d[1] * sc), pack_bf16(d[2] * sc, d[3] * sc));
    __syncwarp();
    if (lane < 16) stg_u128(qxo, lds4(stg + lane * 16));
    if (lane == 0) mbar_arrive(hi + BAR(BAR_P2E));
  }
  const uint32_t ckx = clk32();
  TL(9);
  uint32_t fb = 0;
  {
    const uint32_t* qx = pin(QX + bI * 8192 + w * 1024 + lane * 4);
    mbar_wait(hi + BAR(BAR_FULL + QX_AT));
    wait_until(ckx, D_QX);
    TL(4);
    uint4 v[8];
#pragma unroll
    for (int i = 0; i < 8; i++) v[i] = ldg_u128(qx + i * 128);
    cbar();
    while (true) {
      bool all = true;
#pragma unroll
      for (int i = 0; i < 8; i++) all = all && v[i].w != 0;
      if (all) break;
#pragma unroll
      for (int i = 0; i < 8; i++) if (v[i].w == 0) v[i] = ldg_u128(qx + i * 128);
    }
    TL(5);
#pragma unroll
    for (int i = 0; i < 8; i++) {
      const int hh = (4 * w + (i >> 1)) ^ (16 * rI), ch = 32 * (i & 1) + lane;
      sts4(hi + OFF_R0 + (ch >> 3) * 4096 + hh * 128 + (((ch & 7) ^ (hh & 7)) << 4), v[i]);
    }
    asm volatile("fence.proxy.async.shared::cta;" ::: "memory");
    cbar();
    if (tid == 0) mbar_arrive(hi + BAR(BAR_GO));
  }
  TL(10);

  uint32_t ck1;
  const uint32_t *px, *pm;
  uint32_t *x2o, *x2p;
  {
    float O32[4][16], O16[4][8];
    uint32_t ebar;
    asm("mapa.shared::cluster.u32 %0, %1, %2;" : "=r"(ebar) : "r"(hi + BAR(BAR_EMPTY)), "r"(rI ^ (lane & 1)));
#pragma unroll
    for (int i = 0; i < 16; i++) O32[0][i] = O32[1][i] = O32[2][i] = O32[3][i] = 0.f;
#pragma unroll
    for (int i = 0; i < 4; i++) tie(O32[i]);
    auto pv2 = [&](int T, int WG, auto& O, int mb, int k0, int k1) {
      const int n = 8 * T + 4 * WG + mb;
      const uint32_t da = dlo(SB) + (sizeof(O[0]) == 64 ? n : n - 21) * 512, db = (WG && mb && T == 2) ? dlo(SB) : da + 512, dp = dlo(OFF_PT) + (T & 1) * 256;
#pragma unroll
      for (int ks = k0; ks < k1; ks++) { wgmma_ss<1, 1>(O[mb], da + ks * 128, dp + ks * 2); wgmma_ss<1, 1>(O[mb + 1], db + ks * 128, dp + ks * 2); }
      wg_commit();
    };
    auto pv = [&](int T, int WG, auto& O) { wg_fence(); pv2(T, WG, O, 0, 0, 4); pv2(T, WG, O, 2, 0, 4); };
    auto release = [&](int T, auto& O) {
      wg_wait<0>();
#pragma unroll
      for (int i = 0; i < 4; i++) tie(O[i]);
      if (lane < 2) mbar_arrive_cluster(ebar + 8 * T);
      TL(T < 3 ? 24 + T : 32);
    };
    auto rescale = [&](auto& O) {
#pragma unroll
      for (int jn = 0; jn < (int)(sizeof(O[0]) / 16); jn++) {
        const float2 a = ldsf2(hi + OFF_ALPHA + (8 * jn + 2 * t) * 4);
#pragma unroll
        for (int mb = 0; mb < 4; mb++) { O[mb][4 * jn] *= a.x; O[mb][4 * jn + 1] *= a.y; O[mb][4 * jn + 2] *= a.x; O[mb][4 * jn + 3] *= a.y; }
      }
    };
    uint64_t oe[8];
    uint32_t* const x1e = hold(gs->XE + (((16 * (1 - rI) + 2 * t) * 4 + 2 * wg) * 64 + (cta >> 1)) * 64 + (((wq * 8 + g) * 2) ^ ((pI & 3) << 3)));
    auto split_o = [&] {
#pragma unroll
      for (int i = 0; i < 8; i++) {
        const int jj = i >> 2, r = 8 + 4 * ((i >> 1) & 1) + (i & 1);
        oe[i] = pair64(pack_bf16(O32[2 * jj][r], O32[2 * jj][r + 2]), (pack_bf16(O32[2 * jj + 1][r], O32[2 * jj + 1][r + 2]) | 1u) ^ par);
      }
#pragma unroll
      for (int i = 0; i < 32; i++) asm volatile("mov.b32 %0, %1;" : "=f"(O16[i >> 3][i & 7]) : "f"(O32[i >> 3][i & 7]));
    };
    auto put_early = [&](int i) { stg_b64(x1e + ((8 * ((i >> 1) & 1) + (i & 1)) * 4 + (i >> 2)) * 4096, oe[i]); };
    auto p0b = [&] {
      const int mi = lane >> 3, r = lane & 7;
      const uint32_t abase = hi + OFF_WM + wg * (20 * 8192) + (64 * wq + 16 * (r >> 1) + 2 * (mi >> 1) + (r & 1)) * 64;
      mbar_wait(hi + BAR(BAR_FULL + U_WMOD) + 8 * wg);
      float e0[4] = {0.f, 0.f, 0.f, 0.f}, e1[4] = {0.f, 0.f, 0.f, 0.f};
      uint32_t a[4][4];
#pragma unroll
      for (int ks = 0; ks < 4; ks++) ldsm4t(a[ks], abase + ks * 256 + (((2 * rI + (mi & 1)) ^ ((2 * ks + (mi >> 1)) & 3)) << 4));
#pragma unroll
      for (int ks = 0; ks < 4; ks++) mma16816((ks & 1) ? e1 : e0, a[ks], cf[2 * ks], cf[2 * ks + 1]);
      sts4f(hi + OFF_R0 + w * 4096 + 2048 + lane * 16, e0[0] + e1[0], e0[1] + e1[1], e0[2] + e1[2], e0[3] + e1[3]);
    };
    uint32_t* x1l[4];
    auto late_addr = [&] {
      mbar_wait(hi + BAR(BAR_FM));
      fb = lds1(hi + OFF_FB + tid * 4);
#pragma unroll
      for (int i = 0; i < 4; i++)
        x1l[i] = hold(inbox((16 * rI + 2 * t) * 4 + 2 * wg + (bI >> 2), bI & 3, fb, 4 * (i & 1) + (i >> 1), pI * 128 + (wq * 8 + g) * 2));
      px = hold(inbox((cta & ~1) + wg, wq, (fb >> (8 + (jI & 2) + wg)) ^ wq, 0, t * 128 + rI * 64 + 4 * g));
      pm = hold(inbox(cta & ~1, 6, fb, 8 + (jI & 2), 512 + (w * 8 + t) * 8));
      x2o = hold(inbox(4 * hI + (jI >> 1) + (~jI & 2), 7, ~fb, 8 + (jI >> 1) + (~jI & 2), (jI & 1) * 512 + tid * 2));
      x2p = hold(inbox(4 * hI + (jI >> 1) + (jI & 2), 7, ~fb, 8 + (jI >> 1) + (jI & 2), (jI & 1) * 512 + tid * 2));
    };
    auto put_late = [&](int jj) {
#pragma unroll
      for (int i = 0; i < 4; i++) {
        const int jn = i >> 1, e = i & 1, r = 4 * jn + e;
        stg_u64(x1l[i] + (8 * jn + e) * 4 * 16384 + jj * 64, pack_bf16(O16[2 * jj][r], O16[2 * jj][r + 2]), pack_bf16(O16[2 * jj + 1][r], O16[2 * jj + 1][r + 2]));
      }
    };
    auto last_products = [&](int WG) {
      wg_fence();
      pv2(4, WG, O16, 0, 0, 4);
      ck1 = clk32();
      pv2(4, WG, O16, 2, 0, PV_SPLIT);
      wg_wait<1>();
      tie(O16[0]); tie(O16[1]);
      TL(12);
      put_late(0);
      __syncwarp();
      if (PV_SPLIT < 4) { wg_fence(); pv2(4, WG, O16, 2, PV_SPLIT, 4); }
      wg_wait<0>();
      tie(O16[2]); tie(O16[3]);
      TL(50);
      put_late(1);
    };

    if (wg == 0) {
      float S32[16], S16[8];
      float m_run = -INFINITY;
      float mh[8];
#pragma unroll
      for (int i = 0; i < 16; i++) S32[i] = S16[i & 7] = mh[i & 7] = 0.f;
      const uint32_t ptl = hold32(hi + OFF_PT + (8 * (lane >> 4) + (lane & 7)) * 128 + (((2 * wq + ((lane >> 3) & 1)) ^ (lane & 7)) << 4));
      auto landed = [&](int T) { return __ballot_sync(~0u, mbar_test(hi + BAR(BAR_FULL + 8 * T) + 8 * (lane & 7))); };
      auto softmax = [&](int T, auto& O, auto& S) {
        constexpr int NJ = sizeof(S) / 16;
        wg_wait<0>();
        tie(S);
        if (NJ == 2) TL(T == 4 ? 11 : 52);
        auto update = [&] {
            float mx[2 * NJ];
#pragma unroll
            for (int jn = 0; jn < NJ; jn++) { mx[2 * jn] = fmaxf(S[4 * jn], S[4 * jn + 2]); mx[2 * jn + 1] = fmaxf(S[4 * jn + 1], S[4 * jn + 3]); }
            float a4[4], a2[2], a1;
            if constexpr (NJ == 4) {
              const bool up = lane & 16;
#pragma unroll
              for (int i = 0; i < 4; i++) { const float send = up ? mx[i] : mx[4 + i]; const float keep = up ? mx[4 + i] : mx[i]; a4[i] = fmaxf(keep, __shfl_xor_sync(~0u, send, 16)); }
            } else {
#pragma unroll
              for (int i = 0; i < 4; i++) { a4[i] = fmaxf(mx[i], __shfl_xor_sync(~0u, mx[i], 16)); if (lane & 16) a4[i] = -INFINITY; }
            }
            {
              const bool up = lane & 8;
#pragma unroll
              for (int i = 0; i < 2; i++) { const float send = up ? a4[i] : a4[2 + i]; const float keep = up ? a4[2 + i] : a4[i]; a2[i] = fmaxf(keep, __shfl_xor_sync(~0u, send, 8)); }
            }
            {
              const bool up = lane & 4;
              const float send = up ? a2[0] : a2[1]; const float keep = up ? a2[1] : a2[0];
              a1 = fmaxf(keep, __shfl_xor_sync(~0u, send, 4));
            }
            stsf(hi + OFF_RED + (wq * 32 + 8 * (g >> 1) + 2 * t + (g & 1)) * 4, a1);
            wg0bar();
            const float mt = fmaxf(fmaxf(ldsf(hi + OFF_RED + lane * 4), ldsf(hi + OFF_RED + 128 + lane * 4)),
                                   fmaxf(ldsf(hi + OFF_RED + 256 + lane * 4), ldsf(hi + OFF_RED + 384 + lane * 4)));
            const float m_new = fmaxf(m_run, ceilf(mt));
            if (wq == 0) { stsf(hi + OFF_MREF + lane * 4, m_new); stsf(hi + OFF_ALPHA + lane * 4, ex2(m_run - m_new)); }
            m_run = m_new;
#pragma unroll
            for (int i = 0; i < 2 * NJ; i++) mh[i] = __shfl_sync(~0u, m_new, 8 * (i >> 1) + 2 * t + (i & 1));
            if (T > 0) { wg0bar(); rescale(O); }
        };
        auto write_p = [&] {
          uint32_t pk[2 * NJ];
          float x[4 * NJ];
#pragma unroll
          for (int i = 0; i < 4 * NJ; i++) x[i] = S[i] - mh[2 * (i >> 2) + (i & 1)];
#pragma unroll
          for (int i = 0; i < 2 * NJ; i++) pk[i] = pack_bf16(ex2(x[2 * i]), ex2(x[2 * i + 1]));
#pragma unroll
          for (int hf = 0; hf < NJ / 2; hf++) stsm4t(ptl + (T & 1) * 4096 + hf * 2048, pk[4 * hf], pk[4 * hf + 1], pk[4 * hf + 2], pk[4 * hf + 3]);
          asm volatile("fence.proxy.async.shared::cta;" ::: "memory");
          if constexpr (NJ == 4) {
#pragma unroll
            for (int i = 0; i < 8; i++) x[i] = fmaxf(x[i], x[i + 8]);
          }
          return cbar_or(fmaxf(fmaxf(fmaxf(x[0], x[1]), fmaxf(x[2], x[3])), fmaxf(fmaxf(x[4], x[5]), fmaxf(x[6], x[7]))) > 64.f);
        };
        if constexpr (NJ == 4) {
          bool over = T == 0;
#pragma unroll 1
          do {
            if (over) update();
            over = write_p();
          } while (__builtin_expect(over, 0));
        } else {
#pragma unroll 1
          while (__builtin_expect(write_p(), 0)) update();
        }
        if (NJ == 2) TL(T == 4 ? 34 : 53);
      };
      uint32_t have = 0;
#pragma unroll
      for (int i = 0; i < 4; i++) x1l[i] = nullptr;
      px = pm = x2o = x2p = nullptr;
#pragma unroll 1
      for (int T = 0; T < 3; T++) {
        UNROLL(QK_UNROLL)
        for (int jj = 0; jj < 8; jj++) {
          const uint32_t da = dlo(SB) + box_slot(8 * T + jj) * 512, db = dlo(OFF_R0) + jj * 256;
          mbar_wait(hi + BAR(BAR_FULL) + 64 * T + 8 * jj);
          wg_fence();
          wgmma_ss_p(S32, da, db, jj);
#pragma unroll
          for (int ks = 1; ks < 4; ks++) wgmma_ss<0, 1>(S32, da + ks * 2, db + ks * 2);
          wg_commit();
        }
        softmax(T, O32, S32);
        pv(T, 0, O32);
        have = landed(3);
        release(T, O32);
        if (T == 1) late_addr();
      }
      split_o();
      p0b();
      TL(27);
#pragma unroll 1
      for (int T = 3;; T++) {
        sfor<0, 8>([&](auto jc) {
          constexpr int jj = decltype(jc)::value;
          const uint32_t da = dlo(SB) + (8 * T + jj - 21) * 512, db = dlo(OFF_R0) + jj * 256;
          if (!((have >> jj) & 1)) mbar_wait(hi + BAR(BAR_FULL) + 64 * T + 8 * jj);
          wg_fence();
          wgmma_ss<0, jj != 0>(S16, da, db);
#pragma unroll
          for (int ks = 1; ks < 4; ks++) wgmma_ss<0, 1>(S16, da + ks * 2, db + ks * 2);
          wg_commit();
          if (T == 3) {
            put_early(jj);
          }
        });
        softmax(T, O16, S16);
        if (T == 4) break;
        pv(3, 0, O16);
        have = landed(4);
        release(3, O16);
      }
      last_products(0);
    } else {
      float ls[2] = {0.f, 0.f};
      const int hr = 4 * wq + (lane >> 3);
      const uint32_t ptl = hi + OFF_PT + (tid & 127) * 16;
      auto sum8 = [](const uint4& v) { return ((bf_lo(v.x) + bf_hi(v.x)) + (bf_lo(v.y) + bf_hi(v.y))) + ((bf_lo(v.z) + bf_hi(v.z)) + (bf_lo(v.w) + bf_hi(v.w))); };
      auto row_sum = [](float l) { l += __shfl_xor_sync(~0u, l, 1); l += __shfl_xor_sync(~0u, l, 2); return l + __shfl_xor_sync(~0u, l, 4); };
      auto get_p = [&](auto& O) {
        if (__builtin_expect(cbar_or(false), 0)) {
          cbar_or(false);
          rescale(O);
          ls[0] *= ldsf(hi + OFF_ALPHA + hr * 4);
          if (sizeof(O[0]) == 64) ls[1] *= ldsf(hi + OFF_ALPHA + 64 + hr * 4);
        }
      };
#pragma unroll 1
      for (int T = 0; T < 3; T++) {
        get_p(O32);
        pv(T, 1, O32);
        ls[0] += sum8(lds4(ptl + (T & 1) * 4096));
        ls[1] += sum8(lds4(ptl + (T & 1) * 4096 + 2048));
        release(T, O32);
      }
      split_o();
      {
        const float l0 = row_sum(ls[0]), l1 = row_sum(ls[1]);
        const int hl = hr + 8 * (lane & 2);
        const uint32_t m = lds1(hi + OFF_MREF + hl * 4), l = (__float_as_uint((lane & 2) ? l1 : l0) | 1u) ^ par;
        if (!(lane & 4)) stg4_b128(gs->MLE + ((hl ^ (16 * rI)) * 128 + cta) * 8 + (lane & 1) * 4, make_uint4(m, l, m, l));
#pragma unroll
        for (int i = 0; i < 8; i++) put_early(i);
      }
      get_p(O16);
      pv(3, 1, O16);
      ls[0] += sum8(lds4(ptl + 4096));
      release(3, O16);
      p0b();
      asm volatile("bar.sync 3, 128;" ::: "memory");
      if (wq < 2) {
        if (tid == 128) mbar_arrive(hi + BAR(BAR_P0D));
        float2 v[8];
#pragma unroll
        for (int i = 0; i < 8; i++) v[i] = ldsf2(hi + OFF_R0 + i * 4096 + 2048 + lane * 16 + wq * 8);
        stg1(gs->MODB[par] + cta * 64 + wq * 32 + lane, nz(pack_bf16(((v[0].x + v[1].x) + (v[2].x + v[3].x)) + ((v[4].x + v[5].x) + (v[6].x + v[7].x)),
                                                                     ((v[0].y + v[1].y) + (v[2].y + v[3].y)) + ((v[4].y + v[5].y) + (v[6].y + v[7].y)))));
        TLW(31);
      }
      late_addr();
      uint32_t* const mlo = hold(inbox((16 * rI + hr) * 4 + (lane & 2), 6, fb, 13, 512 + (cta >> 1) * 8 + (lane & 1) * 4));
      mbar_wait(hi + BAR(BAR_CLR));
      get_p(O16);
      {
        const uint32_t m = lds1(hi + OFF_MREF + hr * 4), l = nz(__float_as_uint(row_sum(ls[0] + sum8(lds4(ptl)))));
        if (!(lane & 4)) stg4_b128(mlo, make_uint4(m, l, m, l));
      }
      last_products(1);
    }
  }
  if (lane == 0) mbar_arrive(hi + BAR(BAR_X1W));
  TL(13);

  uint32_t aw[8][4];
  {
    uint2 mle[4];
    uint4 ve[4];
    wait_until(ck1, X1_D0);
    uint2 ml[2];
    uint4 v[4];
#pragma unroll
    for (int i = 0; i < 4; i++) v[i] = ldg_2u64(px + (i >> 1) * 512 + (i & 1) * 32);
#pragma unroll
    for (int i = 0; i < 2; i++) ml[i] = ldg_u64(pm + i * 32);
    TL(43);
    mbar_wait(hi + BAR(BAR_XE));
#pragma unroll
    for (int i = 0; i < 4; i++) mle[i] = lds2(hi + OFF_MLS + (w * 16 + 2 * t + 8 * (i & 1) + ((hI >> 4) ^ (i >> 1))) * 32);
#pragma unroll
    for (int i = 0; i < 4; i++) ve[i] = lds4(hi + OFF_XE + (w * 8 + t) * 256 + (g ^ (2 * t)) * 16 + (i >> 1) * 1024 + (i & 1) * 128);
#pragma unroll 1
    while (true) {
      uint32_t a = 1u, o = 0u;
#pragma unroll
      for (int i = 0; i < 4; i++) { a &= ve[i].y & ve[i].w & mle[i].y; o |= ve[i].y | ve[i].w | mle[i].y; }
      if (__all_sync(~0u, (par ? ~o : a) & 1)) break;
#pragma unroll
      for (int i = 0; i < 4; i++) {
        ve[i] = ldg_2u64(gs->XE + (cta * 64 + w * 8 + t) * 64 + 4 * (g ^ (2 * t)) + (i >> 1) * 256 + (i & 1) * 32);
        mle[i] = ldg_u64(gs->MLE + (hI * 128 + w * 16 + 2 * t + 8 * (i & 1) + ((hI >> 4) ^ (i >> 1))) * 8);
      }
      TL(55);
    }
    float M = fmaxf(fmaxf(__uint_as_float(mle[0].x), __uint_as_float(mle[1].x)), fmaxf(__uint_as_float(mle[2].x), __uint_as_float(mle[3].x)));
    M = fmaxf(M, __shfl_xor_sync(~0u, M, 1)); M = fmaxf(M, __shfl_xor_sync(~0u, M, 2));
    uint32_t wb[4];
#pragma unroll
    for (int i = 0; i < 4; i++) wb[i] = pack_bf16(ex2(__uint_as_float(mle[i].x) - M), 0.f);
    float Ls = bf_lo(wb[2]) * __uint_as_float(mle[2].y) + bf_lo(wb[3]) * __uint_as_float(mle[3].y);
    float d0[4] = {0.f, 0.f, 0.f, 0.f}, d1[4] = {0.f, 0.f, 0.f, 0.f};
#pragma unroll
    for (int i = 0; i < 4; i++) mma_v((i & 2) ? d1 : d0, ve[i], shl_clamp(wb[2 + (i >> 1)], 16 * g - 64 * (i & 1)), shl_clamp(wb[2 + (i >> 1)], 16 * g - 64 * (i & 1) - 32));
    uint32_t sel[4][2];
#pragma unroll
    for (int i = 0; i < 4; i++) { sel[i][0] = pin32(shl_clamp(wb[i >> 1], 16 * g - 64 * (i & 1))); sel[i][1] = pin32(shl_clamp(wb[i >> 1], 16 * g - 64 * (i & 1) - 32)); }
    const uint32_t bso = hold32(hi + OFF_BS4 + w * 320 + (16 * (t >> 1) + 8 * (g >> 2) + 4 * (g & 1) + 2 * (t & 1) + ((g >> 1) & 1)) * 8), bsi = hold32(hi + OFF_BS4 + g * 320 + t * 16);
    const uint32_t lso = hold32(hi + OFF_BS4 + w * 320 + 256 + t * 4), lsi = hold32(hi + OFF_BS4 + t * 640 + 256);
    TL(14);
    {
      const int mi = lane >> 3, r = lane & 7;
      const uint32_t base = hi + OFF_WUV + wg * 16384 + (mi >> 1) * 8192 + r * 128 + (((2 * wq + (mi & 1)) ^ r) << 4);
      mbar_wait(hi + BAR(BAR_FULL + U_WUV) + 16 * wg); mbar_wait(hi + BAR(BAR_FULL + U_WUV + 1) + 16 * wg);
#pragma unroll
      for (int ks = 0; ks < 8; ks++) ldsm4t(aw[ks], base + ks * 1024);
    }
    mbar_wait(hi + BAR(BAR_XE));
#pragma unroll
    for (int i = 0; i < 4; i++) tie(v[i]);
    tie(ml[0]); tie(ml[1]);
    TL(44);
    float e0[4], e1[4];
#pragma unroll 1
    while (true) {
      const bool valid = min(min3(min3(v[0].y, v[0].w, v[1].y), v[1].w, ml[0].y), min3(min3(v[2].y, v[2].w, v[3].y), v[3].w, ml[1].y)) != 0;
      const bool ok = __all_sync(~0u, valid && ml[0].x == mle[0].x && ml[1].x == mle[1].x);
#pragma unroll
      for (int i = 0; i < 4; i++) { e0[i] = d0[i]; e1[i] = d1[i]; }
      mma_v(e0, v[0], sel[0][0], sel[0][1]); mma_v(e1, v[2], sel[2][0], sel[2][1]);
      mma_v(e0, v[1], sel[1][0], sel[1][1]); mma_v(e1, v[3], sel[3][0], sel[3][1]);
      if (ok) break;
      if (__all_sync(~0u, valid)) {
        float M2 = fmaxf(M, fmaxf(__uint_as_float(ml[0].x), __uint_as_float(ml[1].x)));
        M2 = fmaxf(M2, __shfl_xor_sync(~0u, M2, 1)); M2 = fmaxf(M2, __shfl_xor_sync(~0u, M2, 2));
        const float f = ex2(M - M2);
        Ls *= f;
#pragma unroll
        for (int i = 0; i < 4; i++) { d0[i] *= f; d1[i] *= f; }
#pragma unroll
        for (int i = 0; i < 2; i++) { wb[i] = pack_bf16(ex2(__uint_as_float(ml[i].x) - M2), 0.f); mle[i].x = ml[i].x; }
#pragma unroll
        for (int i = 0; i < 4; i++) { sel[i][0] = shl_clamp(wb[i >> 1], 16 * g - 64 * (i & 1)); sel[i][1] = shl_clamp(wb[i >> 1], 16 * g - 64 * (i & 1) - 32); }
      }
#pragma unroll
      for (int i = 0; i < 4; i++) if (v[i].y == 0 || v[i].w == 0) v[i] = ldg_2u64(px + (i >> 1) * 512 + (i & 1) * 32);
#pragma unroll
      for (int i = 0; i < 2; i++) if (ml[i].y == 0) ml[i] = ldg_u64(pm + i * 32);
    }
    TL(15);
    stsf(lso, Ls + bf_lo(wb[0]) * __uint_as_float(ml[0].y) + bf_lo(wb[1]) * __uint_as_float(ml[1].y));
    sts2(bso, pack_bf16(e0[0] + e1[0], e0[1] + e1[1]), pack_bf16(e0[2] + e1[2], e0[3] + e1[3]));
    cbar();
    TL(16);
    float o[4][4] = {{0.f, 0.f, 0.f, 0.f}, {0.f, 0.f, 0.f, 0.f}, {0.f, 0.f, 0.f, 0.f}, {0.f, 0.f, 0.f, 0.f}};
    uint4 b[4];
#pragma unroll
    for (int kk = 0; kk < 4; kk++) b[kk] = lds4(bsi + kk * 64);
    const float4 la = ldsf4(lsi), lb = ldsf4(lsi + 320);
#pragma unroll
    for (int kk = 0; kk < 4; kk++) { mma16816(o[(2 * kk) & 3], aw[2 * kk], b[kk].x, b[kk].y); mma16816(o[(2 * kk + 1) & 3], aw[2 * kk + 1], b[kk].z, b[kk].w); }
    const float ia = rcp((la.x + la.y) + (la.z + la.w)), ib = rcp((lb.x + lb.y) + (lb.z + lb.w));
    const uint32_t y0 = pack_bf16(((o[0][0] + o[1][0]) + (o[2][0] + o[3][0])) * ia, ((o[0][1] + o[1][1]) + (o[2][1] + o[3][1])) * ib);
    const uint32_t y1 = pack_bf16(((o[0][2] + o[1][2]) + (o[2][2] + o[3][2])) * ia, ((o[0][3] + o[1][3]) + (o[2][3] + o[3][3])) * ib);
    stg_u64(x2o, y0, y1);
    stg_u64(x2p, y0, y1);
  }
  const uint32_t ck2 = clk32();
  TL(17);
  {
    uint32_t* const o = hold(inbox(4 * (8 * jI + w) + (g >> 1), 6, fb, 12, (g & 1) * 256 + hI * 8 + 2 * t));
    const uint32_t* const x2i = hold(inbox(cta & ~1, 7, ~fb, 8 + (jI & 2), tid * 2));
    const uint32_t* const x2j = hold(inbox(cta | 1, 7, ~fb, 8 + (jI | 1), tid * 2));
    const uint32_t bso = hold32(hi + OFF_BS5 + (16 * w + g) * 16 + t * 4), bsi = hold32(hi + OFF_BS5 + lane * 16);
    const uint32_t wa = hold32(hi + OFF_WO + wg * 8192 + (8 * (lane >> 4) + (lane & 7)) * 128 + (((2 * wq + ((lane >> 3) & 1)) ^ (lane & 7)) << 4));
    TL(45);
    wait_until(ck2, D_X2);
    uint2 v[4];
#pragma unroll
    for (int i = 0; i < 4; i++) v[i] = ldg_u64(((i & 2) ? x2j : x2i) + (i & 1) * 512);
    mbar_wait(hi + BAR(BAR_FULL + U_WO) + 8 * wg);
#pragma unroll
    for (int ks = 0; ks < 4; ks++) ldsm4t(aw[ks], wa + ks * 2048);
    const bool wo_ok = mbar_test(hi + BAR(BAR_FULL + U_WO + 2) + 8 * wg);
    if (wo_ok) {
#pragma unroll
      for (int ks = 0; ks < 4; ks++) ldsm4t(aw[4 + ks], wa + 16384 + ks * 2048);
    }
    mbar_wait(hi + BAR(BAR_XE));
#pragma unroll
    for (int i = 0; i < 4; i++) tie(v[i]);
    sum4_to_smem(v, x2i, x2j, bso);
    cbar();
    TL(18);
    float e[4][4] = {{0.f, 0.f, 0.f, 0.f}, {0.f, 0.f, 0.f, 0.f}, {0.f, 0.f, 0.f, 0.f}, {0.f, 0.f, 0.f, 0.f}};
    uint32_t b[4][4];
#pragma unroll
    for (int kk = 0; kk < 4; kk++) ldsm4t(b[kk], bsi + kk * 512);
    if (!wo_ok) {
      mbar_wait(hi + BAR(BAR_FULL + U_WO + 2) + 8 * wg);
#pragma unroll
      for (int ks = 0; ks < 4; ks++) ldsm4t(aw[4 + ks], wa + 16384 + ks * 2048);
    }
#pragma unroll
    for (int ks = 0; ks < 8; ks++) mma16816(e[ks & 3], aw[ks], b[ks >> 1][2 * (ks & 1)], b[ks >> 1][2 * (ks & 1) + 1]);
    stg_u64(o, pack_bf16((e[0][0] + e[1][0]) + (e[2][0] + e[3][0]), (e[0][1] + e[1][1]) + (e[2][1] + e[3][1])),
            pack_bf16((e[0][2] + e[1][2]) + (e[2][2] + e[3][2]), (e[0][3] + e[1][3]) + (e[2][3] + e[3][3])));
    if (lane == 0) mbar_arrive(hi + BAR(BAR_P5D));
  }
  const uint32_t ck3 = clk32();
  TL(19);
  if (cta < NFF) {
    const int mi = lane >> 3, r = lane & 7;
    uint32_t a1[4][4], a2[4][4];
    uint32_t bc[8], bs[8];
    const uint32_t* const mbi = gs->MODB[par] + (512 + 64 * w) * 4 + lane;
#pragma unroll
    for (int i = 0; i < 8; i++) { bs[i] = ldg_rlx1(mbi + i * 32); bc[i] = ldg_rlx1(mbi + 2048 + i * 32); }
    const int lp = (tid >> 2) & 31, kq = tid & 3;
    const int fo = (lp >> 2) + 8 * (kq >> 1), bo = 2 * (lp & 3) + (kq & 1);
    const uint32_t* xb = hold(gs->X3B + ((cta >> 1) & 1) * 4096 + wg * 2048 + (((fb >> 14) & 1) << 10) + (16 * wq + t) * 16 + 2 * g);
    uint32_t* ox[4];
#pragma unroll
    for (int mb = 0; mb < 4; mb++) ox[mb] = hold(inbox(16 * w + 4 * mb + (g >> 1), 4 + (cta >= 56), fb, 16 + 4 * mb, (cta >= 56 ? cta - 56 : cta) * 16 + (g & 1) * 8 + 2 * t));
    const uint32_t gi = hold32(hi + OFF_REDG + tid * 4);
    const uint32_t h1o = hold32(hi + OFF_H1 + fo * 16 + bo * 2), sti = hold32(hi + OFF_REDS + bo * 80), sto = hold32(hi + OFF_REDS + g * 80 + w * 8);
    const uint32_t a1a = hold32(hi + OFF_W1 + (64 * w + 8 * (mi >> 1) + r) * 64 + (((2 * rI + (mi & 1)) ^ (r >> 1)) << 4));
    bool w2ok = false;
    uint32_t a2a[4];
#pragma unroll
    for (int mb = 0; mb < 4; mb++) {
      a2a[mb] = hi + OFF_W2 + w * 2048 + (8 * (mi >> 1) + r) * 128 + (((2 * mb + (mi & 1)) ^ r) << 4);
      a2[mb][0] = a2[mb][1] = a2[mb][2] = a2[mb][3] = 0;
    }
#pragma unroll 1
    while (true) {
      uint32_t mn = 0xffffffffu;
#pragma unroll
      for (int i = 0; i < 8; i++) mn = min3(mn, bs[i], bc[i]);
      if (__all_sync(~0u, mn != 0)) break;
#pragma unroll
      for (int i = 0; i < 8; i++) { bs[i] = ldg_rlx1(mbi + i * 32); bc[i] = ldg_rlx1(mbi + 2048 + i * 32); }
    }
#pragma unroll
    for (int i = 0; i < 8; i++) { bs[i] = movm(bs[i]); bc[i] = hadd2(movm(bc[i]), ONE2); }
    mbar_wait(hi + BAR(BAR_FULL + U_W1) + 8 * wg);
#pragma unroll
    for (int ks = 0; ks < 4; ks++) ldsm4t(a1[ks], a1a + ks * 1024);
    {
      float u[2][4] = {{0.f, 0.f, 0.f, 0.f}, {0.f, 0.f, 0.f, 0.f}}, vv[2][4] = {{0.f, 0.f, 0.f, 0.f}, {0.f, 0.f, 0.f, 0.f}};
#pragma unroll
      for (int ks = 0; ks < 4; ks++) { mma16816(u[ks & 1], a1[ks], bc[2 * ks], bc[2 * ks + 1]); mma16816(vv[ks & 1], a1[ks], bs[2 * ks], bs[2 * ks + 1]); }
      sts4f(hi + OFF_REDU + tid * 16, u[0][0] + u[1][0], u[0][1] + u[1][1], u[0][2] + u[1][2], u[0][3] + u[1][3]);
      sts4f(hi + OFF_REDV + tid * 16, vv[0][0] + vv[1][0], vv[0][1] + vv[1][1], vv[0][2] + vv[1][2], vv[0][3] + vv[1][3]);
    }
    if (wg) asm volatile("bar.arrive 1, 256;" ::: "memory"); else cbar();
    float U = 0.f, V = 0.f;
    bool uv = wg;
    TL(46);
    wait_until(ck3, D_X3B);
    float G[2][4], S[2][4];
    bool ok;
#pragma unroll 1
    do {
      uint2 x[4];
#pragma unroll
      for (int ks = 0; ks < 4; ks++) x[ks] = ldg_u64(xb + ks * 64);
      if (!uv) {
        uv = true;
        float a[8], b[8];
#pragma unroll
        for (int i = 0; i < 8; i++) { a[i] = ldsf(gi + (OFF_REDU - OFF_REDG) + i * 512); b[i] = ldsf(gi + (OFF_REDV - OFF_REDG) + i * 512); }
        U = ((a[0] + a[1]) + (a[2] + a[3])) + ((a[4] + a[5]) + (a[6] + a[7]));
        V = ((b[0] + b[1]) + (b[2] + b[3])) + ((b[4] + b[5]) + (b[6] + b[7]));
      }
      if (!w2ok && mbar_test(hi + BAR(BAR_FULL + U_W2) + 8 * wg)) {
        w2ok = true;
#pragma unroll
        for (int mb = 0; mb < 4; mb++) ldsm4t(a2[mb], a2a[mb]);
      }
#pragma unroll
      for (int ks = 0; ks < 4; ks++) tie(x[ks]);
      ok = __all_sync(~0u, min(min3(x[0].y, x[1].y, x[2].y), x[3].y) != 0);
#pragma unroll
      for (int i = 0; i < 4; i++) G[0][i] = G[1][i] = S[0][i] = S[1][i] = 0.f;
#pragma unroll
      for (int ks = 0; ks < 4; ks++) {
        const uint32_t s0[4] = {x[ks].x, ONE2, x[ks].y, ONE2};
        mma16816(S[ks & 1], s0, x[ks].x, x[ks].y);
        mma16816(G[ks & 1], a1[ks], hmul2(x[ks].x, bc[2 * ks]), hmul2(x[ks].y, bc[2 * ks + 1]));
      }
    } while (!ok);
    TL(21);
    if ((g >> 1) == t) sts2f(sto, (g & 1) ? S[0][3] + S[1][3] : S[0][2] + S[1][2], (g & 1) ? S[0][1] + S[1][1] : S[0][0] + S[1][0]);
    sts4f(hi + OFF_REDG + tid * 16, G[0][0] + G[1][0], G[0][1] + G[1][1], G[0][2] + G[1][2], G[0][3] + G[1][3]);
    if (wg) asm volatile("bar.arrive 3, 256;" ::: "memory"); else asm volatile("bar.sync 3, 256;" ::: "memory");
    TL(39);
    if (tid < 128) {
      float gv[8];
      float4 sv[4];
#pragma unroll
      for (int i = 0; i < 4; i++) sv[i] = ldsf4(sti + i * 16);
#pragma unroll
      for (int i = 0; i < 8; i++) gv[i] = ldsf(gi + i * 512);
      const float s1 = ((sv[0].x + sv[0].z) + (sv[1].x + sv[1].z)) + ((sv[2].x + sv[2].z) + (sv[3].x + sv[3].z));
      const float s2 = ((sv[0].y + sv[0].w) + (sv[1].y + sv[1].w)) + ((sv[2].y + sv[2].w) + (sv[3].y + sv[3].w));
      const float gs_ = ((gv[0] + gv[1]) + (gv[2] + gv[3])) + ((gv[4] + gv[5]) + (gv[6] + gv[7]));
      const float mu = s1 * (1.f / 512.f);
      const float rs = rsq(fmaxf(s2 * (1.f / 512.f) - mu * mu, 0.f) + 1e-5f);
      const float hv = fmaxf(rs * (gs_ - mu * U) + V, 0.f);
      asm volatile("st.shared.u16 [%0], %1;" ::"r"(h1o), "h"(__bfloat16_as_ushort(__float2bfloat16(hv))) : "memory");
    }
    if (!w2ok) {
      mbar_wait(hi + BAR(BAR_FULL + U_W2) + 8 * wg);
#pragma unroll
      for (int mb = 0; mb < 4; mb++) ldsm4t(a2[mb], a2a[mb]);
    }
    asm volatile("bar.sync 2, 256;" ::: "memory");
    TL(40);
    uint32_t b0, b1;
    ldsm2t(b0, b1, hi + OFF_H1 + (lane & 15) * 16);
#pragma unroll
    for (int mb = 0; mb < 4; mb++) {
      float o[4] = {0.f, 0.f, 0.f, 0.f};
      mma16816(o, a2[mb], b0, b1);
      stg_u64(ox[mb], pack_bf16(o[0], o[1]), pack_bf16(o[2], o[3]));
    }
    TL(22);
    if (lane == 0) mbar_arrive(hi + BAR(BAR_P7D));
  }
}

typedef CUresult (*EncodeTiledFn)(CUtensorMap*, CUtensorMapDataType, cuuint32_t, void*, const cuuint64_t*, const cuuint64_t*,
                                  const cuuint32_t*, const cuuint32_t*, CUtensorMapInterleave, CUtensorMapSwizzle,
                                  CUtensorMapL2promotion, CUtensorMapFloatOOBfill);

void make_map(EncodeTiledFn enc, CUtensorMap* m, const void* base, uint64_t cols, uint64_t rows, uint32_t bc, uint32_t br,
              CUtensorMapSwizzle sw, CUtensorMapL2promotion promo) {
  cuuint64_t dims[2] = {cols, rows};
  cuuint64_t strides[1] = {cols * 2};
  cuuint32_t box[2] = {bc, br};
  cuuint32_t es[2] = {1, 1};
  enc(m, CU_TENSOR_MAP_DATA_TYPE_BFLOAT16, 2, const_cast<void*>(base), dims, strides, box, es, CU_TENSOR_MAP_INTERLEAVE_NONE, sw, promo,
      CU_TENSOR_MAP_FLOAT_OOB_FILL_NONE);
}
void make_map3(EncodeTiledFn enc, CUtensorMap* m, const void* base, uint64_t rows, uint32_t br, uint32_t bb) {
  cuuint64_t dims[3] = {64, rows, 8};
  cuuint64_t strides[2] = {1024, 128};
  cuuint32_t box[3] = {64, br, bb};
  cuuint32_t es[3] = {1, 1, 1};
  enc(m, CU_TENSOR_MAP_DATA_TYPE_BFLOAT16, 3, const_cast<void*>(base), dims, strides, box, es, CU_TENSOR_MAP_INTERLEAVE_NONE,
      CU_TENSOR_MAP_SWIZZLE_128B, CU_TENSOR_MAP_L2_PROMOTION_NONE, CU_TENSOR_MAP_FLOAT_OOB_FILL_NONE);
}

}

extern "C" void kernel_launch(void* const* d_in, const int* in_sizes, int n_in, void* d_out, int out_size) {
  (void)in_sizes; (void)n_in; (void)out_size;
  static EncodeTiledFn enc = nullptr;
  static Scratch* scratch = nullptr;
  if (!enc) {
    void* sp = nullptr;
    cudaGetSymbolAddress(&sp, g_s);
    scratch = (Scratch*)(((uintptr_t)sp + 65535) & ~(uintptr_t)65535);
    void* fn = nullptr;
    cudaDriverEntryPointQueryResult q;
    cudaGetDriverEntryPoint("cuTensorMapEncodeTiled", &fn, cudaEnableDefault, &q);
    enc = (EncodeTiledFn)fn;
    cudaFuncSetAttribute(fused_decode_kernel, cudaFuncAttributeMaxDynamicSharedMemorySize, SMEM_BYTES);
  }
  Params P;
  make_map(enc, &P.ckv, d_in[1], 512, 8 * 4096, 64, 64, CU_TENSOR_MAP_SWIZZLE_128B, CU_TENSOR_MAP_L2_PROMOTION_NONE);
  make_map(enc, &P.wq, d_in[2], 4096, 512, 64, 64, CU_TENSOR_MAP_SWIZZLE_128B, CU_TENSOR_MAP_L2_PROMOTION_NONE);
  make_map(enc, &P.wuk, d_in[3], 4096, 512, 64, 64, CU_TENSOR_MAP_SWIZZLE_128B, CU_TENSOR_MAP_L2_PROMOTION_NONE);
  {
    cuuint64_t dims[4] = {4096, 2, 8, 32};
    cuuint64_t strides[3] = {8 * 8192, 8192, 16 * 8192};
    cuuint32_t box[4] = {64, 2, 8, 4};
    cuuint32_t es[4] = {1, 1, 1, 1};
    enc(&P.wuv, CU_TENSOR_MAP_DATA_TYPE_BFLOAT16, 4, d_in[4], dims, strides, box, es, CU_TENSOR_MAP_INTERLEAVE_NONE, CU_TENSOR_MAP_SWIZZLE_128B,
        CU_TENSOR_MAP_L2_PROMOTION_NONE, CU_TENSOR_MAP_FLOAT_OOB_FILL_NONE);
  }
  make_map(enc, &P.wo, d_in[5], 512, 4096, 64, 64, CU_TENSOR_MAP_SWIZZLE_128B, CU_TENSOR_MAP_L2_PROMOTION_NONE);
  make_map(enc, &P.w1, d_in[7], 1792, 512, 2 * FCH, 128, CU_TENSOR_MAP_SWIZZLE_64B, PROMO);
  make_map3(enc, &P.w2, d_in[8], 1792, FCH, 4);
  make_map(enc, &P.wma, d_in[10], 3072, 512, 64, 128, CU_TENSOR_MAP_SWIZZLE_128B, CU_TENSOR_MAP_L2_PROMOTION_NONE);
  make_map(enc, &P.wmod, d_in[10], 3072, 512, 32, 128, CU_TENSOR_MAP_SWIZZLE_64B, PROMO);
  fused_decode_kernel<<<NCTA, NTHREADS, SMEM_BYTES>>>((__nv_bfloat16*)d_out, scratch, (const uint8_t*)d_in[2], (const uint8_t*)d_in[0],
                                                      (const uint8_t*)d_in[9], P);
}
```

```cpp
#include <cuda_runtime.h>
#include <cuda.h>
#include <cuda_bf16.h>
#include <stdint.h>

namespace {

constexpr int NCTA = 128;
constexpr int NTHREADS = 384;
constexpr int FCH = 16;
constexpr int NFF = 1792 / FCH;

constexpr uint32_t SB = 1024;
__host__ __device__ constexpr uint32_t slot(int i) { return SB + i * 8192; }
constexpr uint32_t OFF_R1 = slot(16);
constexpr uint32_t OFF_R2 = slot(20);
constexpr uint32_t OFF_PT = slot(23);
constexpr uint32_t OFF_R0 = slot(24);
constexpr uint32_t OFF_MISC = SB + 229376;
constexpr uint32_t OFF_BARS = OFF_MISC;
constexpr uint32_t OFF_FM = OFF_MISC + 736;
constexpr uint32_t OFF_EPOCH = OFF_MISC + 768;
constexpr uint32_t OFF_TL = OFF_MISC + 784;
constexpr uint32_t OFF_BS = OFF_MISC + 1024;
constexpr uint32_t SMEM_BYTES = 229376 + 3072;
constexpr uint32_t OFF_P0S = OFF_R0 + 24576;
constexpr uint32_t OFF_BS2 = OFF_R0 + 30720;
constexpr uint32_t OFF_RED = OFF_BS;
constexpr uint32_t OFF_ALPHA = OFF_BS + 512;
constexpr uint32_t OFF_MREF = OFF_BS + 640;
constexpr uint32_t OFF_FB = OFF_BS + 1024;
__host__ __device__ constexpr int box_slot(int n) { return n < 23 ? n : n - 23; }
constexpr uint32_t OFF_WUV = slot(1);
constexpr uint32_t OFF_XE = slot(21);
constexpr uint32_t OFF_BS4 = slot(0);
constexpr uint32_t OFF_BS5 = slot(0) + 4096;
constexpr uint32_t OFF_MLS = slot(0) + 4096;
constexpr uint32_t OFF_WM = slot(17);
constexpr uint32_t OFF_WO = slot(5);
constexpr uint32_t OFF_W1 = slot(9);
constexpr uint32_t OFF_W2 = slot(13);
constexpr uint32_t OFF_REDG = OFF_R0;
constexpr uint32_t OFF_REDS = OFF_R0 + 4096;
constexpr uint32_t OFF_REDU = OFF_R0 + 8192;
constexpr uint32_t OFF_REDV = OFF_R0 + 12288;
constexpr uint32_t OFF_H1 = OFF_R0 + 16384;

constexpr int BAR_FULL = 8;
constexpr int U_WQ = -8, U_WUK = -4, U_WMOD = 40, U_WUV = 42, U_WO = 46, U_W1 = 50, U_W2 = 52, NUNITS = 54;
constexpr int BAR_EMPTY = 62;
constexpr int BAR_GO = 67, BAR_CLR = 68, BAR_EPOCH = 69;
constexpr int BAR_P2E = 70, BAR_P5D = 71, BAR_P7D = 72;
constexpr int BAR_XE = 73;
constexpr int BAR_FM = 74;
constexpr int BAR_WA = 75;
__host__ __device__ constexpr uint32_t BAR(int i) { return OFF_BARS + 8 * i; }
#define CPA_N 4
#define PACE_T0 608
#define PACE_DT 320
#define PACE_DTM 320
#define PACE_NM 10
#define PACE_DTE 324
#define PACE_GAP 0
#define PACE_DT2 325
#define D_FIN2 2000
#define PACE_DT3 380
#define PACE_DT4 440
#define PACE_GAP3 220
#define PACE_GAP4 100
#define GA_AT 46
#define PROMO CU_TENSOR_MAP_L2_PROMOTION_NONE
#define NPROBE 3
#define WIN_PRE 5
#define WIN_MID 8
#define WIN_END 6
#define WIN_TAIL 5
#define CLR_CLK 220
#define D_MOD 600
#define MOD_AT 3
#define D_QP 1600
#define D_QX 1400
#define QX_AT 5
#define QK_UNROLL 8
#define PV_SPLIT 3
#define XE_AT 39
#define CNT_AT 27
#define X1_D0 1400
#define D_X2 380
#define D_X3A 400
#define D_X3B 1300
#define D_FIN 450

struct Scratch {
  uint32_t MODA[1024 * 4];
  uint32_t QP[128 * 256 * 2];
  uint32_t MODB[2][2048 * 4];
  uint32_t FL[2][128];
  uint32_t QX[2][8 * 32 * 256];
  uint32_t XE[128 * 64 * 64];
  uint32_t MLE[32 * 128 * 8];
  uint32_t epoch;
  uint32_t pad[31];
  uint32_t cnt;
  alignas(65536) uint32_t X3B[16384];
  uint32_t IN[128][16384];
};
__device__ uint8_t g_s[sizeof(Scratch) + 65536];

#define TL(idx) do {} while (0)
#define TLW(idx) do {} while (0)
#define PROBE_UNITS(a, b) do {} while (0)

struct Params {
  CUtensorMap wma, wq, wuk, wmod, ckv, wuv, wo, w1, w2;
};

__device__ __forceinline__ void mbar_init(uint32_t bar, int cnt) { asm volatile("mbarrier.init.shared::cta.b64 [%0], %1;" ::"r"(bar), "r"(cnt)); }
__device__ __forceinline__ void mbar_expect(uint32_t bar, uint32_t bytes) { asm volatile("mbarrier.arrive.expect_tx.shared::cta.b64 _, [%0], %1;" ::"r"(bar), "r"(bytes) : "memory"); }
__device__ __forceinline__ void mbar_arrive(uint32_t bar) { asm volatile("mbarrier.arrive.shared::cta.b64 _, [%0];" ::"r"(bar) : "memory"); }
__device__ __forceinline__ void mbar_arrive_cluster(uint32_t bar) { asm volatile("mbarrier.arrive.shared::cluster.b64 _, [%0];" ::"r"(bar) : "memory"); }
__device__ __forceinline__ bool mbar_test(uint32_t bar) {
  uint32_t ok;
  asm volatile("{\n.reg .pred p;\nmbarrier.test_wait.parity.shared::cta.b64 p, [%1], 0;\nselp.u32 %0,1,0,p;\n}" : "=r"(ok) : "r"(bar) : "memory");
  return ok;
}
__device__ __forceinline__ uint32_t gtime32() { uint32_t c; asm volatile("mov.u32 %0, %%globaltimer_lo;" : "=r"(c) :: "memory"); return c; }
__device__ __forceinline__ uint32_t clk32() { uint32_t c; asm volatile("{\n.reg .u64 t;\nmov.u64 t, %%clock64;\ncvt.u32.u64 %0, t;\n}" : "=r"(c) :: "memory"); return c; }
__device__ __forceinline__ void wait_until(uint32_t c0, int clocks) { if (clocks > 0) while ((int)(clk32() - c0) < clocks) {} }
__device__ __forceinline__ void backoff(int clocks) { if (clocks > 0) wait_until(clk32(), clocks); }
__device__ __forceinline__ uint32_t pin32(uint32_t p) { asm volatile("" : "+r"(p)); return p; }
template <typename T> __device__ __forceinline__ T* pin(T* p) { asm volatile("" : "+l"(p)); return p; }
__device__ __forceinline__ uint32_t hold32(uint32_t p) { asm volatile("shfl.sync.bfly.b32 %0, %0, 0, 0x1f, 0xffffffff;" : "+r"(p) :: "memory"); return p; }
__device__ __forceinline__ float holdf(float p) { return __uint_as_float(hold32(__float_as_uint(p))); }
template <typename T> __device__ __forceinline__ T* hold(T* p) {
  asm volatile("{\n.reg .b32 a, b;\nmov.b64 {a, b}, %0;\nshfl.sync.bfly.b32 a, a, 0, 0x1f, 0xffffffff;\nshfl.sync.bfly.b32 b, b, 0, 0x1f, 0xffffffff;\nmov.b64 %0, {a, b};\n}" : "+l"(p) :: "memory");
  return p;
}
constexpr int SPIN_LIMIT = 1 << 22;
__device__ __forceinline__ void mbar_wait(uint32_t bar) {
  asm volatile("{\n.reg .pred p;\nMW_LOOP:\nmbarrier.try_wait.parity.shared::cta.b64 p, [%0], 0;\n@!p bra MW_LOOP;\n}" ::"r"(bar) : "memory");
}
__device__ __forceinline__ void mbar_wait_b(uint32_t bar) {
  asm volatile("{\n.reg .pred p;\n.reg .u32 c;\nmov.u32 c, 0;\n"
               "MW_LOOP:\nmbarrier.try_wait.parity.shared::cta.b64 p, [%0], 0;\n@p bra MW_DONE;\n"
               "add.u32 c, c, 1;\nsetp.lt.u32 p, c, 1048576;\n@p bra MW_LOOP;\ntrap;\nMW_DONE:\n}"
               ::"r"(bar) : "memory");
}
__device__ __forceinline__ void tma2d(uint32_t dst, const CUtensorMap* m, int c0, int c1, uint32_t bar, uint64_t pol) {
  asm volatile("cp.async.bulk.tensor.2d.shared::cluster.global.mbarrier::complete_tx::bytes.L2::cache_hint [%0], [%1, {%3,%4}], [%2], %5;"
               ::"r"(dst), "l"(m), "r"(bar), "r"(c0), "r"(c1), "l"(pol) : "memory");
}
__device__ __forceinline__ void tma2d_both(uint32_t dst, const CUtensorMap* m, int c0, int c1, uint32_t bar, uint64_t pol) {
  asm volatile("cp.async.bulk.tensor.2d.shared::cluster.global.mbarrier::complete_tx::bytes.multicast::cluster.L2::cache_hint [%0], [%1, {%3,%4}], [%2], %6, %5;"
               ::"r"(dst), "l"(m), "r"(bar), "r"(c0), "r"(c1), "l"(pol), "h"((uint16_t)3) : "memory");
}
__device__ __forceinline__ void tma3d(uint32_t dst, const CUtensorMap* m, int c0, int c1, int c2, uint32_t bar, uint64_t pol) {
  asm volatile("cp.async.bulk.tensor.3d.shared::cluster.global.mbarrier::complete_tx::bytes.L2::cache_hint [%0], [%1, {%3,%4,%5}], [%2], %6;"
               ::"r"(dst), "l"(m), "r"(bar), "r"(c0), "r"(c1), "r"(c2), "l"(pol) : "memory");
}
__device__ __forceinline__ void tma5d(uint32_t dst, const CUtensorMap* m, int c0, int c3, int c4, uint32_t bar, uint64_t pol) {
  asm volatile("cp.async.bulk.tensor.5d.shared::cluster.global.mbarrier::complete_tx::bytes.L2::cache_hint [%0], [%1, {%3,%7,%7,%4,%5}], [%2], %6;"
               ::"r"(dst), "l"(m), "r"(bar), "r"(c0), "r"(c3), "r"(c4), "l"(pol), "r"(0) : "memory");
}
__device__ __forceinline__ void bulk_load(uint32_t dst, const void* src, uint32_t bytes, uint32_t bar) {
  asm volatile("cp.async.bulk.shared::cluster.global.mbarrier::complete_tx::bytes [%0], [%1], %2, [%3];" ::"r"(dst), "l"(src), "r"(bytes), "r"(bar) : "memory");
}
__device__ __forceinline__ void cbar() { asm volatile("bar.sync 1, 256;" ::: "memory"); }
__device__ __forceinline__ void wg0bar() { asm volatile("bar.sync 2, 128;" ::: "memory"); }
__device__ __forceinline__ bool cbar_or(bool p) {
  uint32_t r;
  asm volatile("{\n.reg .pred p, q;\nsetp.ne.u32 p, %1, 0;\nbarrier.cta.red.or.aligned.pred q, 1, 256, p;\nselp.u32 %0, 1, 0, q;\n}" : "=r"(r) : "r"((uint32_t)p) : "memory");
  return r;
}

__device__ __forceinline__ uint32_t ldg_rlx1(const void* p) { uint32_t v; asm volatile("ld.relaxed.gpu.global.u32 %0, [%1];" : "=r"(v) : "l"(p) : "memory"); return v; }
__device__ __forceinline__ void stg4(void* p, uint4 v) { asm volatile("st.relaxed.gpu.global.v4.u32 [%0], {%1,%2,%3,%4};" ::"l"(p), "r"(v.x), "r"(v.y), "r"(v.z), "r"(v.w) : "memory"); }
__device__ __forceinline__ void stg1(void* p, uint32_t a) { asm volatile("st.relaxed.gpu.global.u32 [%0], %1;" ::"l"(p), "r"(a) : "memory"); }
__device__ __forceinline__ uint32_t nz(uint32_t w) { uint32_t r; asm("max.u32 %0, %1, 1;" : "=r"(r) : "r"(w)); return r; }
__device__ __forceinline__ uint32_t min3(uint32_t a, uint32_t b, uint32_t c) { return min(min(a, b), c); }

__device__ __forceinline__ uint32_t pack_bf16(float lo, float hi) { uint32_t r; asm("cvt.rn.bf16x2.f32 %0, %1, %2;" : "=r"(r) : "f"(hi), "f"(lo)); return r; }
__device__ __forceinline__ float bf_lo(uint32_t w) { return __uint_as_float(w << 16); }
__device__ __forceinline__ float bf_hi(uint32_t w) { return __uint_as_float(w & 0xffff0000u); }
__device__ __forceinline__ float ex2(float x) { float r; asm("ex2.approx.ftz.f32 %0, %1;" : "=f"(r) : "f"(x)); return r; }
__device__ __forceinline__ float rcp(float x) { float r; asm("rcp.approx.ftz.f32 %0, %1;" : "=f"(r) : "f"(x)); return r; }
__device__ __forceinline__ float rsq(float x) { float r; asm("rsqrt.approx.ftz.f32 %0, %1;" : "=f"(r) : "f"(x)); return r; }
__device__ __forceinline__ uint32_t silu2(uint32_t c) {
  const float a = bf_lo(c), b = bf_hi(c);
  return pack_bf16(__fdividef(a, 1.f + __expf(-a)), __fdividef(b, 1.f + __expf(-b)));
}
__device__ __forceinline__ uint32_t shl_clamp(uint32_t x, int s) { uint32_t r; asm("shl.b32 %0, %1, %2;" : "=r"(r) : "r"(x), "r"(s)); return r; }

__device__ __forceinline__ void ldsm4(uint32_t (&r)[4], uint32_t a) { asm volatile("ldmatrix.sync.aligned.m8n8.x4.shared.b16 {%0,%1,%2,%3}, [%4];" : "=r"(r[0]), "=r"(r[1]), "=r"(r[2]), "=r"(r[3]) : "r"(a) : "memory"); }
__device__ __forceinline__ void ldsm4t(uint32_t (&r)[4], uint32_t a) { asm volatile("ldmatrix.sync.aligned.m8n8.x4.trans.shared.b16 {%0,%1,%2,%3}, [%4];" : "=r"(r[0]), "=r"(r[1]), "=r"(r[2]), "=r"(r[3]) : "r"(a) : "memory"); }
__device__ __forceinline__ void ldsm2t(uint32_t& r0, uint32_t& r1, uint32_t a) { asm volatile("ldmatrix.sync.aligned.m8n8.x2.trans.shared.b16 {%0,%1}, [%2];" : "=r"(r0), "=r"(r1) : "r"(a) : "memory"); }
__device__ __forceinline__ void stsm4t(uint32_t a, uint32_t r0, uint32_t r1, uint32_t r2, uint32_t r3) { asm volatile("stmatrix.sync.aligned.m8n8.x4.trans.shared.b16 [%0], {%1,%2,%3,%4};" ::"r"(a), "r"(r0), "r"(r1), "r"(r2), "r"(r3) : "memory"); }
__device__ __forceinline__ void stsm2t(uint32_t a, uint32_t r0, uint32_t r1) { asm volatile("stmatrix.sync.aligned.m8n8.x2.trans.shared.b16 [%0], {%1,%2};" ::"r"(a), "r"(r0), "r"(r1) : "memory"); }
__device__ __forceinline__ void mma16816(float (&d)[4], const uint32_t (&a)[4], uint32_t b0, uint32_t b1) {
  asm volatile("mma.sync.aligned.m16n8k16.row.col.f32.bf16.bf16.f32 {%0,%1,%2,%3}, {%4,%5,%6,%7}, {%8,%9}, {%0,%1,%2,%3};"
               : "+f"(d[0]), "+f"(d[1]), "+f"(d[2]), "+f"(d[3]) : "r"(a[0]), "r"(a[1]), "r"(a[2]), "r"(a[3]), "r"(b0), "r"(b1));
}
__device__ __forceinline__ void mma_v(float (&d)[4], const uint4& a, uint32_t b0, uint32_t b1) {
  asm volatile("mma.sync.aligned.m16n8k16.row.col.f32.bf16.bf16.f32 {%0,%1,%2,%3}, {%4,%5,%6,%7}, {%8,%9}, {%0,%1,%2,%3};"
               : "+f"(d[0]), "+f"(d[1]), "+f"(d[2]), "+f"(d[3]) : "r"(a.x), "r"(a.y), "r"(a.z), "r"(a.w), "r"(b0), "r"(b1));
}
__device__ __forceinline__ void sts1(uint32_t a, uint32_t v) { asm volatile("st.shared.u32 [%0], %1;" ::"r"(a), "r"(v) : "memory"); }
__device__ __forceinline__ void sts2(uint32_t a, uint32_t x, uint32_t y) { asm volatile("st.shared.v2.u32 [%0], {%1,%2};" ::"r"(a), "r"(x), "r"(y) : "memory"); }
__device__ __forceinline__ void sts4(uint32_t a, uint4 v) { asm volatile("st.shared.v4.u32 [%0], {%1,%2,%3,%4};" ::"r"(a), "r"(v.x), "r"(v.y), "r"(v.z), "r"(v.w) : "memory"); }
__device__ __forceinline__ void sts4f(uint32_t a, float x, float y, float z, float w) { asm volatile("st.shared.v4.f32 [%0], {%1,%2,%3,%4};" ::"r"(a), "f"(x), "f"(y), "f"(z), "f"(w) : "memory"); }
__device__ __forceinline__ void sts2f(uint32_t a, float x, float y) { asm volatile("st.shared.v2.f32 [%0], {%1,%2};" ::"r"(a), "f"(x), "f"(y) : "memory"); }
__device__ __forceinline__ void stsf(uint32_t a, float v) { asm volatile("st.shared.f32 [%0], %1;" ::"r"(a), "f"(v) : "memory"); }
__device__ __forceinline__ uint32_t lds1(uint32_t a) { uint32_t v; asm volatile("ld.shared.u32 %0, [%1];" : "=r"(v) : "r"(a) : "memory"); return v; }
__device__ __forceinline__ uint2 lds2(uint32_t a) { uint2 v; asm volatile("ld.shared.v2.u32 {%0,%1}, [%2];" : "=r"(v.x), "=r"(v.y) : "r"(a) : "memory"); return v; }
__device__ __forceinline__ float ldsf(uint32_t a) { float v; asm volatile("ld.shared.f32 %0, [%1];" : "=f"(v) : "r"(a) : "memory"); return v; }
__device__ __forceinline__ float2 ldsf2(uint32_t a) { float2 v; asm volatile("ld.shared.v2.f32 {%0,%1}, [%2];" : "=f"(v.x), "=f"(v.y) : "r"(a) : "memory"); return v; }
__device__ __forceinline__ float4 ldsf4(uint32_t a) { float4 v; asm volatile("ld.shared.v4.f32 {%0,%1,%2,%3}, [%4];" : "=f"(v.x), "=f"(v.y), "=f"(v.z), "=f"(v.w) : "r"(a) : "memory"); return v; }
__device__ __forceinline__ uint4 lds4(uint32_t a) { uint4 v; asm volatile("ld.shared.v4.u32 {%0,%1,%2,%3}, [%4];" : "=r"(v.x), "=r"(v.y), "=r"(v.z), "=r"(v.w) : "r"(a) : "memory"); return v; }

__device__ __forceinline__ void wg_fence() { asm volatile("wgmma.fence.sync.aligned;" ::: "memory"); }
__device__ __forceinline__ void wg_commit() { asm volatile("wgmma.commit_group.sync.aligned;" ::: "memory"); }
template <int N> __device__ __forceinline__ void wg_wait() { asm volatile("wgmma.wait_group.sync.aligned %0;" ::"n"(N) : "memory"); }
__host__ __device__ constexpr uint32_t dlo(uint32_t addr) { return (addr >> 4) | 0x10000u; }
constexpr uint32_t ONE2 = 0x3f803f80u;
template <int TA, int ACC> __device__ __forceinline__ void wgmma_ss(float (&d)[16], uint32_t da, uint32_t db) {
  asm volatile("{\n.reg .b64 da, db;\nmov.b64 da, {%16, 0x40000040};\nmov.b64 db, {%17, 0x40000040};\n"
               "wgmma.mma_async.sync.aligned.m64n32k16.f32.bf16.bf16 {%0,%1,%2,%3,%4,%5,%6,%7,%8,%9,%10,%11,%12,%13,%14,%15}, da, db, %18, 1, 1, %19, 0;\n}"
               : "+f"(d[0]), "+f"(d[1]), "+f"(d[2]), "+f"(d[3]), "+f"(d[4]), "+f"(d[5]), "+f"(d[6]), "+f"(d[7]),
                 "+f"(d[8]), "+f"(d[9]), "+f"(d[10]), "+f"(d[11]), "+f"(d[12]), "+f"(d[13]), "+f"(d[14]), "+f"(d[15])
               : "r"(da), "r"(db), "n"(ACC), "n"(TA));
}
template <int TA, int ACC> __device__ __forceinline__ void wgmma_ss(float (&d)[8], uint32_t da, uint32_t db) {
  asm volatile("{\n.reg .b64 da, db;\nmov.b64 da, {%8, 0x40000040};\nmov.b64 db, {%9, 0x40000040};\n"
               "wgmma.mma_async.sync.aligned.m64n16k16.f32.bf16.bf16 {%0,%1,%2,%3,%4,%5,%6,%7}, da, db, %10, 1, 1, %11, 0;\n}"
               : "+f"(d[0]), "+f"(d[1]), "+f"(d[2]), "+f"(d[3]), "+f"(d[4]), "+f"(d[5]), "+f"(d[6]), "+f"(d[7])
               : "r"(da), "r"(db), "n"(ACC), "n"(TA));
}
__device__ __forceinline__ void wgmma_n8(float (&d)[4], uint32_t da, uint32_t db) {
  asm volatile("{\n.reg .b64 da, db;\nmov.b64 da, {%4, 0x40000040};\nmov.b64 db, {%5, 0x40000040};\n"
               "wgmma.mma_async.sync.aligned.m64n8k16.f32.bf16.bf16 {%0,%1,%2,%3}, da, db, 1, 1, 1, 1, 0;\n}"
               : "+f"(d[0]), "+f"(d[1]), "+f"(d[2]), "+f"(d[3]) : "r"(da), "r"(db));
}
__device__ __forceinline__ void wgmma_ss_p(float (&d)[16], uint32_t da, uint32_t db, int acc) {
  asm volatile("{\n.reg .pred p;\n.reg .b64 da, db;\nsetp.ne.b32 p, %18, 0;\nmov.b64 da, {%16, 0x40000040};\nmov.b64 db, {%17, 0x40000040};\n"
               "wgmma.mma_async.sync.aligned.m64n32k16.f32.bf16.bf16 {%0,%1,%2,%3,%4,%5,%6,%7,%8,%9,%10,%11,%12,%13,%14,%15}, da, db, p, 1, 1, 0, 0;\n}"
               : "+f"(d[0]), "+f"(d[1]), "+f"(d[2]), "+f"(d[3]), "+f"(d[4]), "+f"(d[5]), "+f"(d[6]), "+f"(d[7]),
                 "+f"(d[8]), "+f"(d[9]), "+f"(d[10]), "+f"(d[11]), "+f"(d[12]), "+f"(d[13]), "+f"(d[14]), "+f"(d[15])
               : "r"(da), "r"(db), "r"(acc));
}
__device__ __forceinline__ void wgmma_ss_p(float (&d)[8], uint32_t da, uint32_t db, int acc) {
  asm volatile("{\n.reg .pred p;\n.reg .b64 da, db;\nsetp.ne.b32 p, %10, 0;\nmov.b64 da, {%8, 0x40000040};\nmov.b64 db, {%9, 0x40000040};\n"
               "wgmma.mma_async.sync.aligned.m64n16k16.f32.bf16.bf16 {%0,%1,%2,%3,%4,%5,%6,%7}, da, db, p, 1, 1, 0, 0;\n}"
               : "+f"(d[0]), "+f"(d[1]), "+f"(d[2]), "+f"(d[3]), "+f"(d[4]), "+f"(d[5]), "+f"(d[6]), "+f"(d[7])
               : "r"(da), "r"(db), "r"(acc));
}
template <int K> __device__ __forceinline__ void tie(float (&d)[K]) {
#pragma unroll
  for (int i = 0; i < K; i += 8)
    asm volatile("" : "+f"(d[i]), "+f"(d[i + 1]), "+f"(d[i + 2]), "+f"(d[i + 3]), "+f"(d[i + 4]), "+f"(d[i + 5]), "+f"(d[i + 6]), "+f"(d[i + 7]) :: "memory");
}
template <bool C, typename A, typename B> __device__ __forceinline__ auto& pick(A& a, B& b) { if constexpr (C) return a; else return b; }
__device__ __forceinline__ void tie(uint4& v) { asm volatile("" : "+r"(v.x), "+r"(v.y), "+r"(v.z), "+r"(v.w) :: "memory"); }
__device__ __forceinline__ void tie(uint2& v) { asm volatile("" : "+r"(v.x), "+r"(v.y) :: "memory"); }
#define PRAGMA(x) _Pragma(#x)
#define UNROLL(n) PRAGMA(unroll n)
template <int I> struct IC { static constexpr int value = I; };
template <int B, int E, typename F> __device__ __forceinline__ void sfor(F&& f) { if constexpr (B < E) { f(IC<B>{}); sfor<B + 1, E>(f); } }

__device__ __forceinline__ uint2 ldg_u64(const void* p) {
  uint2 v; asm volatile("{\n.reg .b64 a;\nld.relaxed.gpu.global.b64 a, [%2];\nmov.b64 {%0,%1}, a;\n}" : "=r"(v.x), "=r"(v.y) : "l"(p) : "memory"); return v;
}
__device__ __forceinline__ uint4 ldg_2u64(const void* p) {
  uint4 v; asm volatile("{\n.reg .b64 a, b;\nld.relaxed.gpu.global.v2.b64 {a, b}, [%4];\nmov.b64 {%0,%1}, a;\nmov.b64 {%2,%3}, b;\n}" : "=r"(v.x), "=r"(v.y), "=r"(v.z), "=r"(v.w) : "l"(p) : "memory"); return v;
}
__device__ __forceinline__ uint4 ldg_u128(const void* p) {
  uint4 v; asm volatile("{\n.reg .b64 a, b;\n.reg .b128 q;\nld.relaxed.gpu.global.b128 q, [%4];\nmov.b128 {a, b}, q;\nmov.b64 {%0,%1}, a;\nmov.b64 {%2,%3}, b;\n}" : "=r"(v.x), "=r"(v.y), "=r"(v.z), "=r"(v.w) : "l"(p) : "memory"); return v;
}
__device__ __forceinline__ void stg_u64(void* p, uint32_t x, uint32_t y) {
  asm volatile("{\n.reg .b64 a;\nmov.b64 a, {%1,%2};\nst.relaxed.gpu.global.b64 [%0], a;\n}" ::"l"(p), "r"(x), "r"(nz(y)) : "memory");
}
__device__ __forceinline__ uint64_t pair64(uint32_t x, uint32_t y) { uint64_t a; asm("mov.b64 %0, {%1,%2};" : "=l"(a) : "r"(x), "r"(y)); return a; }
__device__ __forceinline__ void stg_b64(void* p, uint64_t a) { asm volatile("st.relaxed.gpu.global.b64 [%0], %1;" ::"l"(p), "l"(a) : "memory"); }
__device__ __forceinline__ void stg4_b128(void* p, uint4 v) {
  asm volatile("{\n.reg .b64 a, b;\n.reg .b128 q;\nmov.b64 a, {%1,%2};\nmov.b64 b, {%3,%4};\nmov.b128 q, {a, b};\nst.relaxed.gpu.global.b128 [%0], q;\n}" ::"l"(p), "r"(v.x), "r"(v.y), "r"(v.z), "r"(v.w) : "memory");
}
__device__ __forceinline__ void stg_u128(void* p, uint4 v) {
  asm volatile("{\n.reg .b64 a, b;\n.reg .b128 q;\nmov.b64 a, {%1,%2};\nmov.b64 b, {%3,%4};\nmov.b128 q, {a, b};\nst.relaxed.gpu.global.b128 [%0], q;\n}" ::"l"(p), "r"(v.x), "r"(v.y), "r"(v.z), "r"(nz(v.w)) : "memory");
}
__device__ __forceinline__ uint32_t hmul2(uint32_t a, uint32_t b) { uint32_t r; asm("mul.rn.bf16x2 %0, %1, %2;" : "=r"(r) : "r"(a), "r"(b)); return r; }
__device__ __forceinline__ uint32_t hadd2(uint32_t a, uint32_t b) { uint32_t r; asm("add.rn.bf16x2 %0, %1, %2;" : "=r"(r) : "r"(a), "r"(b)); return r; }
__device__ __forceinline__ uint32_t hfma2(uint32_t a, uint32_t b, uint32_t c) { uint32_t r; asm("fma.rn.bf16x2 %0, %1, %2, %3;" : "=r"(r) : "r"(a), "r"(b), "r"(c)); return r; }
__device__ __forceinline__ uint32_t movm(uint32_t a) { uint32_t d; asm volatile("movmatrix.sync.aligned.m8n8.trans.b16 %0, %1;" : "=r"(d) : "r"(a)); return d; }
__device__ __forceinline__ uint2 ldg_rlx2(const void* p) { uint2 v; asm volatile("ld.relaxed.gpu.global.v2.u32 {%0,%1}, [%2];" : "=r"(v.x), "=r"(v.y) : "l"(p) : "memory"); return v; }
__device__ __forceinline__ uint4 ldg_in4(const void* p) { uint4 v; asm volatile("ld.global.nc.v4.u32 {%0,%1,%2,%3}, [%4];" : "=r"(v.x), "=r"(v.y), "=r"(v.z), "=r"(v.w) : "l"(p) : "memory"); return v; }
__device__ __forceinline__ uint32_t ldg_in1(const void* p) { uint32_t v; asm volatile("ld.global.nc.u32 %0, [%1];" : "=r"(v) : "l"(p)); return v; }
__device__ __forceinline__ uint32_t ldg_inh(const void* p) { uint16_t v; asm volatile("ld.global.nc.u16 %0, [%1];" : "=h"(v) : "l"(p) : "memory"); return v; }

template <typename F> __device__ __forceinline__ void sum4_to_smem(uint2 (&v)[4], const uint32_t* x, const uint32_t* y, uint32_t dst, F&& meanwhile) {
  uint32_t r0, r1;
#pragma unroll 1
  while (true) {
    meanwhile();
#pragma unroll
    for (int i = 0; i < 4; i++) tie(v[i]);
    const bool ok = __all_sync(~0u, min(min3(v[0].y, v[1].y, v[2].y), v[3].y) != 0);
    r0 = pack_bf16((bf_lo(v[0].x) + bf_lo(v[1].x)) + (bf_lo(v[2].x) + bf_lo(v[3].x)), (bf_hi(v[0].x) + bf_hi(v[1].x)) + (bf_hi(v[2].x) + bf_hi(v[3].x)));
    r1 = pack_bf16((bf_lo(v[0].y) + bf_lo(v[1].y)) + (bf_lo(v[2].y) + bf_lo(v[3].y)), (bf_hi(v[0].y) + bf_hi(v[1].y)) + (bf_hi(v[2].y) + bf_hi(v[3].y)));
    sts1(dst, r0);
    sts1(dst + 128, r1);
    if (ok) break;
#pragma unroll
    for (int i = 0; i < 4; i++) v[i] = ldg_u64(((i & 2) ? y : x) + (i & 1) * 512);
  }
}
__device__ __forceinline__ void load_a_t(uint32_t (&a)[8][4], uint32_t box, int wq, int lane) {
  const int mi = lane >> 3, r = lane & 7;
  const uint32_t base = box + (8 * (mi >> 1) + r) * 128 + (((2 * wq + (mi & 1)) ^ r) << 4);
#pragma unroll
  for (int ks = 0; ks < 8; ks++) ldsm4t(a[ks], base + ks * 2048);
}
__device__ __forceinline__ void mma128(float (&d)[4], const uint32_t (&a)[8][4], uint32_t bs) {
  float e[4][4] = {{0.f, 0.f, 0.f, 0.f}, {0.f, 0.f, 0.f, 0.f}, {0.f, 0.f, 0.f, 0.f}, {0.f, 0.f, 0.f, 0.f}};
  uint32_t b[4][4];
#pragma unroll
  for (int kk = 0; kk < 4; kk++) ldsm4t(b[kk], bs + 32 * kk * 16);
#pragma unroll
  for (int kk = 0; kk < 4; kk++) { mma16816(e[(2 * kk) & 3], a[2 * kk], b[kk][0], b[kk][1]); mma16816(e[(2 * kk + 1) & 3], a[2 * kk + 1], b[kk][2], b[kk][3]); }
#pragma unroll
  for (int i = 0; i < 4; i++) d[i] = (e[0][i] + e[1][i]) + (e[2][i] + e[3][i]);
}
template <int NL, typename F> __device__ __forceinline__ void poll_vectors(const uint32_t* p, const uint32_t* q, F&& f) {
  int it = 0;
  bool ok;
  uint4 v[NL];
#pragma unroll
  for (int i = 0; i < NL; i++) v[i] = make_uint4(0, 0, 0, 0);
#pragma unroll 1
  do {
    if (++it > SPIN_LIMIT) __trap();
#pragma unroll
    for (int i = 0; i < NL; i++) if (NL <= 4 || min(v[i].y, v[i].w) == 0) v[i] = ldg_2u64(i < NL / 2 ? p + i * 128 : q + (i - NL / 2) * 128);
    f(v);
    uint32_t m0 = min(v[0].y, v[0].w), m1 = min(v[1].y, v[1].w);
#pragma unroll
    for (int i = 2; i < NL; i += 2) { m0 = min3(m0, v[i].y, v[i].w); m1 = min3(m1, v[i + 1].y, v[i + 1].w); }
    ok = __all_sync(~0u, min(m0, m1) != 0);
  } while (!ok);
}

__global__ void __cluster_dims__(2, 1, 1) __launch_bounds__(NTHREADS, 1)
fused_decode_kernel(__nv_bfloat16* __restrict__ gout, Scratch* __restrict__ gs, const uint8_t* __restrict__ gwq,
                    const uint8_t* __restrict__ gx, const uint8_t* __restrict__ gc,
                    const __grid_constant__ Params P) {
  extern __shared__ __align__(1024) uint8_t smem_raw[];
  const uint32_t hi = pin32((uint32_t)__cvta_generic_to_shared(smem_raw) - SB);
  const int tid = threadIdx.x, lane = tid & 31;
  const int w = __shfl_sync(0xffffffffu, tid >> 5, 0);
  const int cta = blockIdx.x;
  const int g = lane >> 2, t = lane & 3;
  const int hI = cta >> 2, jI = cta & 3;
  const int bI = cta >> 4, pI = (cta >> 1) & 7, rI = cta & 1;

  uint32_t epoch0 = 0;
  if (tid == 320) epoch0 = ldg_rlx1(&gs->epoch);
  const bool p0a = (cta & 7) == 0;
  uint4 cw0, cw1, xr0, xr1;
  uint32_t xc;
  if (w < 8) {
    const uint8_t* src = gwq + (size_t)(128 * jI + (tid >> 4)) * 8192 + hI * 256 + (tid & 15) * 16;
    const uint32_t dst = hi + OFF_R1 + ((tid >> 3) & 1) * 16384 + (tid >> 4) * 128 + (((tid ^ (tid >> 4)) & 7) << 4);
    if (p0a) {
      cw0 = ldg_in4(gc + g * 1024 + w * 128 + t * 32); cw1 = ldg_in4(gc + g * 1024 + w * 128 + t * 32 + 16);
      xr0 = ldg_in4(gx + w * 1024 + lane * 16); xr1 = ldg_in4(gx + w * 1024 + 512 + lane * 16);
      xc = ldg_in1(gx + w * 1024 + (cta & 63) * 16 + lane * 4);
    } else {
#pragma unroll
      for (int i = 0; i < CPA_N; i++) asm volatile("cp.async.cg.shared.global [%0], [%1], 16;" ::"r"(dst + i * 2048), "l"(src + i * 16 * 8192) : "memory");
    }
  }
  auto half_of = [&](int c, int k) { return ((lds1(hi + OFF_FM + (c >> 5) * 4) >> (c & 31)) ^ k) & 1; };
  auto inbox = [&](int c, int k, uint32_t bits, int pos, int off) { return gs->IN[0] + (uint32_t)(c * 16384 + k * 2048 + off + (((bits >> pos) & 1) << 10)); };
  auto front_unit = [&](int k, uint64_t pol) {
    tma2d(hi + OFF_R1 + ((k & 4) + 2 * (k & 1) + ((k >> 1) & 1)) * 8192, k < 4 ? &P.wq : &P.wuk, 128 * hI + 64 * (k & 1), 128 * jI + 64 * ((k >> 1) & 1), hi + BAR(k), pol);
  };
  uint32_t tnext = 0;
  if (tid == 256) {
    tnext = gtime32() + PACE_T0;
    if (hi & 0xffffff) __trap();
    if (p0a) {
#pragma unroll
      for (int i = 0; i < 4; i++) mbar_init(hi + BAR(BAR_WA + i), 1);
      asm volatile("fence.mbarrier_init.release.cluster;" ::: "memory");
      uint64_t pol; asm volatile("createpolicy.fractional.L2::evict_first.b64 %0, 1.0;" : "=l"(pol));
#pragma unroll
      for (int i = 0; i < 4; i++) tma2d(hi + slot(8 + 2 * i), &P.wma, 8 * cta, 128 * i, hi + BAR(BAR_WA + i), pol);
    }
    asm volatile("prefetch.tensormap [%0];" ::"l"(&P.wq) : "memory");
    TLW(42);
  } else if (tid == 288) {
#pragma unroll
    for (int i = 0; i < BAR_WA; i++)
      mbar_init(hi + BAR(i), (i >= BAR_EMPTY && i < BAR_EMPTY + 5) ? 16 : (i >= BAR_P2E && i <= BAR_P7D) ? 8 : 1);
    asm volatile("fence.mbarrier_init.release.cluster;" ::: "memory");
  }
  __syncthreads();
  TL(0);

  if (w == 8) {
    auto twice = [](int n) { return (n & ~1) == U_W1 || (n & ~1) == U_WMOD; };
    if (p0a && lane < 4) mbar_expect(hi + BAR(BAR_WA) + 8 * lane, 16384);
    mbar_expect(hi + BAR(0) + 8 * lane, (lane < CPA_N / 2 && !p0a) ? 0 : 8192);
    if (p0a) tnext -= (CPA_N / 2) * PACE_DT;
    if (lane < BAR_EMPTY - 32) mbar_expect(hi + BAR(32) + 8 * lane, twice(32 + lane - BAR_FULL) ? 16384 : 8192);
    __syncwarp();
    const int h = hI, j = jI;
    if (lane == 0) {
      uint64_t pol; asm volatile("createpolicy.fractional.L2::evict_first.b64 %0, 1.0;" : "=l"(pol));
      auto pace = [&](int dt) { if (PACE_DT > 0) { while ((int)(gtime32() - tnext) < 0) {} tnext += dt; } };
      asm volatile("prefetch.tensormap [%0];" ::"l"(&P.wuk) : "memory");
      asm volatile("prefetch.tensormap [%0];" ::"l"(&P.wmod) : "memory");
      asm volatile("prefetch.tensormap [%0];" ::"l"(&P.ckv) : "memory");
#pragma unroll 1
      for (int k = p0a ? 0 : CPA_N / 2; k < 8; k++) { if (k >= WIN_PRE) mbar_wait(hi + BAR(0) + 8 * (k - WIN_PRE)); pace(PACE_DT); front_unit(k, pol); }
      bool go = false;
      const int row0 = bI * 4096 + (cta & 15) * 64;
#pragma unroll 1
      for (int n = 0; n < 24; n++) {
        if (n == 8) mbar_wait(hi + BAR(BAR_P2E));
        if (n == 23) mbar_wait(hi + BAR(BAR_EMPTY));
        if (!go) go = mbar_test(hi + BAR(BAR_GO));
        mbar_wait(hi + BAR(BAR_FULL) + 8 * (n - (go ? WIN_MID : WIN_PRE)));
        pace(n >= PACE_NM ? PACE_DTM : PACE_DT);
        tma2d(hi + slot(box_slot(n)), &P.ckv, (n & 7) * 64, row0 + (n >> 3) * 1024, hi + BAR(BAR_FULL) + 8 * n, pol);
      }
      asm volatile("prefetch.tensormap [%0];" ::"l"(&P.wuv) : "memory");
      asm volatile("prefetch.tensormap [%0];" ::"l"(&P.wo) : "memory");
      asm volatile("prefetch.tensormap [%0];" ::"l"(&P.w1) : "memory");
      asm volatile("prefetch.tensormap [%0];" ::"l"(&P.w2) : "memory");
      const int row1 = bI * 4096 + (24 + pI) * 64;
      tnext += rI * (PACE_DT / 2) - PACE_DT / 4;
#pragma unroll 1
      for (int n = 24 + rI; n < 40; n += 2) {
        const int c = n - 23;
        const int m = c >= 2 * WIN_END ? n - 2 * WIN_END : 23 - (2 * WIN_END - c) / 2;
        mbar_wait(hi + BAR(BAR_FULL) + 8 * m);
        mbar_wait(hi + BAR(BAR_EMPTY) + (c & ~7));
        pace(PACE_DTE);
        tma2d_both(hi + slot(c), &P.ckv, (n & 7) * 64, row1 + (n >> 3) * 512, hi + BAR(BAR_FULL) + 8 * n, pol);
      }
      mbar_wait(hi + BAR(BAR_EMPTY + 2));
      tnext += PACE_GAP;
#pragma unroll 1
      for (int n = U_WMOD; n < (cta < NFF ? NUNITS : U_W1); n++) {
        const int c = n - 39, u = n & 1;
        mbar_wait(hi + BAR(BAR_FULL) + 8 * (c >= WIN_TAIL ? n - WIN_TAIL : 39 - 2 * (WIN_TAIL - c)));
        if (n == U_WUV) mbar_wait(hi + BAR(BAR_EMPTY + 3));
        if (n == U_WO) tnext += PACE_GAP3;
        if (n == U_W1) { mbar_wait(hi + BAR(BAR_EMPTY + 4)); tnext += PACE_GAP4; }
        const uint32_t bar = hi + BAR(BAR_FULL) + 8 * n;
        pace(n < U_WO ? PACE_DT2 : n < U_W1 ? PACE_DT3 : PACE_DT4);
        if (twice(n)) tma2d_both(hi + (n < U_WO ? OFF_WM : OFF_W1) + (2 * u + rI) * 8192, n < U_WO ? &P.wmod : &P.w1, (n < U_WO ? 1024 : 0) + 16 * (cta & ~1), 256 * u + 128 * rI, bar, pol);
        else if (n < U_WO) tma5d(hi + slot(n - 41), &P.wuv, 128 * h + 64 * u, (n - U_WUV) & 2, 2 * j, bar, pol);
        else if (n < U_W1) tma2d(hi + slot(n - 41), &P.wo, 128 * j + 64 * u, 128 * h + 32 * ((n - U_WO) & 2), bar, pol);
        else tma3d(hi + OFF_W2 + u * 8192, &P.w2, 0, FCH * cta, 4 * u, bar, pol);
      }
    }
    return;
  }

  if (w == 11) {
    const uint4 z = make_uint4(0, 0, 0, 0);
    uint32_t f = 0, f2 = 0;
    {
      uint32_t* const p = ((lane & 2) ? gs->X3B + 4 * 2048 + cta * 8 : gs->IN[cta] + 4 * 2048 + 960) + ((lane & 1) << 10);
      if (lane < 8) stg4(p + (lane & 4), z);
      __syncwarp();
      uint32_t best = ~0u;
#pragma unroll 1
      for (int i = 0; i < 4 * NPROBE + (int)(hi & 1); i++) {
        uint32_t v = 0;
        const uint32_t c0 = clk32();
        if (lane == (i & 3)) asm volatile("atom.relaxed.gpu.global.exch.b32 %0, [%1], %2;" : "=r"(v) : "l"(p), "r"(i) : "memory");
        v = __shfl_sync(~0u, v, i & 3);
        const uint32_t dt = clk32() - c0 + (v >> 31);
        if (lane == (i & 3)) best = min(best, dt);
      }
      const uint32_t m = __ballot_sync(~0u, best < __shfl_xor_sync(~0u, best, 1));
      f = (m >> 1) & 1; f2 = (m >> 3) & 1;
    }
    mbar_wait(hi + BAR(BAR_EPOCH));
    const uint32_t epoch = lds1(hi + OFF_EPOCH);
    const int par = epoch & 1;
    if (lane == 0) stg1(gs->FL[par] + cta, 1 + f);
    TLW(51);
    mbar_wait(hi + BAR(BAR_P2E));
#pragma unroll 1
    for (int i = 0; i < 16; i++) {
      const uint32_t c0 = clk32();
      uint32_t* p = gs->IN[cta] + (i >> 1) * 2048 + (((f ^ (i >> 1)) & 1) << 10) + (i & 1) * 512 + lane * 4;
#pragma unroll
      for (int q = 0; q < 4; q++) stg4(p + q * 128, z);
      if (i == 0 && lane < 16) stg4(gs->X3B + cta * 64 + lane * 4, z);
      wait_until(c0, CLR_CLK);
    }
    TLW(35);
    {
      uint32_t u[4];
      do {
#pragma unroll
        for (int i = 0; i < 4; i++) u[i] = ldg_rlx1(gs->FL[par] + 32 * i + lane);
      } while (!__all_sync(~0u, min(min(u[0], u[1]), min(u[2], u[3])) != 0));
      const uint4 m = make_uint4(__ballot_sync(~0u, u[0] == 2), __ballot_sync(~0u, u[1] == 2), __ballot_sync(~0u, u[2] == 2), __ballot_sync(~0u, u[3] == 2));
      if (lane == 0) sts4(hi + OFF_FM, m);
      __syncwarp();
      const uint2 m2 = lds2(hi + OFF_FM + 8 * rI);
      const uint32_t mh = (lds1(hi + OFF_FM + (hI >> 3) * 4) >> (4 * (hI & 7))) & 15;
#pragma unroll 1
      for (int v = 0; v < 8; v++) {
        const int sh = 8 * t + 2 * (v >> 2) + (bI >> 2);
        uint32_t fb = (((m2.x >> sh) & 0x11) | (((m2.y >> sh) & 0x11) << 1)) ^ ((bI & 1) ? 0x33 : 0);
        fb |= mh << 8;
        fb |= half_of(4 * (8 * jI + v) + (g >> 1), 0) << 12;
        fb |= half_of((16 * rI + 4 * (v & 3) + (lane >> 3)) * 4 + (lane & 2), 0) << 13;
        fb |= ((f2 ^ (v >> 2)) & 1) << 14;
        fb |= (((lds1(hi + OFF_FM + (v >> 1) * 4) >> (16 * (v & 1) + (g >> 1))) & 0x1111) ^ (cta >= 56 ? 0x1111 : 0)) << 16;
        sts1(hi + OFF_FB + (v * 32 + lane) * 4, fb);
      }
      __syncwarp();
      if (lane == 0) mbar_arrive(hi + BAR(BAR_FM));
    }
    asm volatile("fence.acq_rel.gpu;" ::: "memory");
    __syncwarp();
    if (lane == 0) asm volatile("red.relaxed.gpu.global.add.u32 [%0], 1;" ::"l"(&gs->cnt) : "memory");
    TLW(36);
    mbar_wait(hi + BAR(BAR_GO));
    if (lane == 0) stg1(gs->FL[par ^ 1] + cta, 0u);
#pragma unroll
    for (int i = 0; i < 4; i++) stg4(gs->QP + cta * 512 + (i * 32 + lane) * 4, z);
#pragma unroll
    for (int i = 0; i < 4; i++) stg4(gs->QX[par ^ 1] + cta * 512 + (i * 32 + lane) * 4, z);
    if (lane < 8) stg4(gs->MODA + cta * 32 + lane * 4, z);
    if (lane < 16) stg4(gs->MODB[par ^ 1] + cta * 64 + lane * 4, z);
    mbar_wait(hi + BAR(BAR_FULL + CNT_AT));
    while ((int)(ldg_rlx1(&gs->cnt) - (epoch + 1) * NCTA) < 0) __nanosleep(100);
    if (lane == 0) mbar_arrive(hi + BAR(BAR_CLR));
    TLW(54);
    return;
  }
  if (w == 10) {
    const int m0 = 16 * hI + 2 * jI;
    const int bo = lane & 7;
    const uint32_t epoch = __shfl_sync(~0u, epoch0, 0);
    if (lane == 0) { sts1(hi + OFF_EPOCH, epoch); mbar_arrive(hi + BAR(BAR_EPOCH)); }
    const int par = epoch & 1;
    const uint32_t* MOD = gs->MODB[par];
    PROBE_UNITS(-8, 16);
    PROBE_UNITS(16, GA_AT + 1);
    mbar_wait_b(hi + BAR(BAR_FULL + GA_AT));
    const uint32_t xw0 = ldg_in1(gx + bo * 1024 + m0 * 2), xw1 = ldg_in1(gx + bo * 1024 + m0 * 2 + 16);
    const int mf = m0 + ((g >> 1) & 1) + 8 * (t >> 1), bf = 2 * (g & 1) + (t & 1);
    float ga[4];
    uint32_t gb2;
    {
      uint32_t u[4];
      int it = 0;
      while (true) {
#pragma unroll
        for (int i = 0; i < 4; i++) u[i] = ldg_rlx1(MOD + (m0 + (i & 1) + 8 * (i >> 1)) * 4 + (bo >> 1));
        gb2 = ldg_rlx1(MOD + (1536 + mf) * 4 + bf);
        if (min3(min3(u[0], u[1], u[2]), u[3], gb2) != 0) break;
        if (++it > SPIN_LIMIT) __trap();
      }
#pragma unroll
      for (int i = 0; i < 4; i++) ga[i] = (bo & 1) ? bf_hi(u[i]) : bf_lo(u[i]);
    }
    uint32_t x2a, x2b;
    mbar_wait_b(hi + BAR(BAR_FM));
    const uint32_t fo_ = half_of(cta, 0);
    {
      const uint32_t* const pi = hold(inbox(cta, 6, fo_, 0, (4 * (g >> 1) + t) * 8 + (g & 1) * 4));
      uint32_t* const po = hold(gs->X3B + (g >> 2) * 4096 + (cta >> 6) * 2048 + ((g >> 1) & 1) * 1024 + (cta & 63) * 16 + bo * 2);
      const uint32_t one = 0x3f80u << (8 * (g & 2)), s0 = g < 4 ? one : 0u, s1 = g < 4 ? 0u : one;
      const uint32_t e0 = hold32((g & 1) ? 0u : s0), e1 = hold32((g & 1) ? 0u : s1), o0 = hold32((g & 1) ? s0 : 0u), o1 = hold32((g & 1) ? s1 : 0u);
      const float xf[4] = {holdf(bf_lo(xw0)), holdf(bf_hi(xw0)), holdf(bf_lo(xw1)), holdf(bf_hi(xw1))};
#pragma unroll
      for (int i = 0; i < 4; i++) ga[i] = holdf(ga[i]);
      PROBE_UNITS(GA_AT + 1, 50);
      mbar_wait_b(hi + BAR(BAR_P5D));
      backoff(D_X3A);
      float d[4][4];
      poll_vectors<4>(pi, pi + 256, [&](const uint4 (&v)[4]) {
#pragma unroll
        for (int i = 0; i < 4; i++) { d[i][0] = d[i][1] = d[i][2] = d[i][3] = 0.f; mma_v(d[i], v[i], (i & 2) ? o0 : e0, (i & 2) ? o1 : e1); }
      });
      TLW(37);
      float s[4] = {d[0][0] + d[1][0], d[2][1] + d[3][1], d[0][2] + d[1][2], d[2][3] + d[3][3]};
#pragma unroll
      for (int i = 0; i < 4; i++) s[i] += __shfl_xor_sync(~0u, s[i], 8);
#pragma unroll
      for (int i = 0; i < 4; i++) s[i] += __shfl_xor_sync(~0u, s[i], 16);
      x2a = pack_bf16(xf[0] + ga[0] * s[0], xf[1] + ga[1] * s[1]);
      x2b = pack_bf16(xf[2] + ga[2] * s[2], xf[3] + ga[3] * s[3]);
      stg_u64(po, x2a, x2b);
      mbar_wait(hi + BAR(BAR_P5D));
    }
    TLW(20);
    {
      const uint32_t a0 = __shfl_sync(~0u, x2a, 2 * bf), a1 = __shfl_sync(~0u, x2a, 2 * bf + 1);
      const uint32_t b0 = __shfl_sync(~0u, x2b, 2 * bf), b1 = __shfl_sync(~0u, x2b, 2 * bf + 1);
      const uint32_t y0 = (t & 2) ? b0 : a0, y1 = (t & 2) ? b1 : a1;
      const float r0 = holdf((g & 2) ? bf_hi(y0) : bf_lo(y0)), r1 = holdf((g & 2) ? bf_hi(y1) : bf_lo(y1)), gb0 = holdf(bf_lo(gb2)), gb1 = holdf(bf_hi(gb2));
      const uint32_t* const pi = hold(inbox(cta, 4, fo_, 0, (4 * (g >> 2) + t) * 16 + (g & 3) * 4));
      const uint32_t* const pj = hold(inbox(cta, 5, ~fo_, 0, (4 * (g >> 2) + t) * 16 + (g & 3) * 4));
      __nv_bfloat16* const fo = hold(gout + (2 * bf) * 512 + mf);
      const uint32_t one = (g & 1) ? 0x3f800000u : 0x00003f80u;
      const uint32_t s0 = hold32((g & 2) ? 0u : one), s1 = hold32((g & 2) ? one : 0u);
      if (cta < NFF) { mbar_wait_b(hi + BAR(BAR_P7D)); backoff(D_FIN); } else backoff(D_FIN2);
      float d[4][4];
      poll_vectors<NFF / 8>(pi, pj, [&](const uint4 (&v)[NFF / 8]) {
#pragma unroll
        for (int i = 0; i < 4; i++) d[i][0] = d[i][1] = d[i][2] = d[i][3] = 0.f;
#pragma unroll
        for (int i = 0; i < NFF / 8; i++) mma_v(d[i & 3], v[i], s0, s1);
      });
      TLW(38);
      const bool up = t & 2;
      float v0 = up ? (d[0][2] + d[1][2]) + (d[2][2] + d[3][2]) : (d[0][0] + d[1][0]) + (d[2][0] + d[3][0]);
      float v1 = up ? (d[0][3] + d[1][3]) + (d[2][3] + d[3][3]) : (d[0][1] + d[1][1]) + (d[2][1] + d[3][1]);
      v0 += __shfl_xor_sync(~0u, v0, 16);
      v1 += __shfl_xor_sync(~0u, v1, 16);
      if (g < 4) {
        asm volatile("st.global.u16 [%0], %1;" ::"l"(fo), "h"(__bfloat16_as_ushort(__float2bfloat16(r0 + gb0 * v0))) : "memory");
        asm volatile("st.global.u16 [%0], %1;" ::"l"(fo + 512), "h"(__bfloat16_as_ushort(__float2bfloat16(r1 + gb1 * v1))) : "memory");
      }
    }
    TLW(23);
    if (cta == 0 && lane == 0) stg1(&gs->epoch, epoch + 1);
    return;
  }

  if (w == 9) {
    uint32_t cf[16][4];
    asm volatile("bar.sync 3, 288;" ::: "memory");
#pragma unroll
    for (int i = 0; i < 16; i++) ldsm4(cf[i], hi + OFF_R0 + (i >> 1) * 1024 + (lane & 7) * 128 + (((4 * (i & 1) + (lane >> 3)) ^ (lane & 7)) << 4));
#pragma unroll
    for (int i = 0; i < 16; i++) cf[i][0] = hold32(cf[i][0]);
    asm volatile("bar.arrive 2, 288;" ::: "memory");
    if (lane == 0) {
      mbar_expect(hi + BAR(BAR_XE), 16384 + 4096);
      mbar_wait(hi + BAR(BAR_EMPTY + 3));
      mbar_wait(hi + BAR(BAR_FULL + XE_AT));
      TLW(33);
      bulk_load(hi + OFF_XE, gs->XE + cta * 4096, 16384, hi + BAR(BAR_XE));
      bulk_load(hi + OFF_MLS, gs->MLE + hI * 1024, 4096, hi + BAR(BAR_XE));
    }
    __syncwarp();
    {
      uint32_t* const mo = gs->MODB[lds1(hi + OFF_EPOCH) & 1] + cta * 64 + lane;
      const uint32_t base = hi + OFF_WM + (8 * (lane >> 4) + (lane & 7)) * 64 + (((2 * rI + ((lane >> 3) & 1)) ^ ((lane & 7) >> 1)) << 4);
      float d[4][4] = {{0.f, 0.f, 0.f, 0.f}, {0.f, 0.f, 0.f, 0.f}, {0.f, 0.f, 0.f, 0.f}, {0.f, 0.f, 0.f, 0.f}};
#pragma unroll
      for (int q = 0; q < 4; q++) {
        if (!(q & 1)) mbar_wait(hi + BAR(BAR_FULL + U_WMOD + (q >> 1)));
        uint32_t a[8][4];
#pragma unroll
        for (int ks = 0; ks < 8; ks++) ldsm4t(a[ks], base + (8 * q + ks) * 1024);
#pragma unroll
        for (int ks = 0; ks < 8; ks++) mma16816(d[ks & 3], a[ks], cf[4 * q + (ks >> 1)][2 * (ks & 1)], cf[4 * q + (ks >> 1)][2 * (ks & 1) + 1]);
      }
      stg1(mo, nz(pack_bf16((d[0][0] + d[1][0]) + (d[2][0] + d[3][0]), (d[0][1] + d[1][1]) + (d[2][1] + d[3][1]))));
      stg1(mo + 32, nz(pack_bf16((d[0][2] + d[1][2]) + (d[2][2] + d[3][2]), (d[0][3] + d[1][3]) + (d[2][3] + d[3][3]))));
      TLW(31);
    }
    if (cta < NFF) PROBE_UNITS(50, 54);
    return;
  }

  const int wg = w >> 2, wq = w & 3;
  if (!p0a) {
    asm volatile("cp.async.wait_all;" ::: "memory");
    cw0 = ldg_in4(gc + g * 1024 + w * 128 + t * 32); cw1 = ldg_in4(gc + g * 1024 + w * 128 + t * 32 + 16);
  }
  sts4(hi + OFF_R0 + w * 1024 + g * 128 + (((2 * t) ^ g) << 4), make_uint4(silu2(cw0.x), silu2(cw0.y), silu2(cw0.z), silu2(cw0.w)));
  sts4(hi + OFF_R0 + w * 1024 + g * 128 + (((2 * t + 1) ^ g) << 4), make_uint4(silu2(cw1.x), silu2(cw1.y), silu2(cw1.z), silu2(cw1.w)));
  asm volatile("bar.arrive 3, 288;" ::: "memory");
  if (p0a) {
    asm volatile("fence.proxy.async.shared::cta;" ::: "memory");
  {
    float v[16];
    const uint32_t u[8] = {xr0.x, xr0.y, xr0.z, xr0.w, xr1.x, xr1.y, xr1.z, xr1.w};
#pragma unroll
    for (int i = 0; i < 8; i++) { v[2 * i] = bf_lo(u[i]); v[2 * i + 1] = bf_hi(u[i]); }
    float s = (((v[0] + v[1]) + (v[2] + v[3])) + ((v[4] + v[5]) + (v[6] + v[7]))) + (((v[8] + v[9]) + (v[10] + v[11])) + ((v[12] + v[13]) + (v[14] + v[15])));
#pragma unroll
    for (int o = 16; o; o >>= 1) s += __shfl_xor_sync(~0u, s, o);
    const float mu = s * (1.f / 512.f);
    float q0 = 0.f, q1 = 0.f;
#pragma unroll
    for (int i = 0; i < 8; i++) { const float a = v[2 * i] - mu, b = v[2 * i + 1] - mu; q0 += a * a; q1 += b * b; }
    float q = q0 + q1;
#pragma unroll
    for (int o = 16; o; o >>= 1) q += __shfl_xor_sync(~0u, q, o);
    const float rs = rsqrtf(q * (1.f / 512.f) + 1e-5f);
    asm volatile("st.shared.u16 [%0], %1;" ::"r"(hi + OFF_P0S + lane * 32 + w * 2), "h"(__bfloat16_as_ushort(__float2bfloat16((bf_lo(xc) - mu) * rs))) : "memory");
    asm volatile("st.shared.u16 [%0], %1;" ::"r"(hi + OFF_P0S + lane * 32 + 16 + w * 2), "h"(__bfloat16_as_ushort(__float2bfloat16((bf_hi(xc) - mu) * rs))) : "memory");
  }
    cbar();
    TL(1);
  }
  if (p0a && wg == 0) {
    uint32_t* const mo = gs->MODA + cta * 32 + wq * 64 + lane;
    const uint32_t xn0 = lds1(hi + OFF_P0S + wq * 256 + lane * 4), xn1 = lds1(hi + OFF_P0S + wq * 256 + 128 + lane * 4);
    float d[4] = {0.f, 0.f, 0.f, 0.f};
    asm volatile("" : "+f"(d[0]), "+f"(d[1]), "+f"(d[2]), "+f"(d[3]) :: "memory");
#pragma unroll 1
    for (int i = 0; i < 4; i++) {
      mbar_wait(hi + BAR(BAR_WA) + 8 * i);
      wg_fence();
#pragma unroll
      for (int ks = 0; ks < 8; ks++) wgmma_n8(d, dlo(slot(8)) + i * 1024 + ks * 128, dlo(OFF_R0) + i * 128 + (ks >> 2) * 64 + (ks & 3) * 2);
      wg_commit();
    }
    wg_wait<0>();
    asm volatile("" : "+f"(d[0]), "+f"(d[1]), "+f"(d[2]), "+f"(d[3]) :: "memory");
    uint32_t y0 = pack_bf16(d[0], d[1]), y1 = pack_bf16(d[2], d[3]);
    if (cta >= 64) { y0 = hmul2(xn0, hadd2(y0, ONE2)); y1 = hmul2(xn1, hadd2(y1, ONE2)); }
    stg1(mo, nz(y0));
    stg1(mo + 32, nz(y1));
    TL(3);
  }
  cbar();
  TL(2);
  {
    uint32_t* const qpo = pin(gs->QP + (cta * 256 + tid) * 2);
    const uint32_t* const modi = pin(gs->MODA + 512 * jI + tid * 2);
    uint32_t a[8][4];
    mbar_wait(hi + BAR(BAR_FULL + U_WQ) + 8 * wg); mbar_wait(hi + BAR(BAR_FULL + U_WQ + 2) + 8 * wg);
    load_a_t(a, hi + OFF_R1 + wg * 16384, wq, lane);
    mbar_wait(hi + BAR(BAR_FULL + U_WQ + MOD_AT));
    backoff(D_MOD);
    TL(48);
    uint2 sa, ca;
    do { sa = ldg_rlx2(modi); ca = ldg_rlx2(modi + 2048); } while (min(min(sa.x, sa.y), min(ca.x, ca.y)) == 0);
    TL(41);
    sts2(hi + OFF_BS + tid * 8, hadd2(ca.x, sa.x), hadd2(ca.y, sa.y));
    cbar();
    float d[4];
    mma128(d, a, hi + OFF_BS + lane * 16);
    stg_u64(qpo, pack_bf16(d[0], d[1]), pack_bf16(d[2], d[3]));
  }
  const uint32_t ckq = clk32();
  TL(6);
  mbar_wait(hi + BAR(BAR_EPOCH));
  const int par = lds1(hi + OFF_EPOCH) & 1;
  uint32_t* const QX = gs->QX[par];
  {
    uint32_t a[8][4];
    {
      const int mi = lane >> 3, r = lane & 7;
      const int row = 16 * w + 8 * (mi & 1) + r;
      mbar_wait(hi + BAR(BAR_FULL + U_WUK) + 16 * wg); mbar_wait(hi + BAR(BAR_FULL + U_WUK + 1) + 16 * wg);
#pragma unroll
      for (int ks = 0; ks < 8; ks++) {
        const int chunk = 2 * ks + (mi >> 1);
        ldsm4(a[ks], hi + OFF_R2 + (ks >> 2) * 16384 + row * 128 + (((chunk & 7) ^ r) << 4));
      }
    }
    TL(8);
    uint32_t* const qxo = pin(QX + ((lane >> 1) * 32 + hI) * 256 + (128 * jI + 16 * w + 8 * (lane & 1)) / 2);
    const uint32_t* const qpi = pin(gs->QP + (hI * 4 * 256 + tid) * 2);
    mbar_wait(hi + BAR(BAR_FULL - 1));
    wait_until(ckq, D_QP);
    TL(29);
    uint2 qp[4];
#pragma unroll
    for (int i = 0; i < 4; i++) qp[i] = ldg_u64(qpi + i * 512);
    sum4_to_smem(qp, qpi, qpi + 1024, hi + OFF_BS2 + (16 * w + g) * 16 + t * 4, [] {});
    TL(7);
    cbar();
    float d[4];
    mma128(d, a, hi + OFF_BS2 + lane * 16);
    const float sc = 0.08838834764831845f * 1.4426950408889634f;
    const uint32_t stg = hi + OFF_P0S + 4096 + w * 256;
    stsm2t(stg + (lane & 7) * 32 + ((lane >> 3) & 1) * 16, pack_bf16(d[0] * sc, d[1] * sc), pack_bf16(d[2] * sc, d[3] * sc));
    __syncwarp();
    if (lane < 16) stg_u128(qxo, lds4(stg + lane * 16));
    if (lane == 0) mbar_arrive(hi + BAR(BAR_P2E));
  }
  const uint32_t ckx = clk32();
  TL(9);
  uint32_t fb = 0;
  {
    const uint32_t* qx = pin(QX + bI * 8192 + w * 1024 + lane * 4);
    mbar_wait(hi + BAR(BAR_FULL + QX_AT));
    wait_until(ckx, D_QX);
    TL(4);
    uint4 v[8];
#pragma unroll
    for (int i = 0; i < 8; i++) v[i] = ldg_u128(qx + i * 128);
    asm volatile("bar.sync 2, 288;" ::: "memory");
    while (true) {
      bool all = true;
#pragma unroll
      for (int i = 0; i < 8; i++) all = all && v[i].w != 0;
      if (all) break;
#pragma unroll
      for (int i = 0; i < 8; i++) if (v[i].w == 0) v[i] = ldg_u128(qx + i * 128);
    }
    TL(5);
#pragma unroll
    for (int i = 0; i < 8; i++) {
      const int hh = (4 * w + (i >> 1)) ^ (16 * rI), ch = 32 * (i & 1) + lane;
      sts4(hi + OFF_R0 + (ch >> 3) * 4096 + hh * 128 + (((ch & 7) ^ (hh & 7)) << 4), v[i]);
    }
    asm volatile("fence.proxy.async.shared::cta;" ::: "memory");
    cbar();
    if (tid == 0) mbar_arrive(hi + BAR(BAR_GO));
  }
  TL(10);

  uint32_t ck1;
  const uint32_t *px, *pm;
  uint32_t *x2o, *x2p;
  {
    float O32[4][16], O16[4][8];
    uint32_t ebar;
    asm("mapa.shared::cluster.u32 %0, %1, %2;" : "=r"(ebar) : "r"(hi + BAR(BAR_EMPTY)), "r"(rI ^ (lane & 1)));
#pragma unroll
    for (int i = 0; i < 16; i++) O32[0][i] = O32[1][i] = O32[2][i] = O32[3][i] = 0.f;
#pragma unroll
    for (int i = 0; i < 4; i++) tie(O32[i]);
    auto pv2 = [&](int T, int WG, auto& O, int mb, int k0, int k1) {
      const int n = 8 * T + 4 * WG + mb;
      const uint32_t da = dlo(SB) + (sizeof(O[0]) == 64 ? n : n - 23) * 512, db = (WG && mb && T == 2) ? dlo(SB) : da + 512, dp = dlo(OFF_PT) + (T & 1) * 256;
#pragma unroll
      for (int ks = k0; ks < k1; ks++) { wgmma_ss<1, 1>(O[mb], da + ks * 128, dp + ks * 2); wgmma_ss<1, 1>(O[mb + 1], db + ks * 128, dp + ks * 2); }
      wg_commit();
    };
    auto pv = [&](int T, int WG, auto& O) { wg_fence(); pv2(T, WG, O, 0, 0, 4); pv2(T, WG, O, 2, 0, 4); };
    auto release = [&](int T, auto& O) {
      wg_wait<0>();
#pragma unroll
      for (int i = 0; i < 4; i++) tie(O[i]);
      if (lane < 2) mbar_arrive_cluster(ebar + 8 * T);
      TL(T < 3 ? 24 + T : 32);
    };
    auto rescale = [&](auto& O) {
#pragma unroll
      for (int jn = 0; jn < (int)(sizeof(O[0]) / 16); jn++) {
        const float2 a = ldsf2(hi + OFF_ALPHA + (8 * jn + 2 * t) * 4);
#pragma unroll
        for (int mb = 0; mb < 4; mb++) { O[mb][4 * jn] *= a.x; O[mb][4 * jn + 1] *= a.y; O[mb][4 * jn + 2] *= a.x; O[mb][4 * jn + 3] *= a.y; }
      }
    };
    uint64_t oe[8];
    uint32_t* const x1e = hold(gs->XE + (((16 * (1 - rI) + 2 * t) * 4 + 2 * wg) * 64 + (cta >> 1)) * 64 + (((wq * 8 + g) * 2) ^ ((pI & 3) << 3)));
    auto split_o = [&] {
#pragma unroll
      for (int i = 0; i < 8; i++) {
        const int jj = i >> 2, r = 8 + 4 * ((i >> 1) & 1) + (i & 1);
        oe[i] = pair64(pack_bf16(O32[2 * jj][r], O32[2 * jj][r + 2]), (pack_bf16(O32[2 * jj + 1][r], O32[2 * jj + 1][r + 2]) | 1u) ^ par);
      }
#pragma unroll
      for (int i = 0; i < 32; i++) asm volatile("mov.b32 %0, %1;" : "=f"(O16[i >> 3][i & 7]) : "f"(O32[i >> 3][i & 7]));
    };
    auto put_early = [&](int i) { stg_b64(x1e + ((8 * ((i >> 1) & 1) + (i & 1)) * 4 + (i >> 2)) * 4096, oe[i]); };
    uint32_t* x1l[4];
    auto late_addr = [&] {
      mbar_wait(hi + BAR(BAR_FM));
      fb = lds1(hi + OFF_FB + tid * 4);
#pragma unroll
      for (int i = 0; i < 4; i++)
        x1l[i] = hold(inbox((16 * rI + 2 * t) * 4 + 2 * wg + (bI >> 2), bI & 3, fb, 4 * (i & 1) + (i >> 1), pI * 128 + (wq * 8 + g) * 2));
      px = hold(inbox((cta & ~1) + wg, wq, (fb >> (8 + (jI & 2) + wg)) ^ wq, 0, t * 128 + rI * 64 + 4 * g));
      pm = hold(inbox(cta & ~1, 6, fb, 8 + (jI & 2), 512 + (w * 8 + t) * 8));
      x2o = hold(inbox(4 * hI + (jI >> 1) + (~jI & 2), 7, ~fb, 8 + (jI >> 1) + (~jI & 2), (jI & 1) * 512 + tid * 2));
      x2p = hold(inbox(4 * hI + (jI >> 1) + (jI & 2), 7, ~fb, 8 + (jI >> 1) + (jI & 2), (jI & 1) * 512 + tid * 2));
    };
    auto put_late = [&](int jj) {
#pragma unroll
      for (int i = 0; i < 4; i++) {
        const int jn = i >> 1, e = i & 1, r = 4 * jn + e;
        stg_u64(x1l[i] + (8 * jn + e) * 4 * 16384 + jj * 64, pack_bf16(O16[2 * jj][r], O16[2 * jj][r + 2]), pack_bf16(O16[2 * jj + 1][r], O16[2 * jj + 1][r + 2]));
      }
    };
    auto last_products = [&](int WG) {
      wg_fence();
      pv2(4, WG, O16, 0, 0, 4);
      ck1 = clk32();
      pv2(4, WG, O16, 2, 0, PV_SPLIT);
      wg_wait<1>();
      tie(O16[0]); tie(O16[1]);
      TL(12);
      put_late(0);
      __syncwarp();
      if (PV_SPLIT < 4) { wg_fence(); pv2(4, WG, O16, 2, PV_SPLIT, 4); }
      wg_wait<0>();
      tie(O16[2]); tie(O16[3]);
      TL(50);
      put_late(1);
      if (lane < 2) mbar_arrive_cluster(ebar + 32);
    };

    if (wg == 0) {
      float S32[16], S16[8];
      float m_run = -INFINITY;
      float mh[8];
#pragma unroll
      for (int i = 0; i < 16; i++) S32[i] = S16[i & 7] = mh[i & 7] = 0.f;
      const uint32_t ptl = hold32(hi + OFF_PT + (8 * (lane >> 4) + (lane & 7)) * 128 + (((2 * wq + ((lane >> 3) & 1)) ^ (lane & 7)) << 4));
      auto landed = [&](int T) { return __ballot_sync(~0u, mbar_test(hi + BAR(BAR_FULL + 8 * T) + 8 * (lane & 7))); };
      auto softmax = [&](int T, auto& O, auto& S) {
        constexpr int NJ = sizeof(S) / 16;
        wg_wait<0>();
        tie(S);
        if (NJ == 2) TL(T == 4 ? 11 : 52);
        auto update = [&] {
            float mx[2 * NJ];
#pragma unroll
            for (int jn = 0; jn < NJ; jn++) { mx[2 * jn] = fmaxf(S[4 * jn], S[4 * jn + 2]); mx[2 * jn + 1] = fmaxf(S[4 * jn + 1], S[4 * jn + 3]); }
            float a4[4], a2[2], a1;
            if constexpr (NJ == 4) {
              const bool up = lane & 16;
#pragma unroll
              for (int i = 0; i < 4; i++) { const float send = up ? mx[i] : mx[4 + i]; const float keep = up ? mx[4 + i] : mx[i]; a4[i] = fmaxf(keep, __shfl_xor_sync(~0u, send, 16)); }
            } else {
#pragma unroll
              for (int i = 0; i < 4; i++) { a4[i] = fmaxf(mx[i], __shfl_xor_sync(~0u, mx[i], 16)); if (lane & 16) a4[i] = -INFINITY; }
            }
            {
              const bool up = lane & 8;
#pragma unroll
              for (int i = 0; i < 2; i++) { const float send = up ? a4[i] : a4[2 + i]; const float keep = up ? a4[2 + i] : a4[i]; a2[i] = fmaxf(keep, __shfl_xor_sync(~0u, send, 8)); }
            }
            {
              const bool up = lane & 4;
              const float send = up ? a2[0] : a2[1]; const float keep = up ? a2[1] : a2[0];
              a1 = fmaxf(keep, __shfl_xor_sync(~0u, send, 4));
            }
            stsf(hi + OFF_RED + (wq * 32 + 8 * (g >> 1) + 2 * t + (g & 1)) * 4, a1);
            wg0bar();
            const float mt = fmaxf(fmaxf(ldsf(hi + OFF_RED + lane * 4), ldsf(hi + OFF_RED + 128 + lane * 4)),
                                   fmaxf(ldsf(hi + OFF_RED + 256 + lane * 4), ldsf(hi + OFF_RED + 384 + lane * 4)));
            const float m_new = fmaxf(m_run, ceilf(mt));
            if (wq == 0) { stsf(hi + OFF_MREF + lane * 4, m_new); stsf(hi + OFF_ALPHA + lane * 4, ex2(m_run - m_new)); }
            m_run = m_new;
#pragma unroll
            for (int i = 0; i < 2 * NJ; i++) mh[i] = __shfl_sync(~0u, m_new, 8 * (i >> 1) + 2 * t + (i & 1));
            if (T > 0) { wg0bar(); rescale(O); }
        };
        auto write_p = [&] {
          uint32_t pk[2 * NJ];
          float x[4 * NJ];
#pragma unroll
          for (int i = 0; i < 4 * NJ; i++) x[i] = S[i] - mh[2 * (i >> 2) + (i & 1)];
#pragma unroll
          for (int i = 0; i < 2 * NJ; i++) pk[i] = pack_bf16(ex2(x[2 * i]), ex2(x[2 * i + 1]));
#pragma unroll
          for (int hf = 0; hf < NJ / 2; hf++) stsm4t(ptl + (T & 1) * 4096 + hf * 2048, pk[4 * hf], pk[4 * hf + 1], pk[4 * hf + 2], pk[4 * hf + 3]);
          asm volatile("fence.proxy.async.shared::cta;" ::: "memory");
          if constexpr (NJ == 4) {
#pragma unroll
            for (int i = 0; i < 8; i++) x[i] = fmaxf(x[i], x[i + 8]);
          }
          return cbar_or(fmaxf(fmaxf(fmaxf(x[0], x[1]), fmaxf(x[2], x[3])), fmaxf(fmaxf(x[4], x[5]), fmaxf(x[6], x[7]))) > 64.f);
        };
        if constexpr (NJ == 4) {
          bool over = T == 0;
#pragma unroll 1
          do {
            if (over) update();
            over = write_p();
          } while (__builtin_expect(over, 0));
        } else {
#pragma unroll 1
          while (__builtin_expect(write_p(), 0)) update();
        }
        if (NJ == 2) TL(T == 4 ? 34 : 53);
      };
      uint32_t have = 0;
#pragma unroll
      for (int i = 0; i < 4; i++) x1l[i] = nullptr;
      px = pm = x2o = x2p = nullptr;
#pragma unroll 1
      for (int T = 0; T < 3; T++) {
        UNROLL(QK_UNROLL)
        for (int jj = 0; jj < 8; jj++) {
          const uint32_t da = dlo(SB) + box_slot(8 * T + jj) * 512, db = dlo(OFF_R0) + jj * 256;
          mbar_wait(hi + BAR(BAR_FULL) + 64 * T + 8 * jj);
          wg_fence();
          wgmma_ss_p(S32, da, db, jj);
#pragma unroll
          for (int ks = 1; ks < 4; ks++) wgmma_ss<0, 1>(S32, da + ks * 2, db + ks * 2);
          wg_commit();
        }
        softmax(T, O32, S32);
        pv(T, 0, O32);
        have = landed(3);
        release(T, O32);
        if (T == 1) late_addr();
      }
      split_o();
      TL(27);
#pragma unroll 1
      for (int T = 3;; T++) {
        sfor<0, 8>([&](auto jc) {
          constexpr int jj = decltype(jc)::value;
          const uint32_t da = dlo(SB) + (8 * T + jj - 23) * 512, db = dlo(OFF_R0) + jj * 256;
          if (!((have >> jj) & 1)) mbar_wait(hi + BAR(BAR_FULL) + 64 * T + 8 * jj);
          wg_fence();
          wgmma_ss<0, jj != 0>(S16, da, db);
#pragma unroll
          for (int ks = 1; ks < 4; ks++) wgmma_ss<0, 1>(S16, da + ks * 2, db + ks * 2);
          wg_commit();
          if (T == 3) {
            put_early(jj);
          }
        });
        softmax(T, O16, S16);
        if (T == 4) break;
        pv(3, 0, O16);
        have = landed(4);
        release(3, O16);
      }
      last_products(0);
    } else {
      float ls[2] = {0.f, 0.f};
      const int hr = 4 * wq + (lane >> 3);
      const uint32_t ptl = hi + OFF_PT + (tid & 127) * 16;
      auto sum8 = [](const uint4& v) { return ((bf_lo(v.x) + bf_hi(v.x)) + (bf_lo(v.y) + bf_hi(v.y))) + ((bf_lo(v.z) + bf_hi(v.z)) + (bf_lo(v.w) + bf_hi(v.w))); };
      auto row_sum = [](float l) { l += __shfl_xor_sync(~0u, l, 1); l += __shfl_xor_sync(~0u, l, 2); return l + __shfl_xor_sync(~0u, l, 4); };
      auto get_p = [&](auto& O) {
        if (__builtin_expect(cbar_or(false), 0)) {
          cbar_or(false);
          rescale(O);
          ls[0] *= ldsf(hi + OFF_ALPHA + hr * 4);
          if (sizeof(O[0]) == 64) ls[1] *= ldsf(hi + OFF_ALPHA + 64 + hr * 4);
        }
      };
#pragma unroll 1
      for (int T = 0; T < 3; T++) {
        get_p(O32);
        pv(T, 1, O32);
        ls[0] += sum8(lds4(ptl + (T & 1) * 4096));
        ls[1] += sum8(lds4(ptl + (T & 1) * 4096 + 2048));
        release(T, O32);
      }
      split_o();
      {
        const float l0 = row_sum(ls[0]), l1 = row_sum(ls[1]);
        const int hl = hr + 8 * (lane & 2);
        const uint32_t m = lds1(hi + OFF_MREF + hl * 4), l = (__float_as_uint((lane & 2) ? l1 : l0) | 1u) ^ par;
        if (!(lane & 4)) stg4_b128(gs->MLE + ((hl ^ (16 * rI)) * 128 + cta) * 8 + (lane & 1) * 4, make_uint4(m, l, m, l));
#pragma unroll
        for (int i = 0; i < 8; i++) put_early(i);
      }
      get_p(O16);
      pv(3, 1, O16);
      ls[0] += sum8(lds4(ptl + 4096));
      release(3, O16);
      late_addr();
      uint32_t* const mlo = hold(inbox((16 * rI + hr) * 4 + (lane & 2), 6, fb, 13, 512 + (cta >> 1) * 8 + (lane & 1) * 4));
      mbar_wait(hi + BAR(BAR_CLR));
      get_p(O16);
      {
        const uint32_t m = lds1(hi + OFF_MREF + hr * 4), l = nz(__float_as_uint(row_sum(ls[0] + sum8(lds4(ptl)))));
        if (!(lane & 4)) stg4_b128(mlo, make_uint4(m, l, m, l));
      }
      last_products(1);
    }
  }
  TL(13);

  uint32_t aw[8][4];
  {
    uint2 mle[4];
    uint4 ve[4];
    wait_until(ck1, X1_D0);
    uint2 ml[2];
    uint4 v[4];
#pragma unroll
    for (int i = 0; i < 4; i++) v[i] = ldg_2u64(px + (i >> 1) * 512 + (i & 1) * 32);
#pragma unroll
    for (int i = 0; i < 2; i++) ml[i] = ldg_u64(pm + i * 32);
    TL(43);
    mbar_wait(hi + BAR(BAR_XE));
#pragma unroll
    for (int i = 0; i < 4; i++) mle[i] = lds2(hi + OFF_MLS + (w * 16 + 2 * t + 8 * (i & 1) + ((hI >> 4) ^ (i >> 1))) * 32);
#pragma unroll
    for (int i = 0; i < 4; i++) ve[i] = lds4(hi + OFF_XE + (w * 8 + t) * 256 + (g ^ (2 * t)) * 16 + (i >> 1) * 1024 + (i & 1) * 128);
#pragma unroll 1
    while (true) {
      uint32_t a = 1u, o = 0u;
#pragma unroll
      for (int i = 0; i < 4; i++) { a &= ve[i].y & ve[i].w & mle[i].y; o |= ve[i].y | ve[i].w | mle[i].y; }
      if (__all_sync(~0u, (par ? ~o : a) & 1)) break;
#pragma unroll
      for (int i = 0; i < 4; i++) {
        ve[i] = ldg_2u64(gs->XE + (cta * 64 + w * 8 + t) * 64 + 4 * (g ^ (2 * t)) + (i >> 1) * 256 + (i & 1) * 32);
        mle[i] = ldg_u64(gs->MLE + (hI * 128 + w * 16 + 2 * t + 8 * (i & 1) + ((hI >> 4) ^ (i >> 1))) * 8);
      }
      TL(55);
    }
    float M = fmaxf(fmaxf(__uint_as_float(mle[0].x), __uint_as_float(mle[1].x)), fmaxf(__uint_as_float(mle[2].x), __uint_as_float(mle[3].x)));
    M = fmaxf(M, __shfl_xor_sync(~0u, M, 1)); M = fmaxf(M, __shfl_xor_sync(~0u, M, 2));
    uint32_t wb[4];
#pragma unroll
    for (int i = 0; i < 4; i++) wb[i] = pack_bf16(ex2(__uint_as_float(mle[i].x) - M), 0.f);
    float Ls = bf_lo(wb[2]) * __uint_as_float(mle[2].y) + bf_lo(wb[3]) * __uint_as_float(mle[3].y);
    float d0[4] = {0.f, 0.f, 0.f, 0.f}, d1[4] = {0.f, 0.f, 0.f, 0.f};
#pragma unroll
    for (int i = 0; i < 4; i++) mma_v((i & 2) ? d1 : d0, ve[i], shl_clamp(wb[2 + (i >> 1)], 16 * g - 64 * (i & 1)), shl_clamp(wb[2 + (i >> 1)], 16 * g - 64 * (i & 1) - 32));
    uint32_t sel[4][2];
#pragma unroll
    for (int i = 0; i < 4; i++) { sel[i][0] = pin32(shl_clamp(wb[i >> 1], 16 * g - 64 * (i & 1))); sel[i][1] = pin32(shl_clamp(wb[i >> 1], 16 * g - 64 * (i & 1) - 32)); }
    const uint32_t bso = hold32(hi + OFF_BS4 + w * 320 + (16 * (t >> 1) + 8 * (g >> 2) + 4 * (g & 1) + 2 * (t & 1) + ((g >> 1) & 1)) * 8), bsi = hold32(hi + OFF_BS4 + g * 320 + t * 16);
    const uint32_t lso = hold32(hi + OFF_BS4 + w * 320 + 256 + t * 4), lsi = hold32(hi + OFF_BS4 + t * 640 + 256);
    TL(14);
    const uint32_t wa = hold32(hi + OFF_WUV + wg * 8192 + (lane >> 4) * 4096 + (lane & 7) * 128 + (((2 * wq + ((lane >> 3) & 1)) ^ (lane & 7)) << 4));
    mbar_wait(hi + BAR(BAR_FULL + U_WUV) + 8 * wg);
#pragma unroll
    for (int ks = 0; ks < 4; ks++) { ldsm4t(aw[ks], wa + ks * 1024); aw[4 + ks][0] = aw[4 + ks][1] = aw[4 + ks][2] = aw[4 + ks][3] = 0; }
    bool wv_ok = false;
    TL(44);
    float e0[4], e1[4];
#pragma unroll 1
    while (true) {
      if (!wv_ok && mbar_test(hi + BAR(BAR_FULL + U_WUV + 2) + 8 * wg)) {
        wv_ok = true;
#pragma unroll
        for (int ks = 0; ks < 4; ks++) ldsm4t(aw[4 + ks], wa + 16384 + ks * 1024);
      }
#pragma unroll
      for (int i = 0; i < 4; i++) tie(v[i]);
      tie(ml[0]); tie(ml[1]);
      const bool valid = min(min3(min3(v[0].y, v[0].w, v[1].y), v[1].w, ml[0].y), min3(min3(v[2].y, v[2].w, v[3].y), v[3].w, ml[1].y)) != 0;
      const bool ok = __all_sync(~0u, valid && ml[0].x == mle[0].x && ml[1].x == mle[1].x);
#pragma unroll
      for (int i = 0; i < 4; i++) { e0[i] = d0[i]; e1[i] = d1[i]; }
      mma_v(e0, v[0], sel[0][0], sel[0][1]); mma_v(e1, v[2], sel[2][0], sel[2][1]);
      mma_v(e0, v[1], sel[1][0], sel[1][1]); mma_v(e1, v[3], sel[3][0], sel[3][1]);
      if (ok) break;
      if (__all_sync(~0u, valid)) {
        float M2 = fmaxf(M, fmaxf(__uint_as_float(ml[0].x), __uint_as_float(ml[1].x)));
        M2 = fmaxf(M2, __shfl_xor_sync(~0u, M2, 1)); M2 = fmaxf(M2, __shfl_xor_sync(~0u, M2, 2));
        const float f = ex2(M - M2);
        Ls *= f;
#pragma unroll
        for (int i = 0; i < 4; i++) { d0[i] *= f; d1[i] *= f; }
#pragma unroll
        for (int i = 0; i < 2; i++) { wb[i] = pack_bf16(ex2(__uint_as_float(ml[i].x) - M2), 0.f); mle[i].x = ml[i].x; }
#pragma unroll
        for (int i = 0; i < 4; i++) { sel[i][0] = shl_clamp(wb[i >> 1], 16 * g - 64 * (i & 1)); sel[i][1] = shl_clamp(wb[i >> 1], 16 * g - 64 * (i & 1) - 32); }
      }
#pragma unroll
      for (int i = 0; i < 4; i++) if (v[i].y == 0 || v[i].w == 0) v[i] = ldg_2u64(px + (i >> 1) * 512 + (i & 1) * 32);
#pragma unroll
      for (int i = 0; i < 2; i++) if (ml[i].y == 0) ml[i] = ldg_u64(pm + i * 32);
    }
    TL(15);
    stsf(lso, Ls + bf_lo(wb[0]) * __uint_as_float(ml[0].y) + bf_lo(wb[1]) * __uint_as_float(ml[1].y));
    sts2(bso, pack_bf16(e0[0] + e1[0], e0[1] + e1[1]), pack_bf16(e0[2] + e1[2], e0[3] + e1[3]));
    cbar();
    TL(16);
    float o[4][4] = {{0.f, 0.f, 0.f, 0.f}, {0.f, 0.f, 0.f, 0.f}, {0.f, 0.f, 0.f, 0.f}, {0.f, 0.f, 0.f, 0.f}};
    uint4 b[4];
#pragma unroll
    for (int kk = 0; kk < 4; kk++) b[kk] = lds4(bsi + kk * 64);
    const float4 la = ldsf4(lsi), lb = ldsf4(lsi + 320);
    if (!wv_ok) {
      mbar_wait(hi + BAR(BAR_FULL + U_WUV + 2) + 8 * wg);
#pragma unroll
      for (int ks = 0; ks < 4; ks++) ldsm4t(aw[4 + ks], wa + 16384 + ks * 1024);
    }
#pragma unroll
    for (int kk = 0; kk < 4; kk++) { mma16816(o[(2 * kk) & 3], aw[2 * kk], b[kk].x, b[kk].y); mma16816(o[(2 * kk + 1) & 3], aw[2 * kk + 1], b[kk].z, b[kk].w); }
    const float ia = rcp((la.x + la.y) + (la.z + la.w)), ib = rcp((lb.x + lb.y) + (lb.z + lb.w));
    const uint32_t y0 = pack_bf16(((o[0][0] + o[1][0]) + (o[2][0] + o[3][0])) * ia, ((o[0][1] + o[1][1]) + (o[2][1] + o[3][1])) * ib);
    const uint32_t y1 = pack_bf16(((o[0][2] + o[1][2]) + (o[2][2] + o[3][2])) * ia, ((o[0][3] + o[1][3]) + (o[2][3] + o[3][3])) * ib);
    stg_u64(x2o, y0, y1);
    stg_u64(x2p, y0, y1);
  }
  const uint32_t ck2 = clk32();
  TL(17);
  {
    uint32_t* const o = hold(inbox(4 * (8 * jI + w) + (g >> 1), 6, fb, 12, (g & 1) * 256 + hI * 8 + 2 * t));
    const uint32_t* const x2i = hold(inbox(cta & ~1, 7, ~fb, 8 + (jI & 2), tid * 2));
    const uint32_t* const x2j = hold(inbox(cta | 1, 7, ~fb, 8 + (jI | 1), tid * 2));
    const uint32_t bso = hold32(hi + OFF_BS5 + (16 * w + g) * 16 + t * 4), bsi = hold32(hi + OFF_BS5 + lane * 16);
    const uint32_t wa = hold32(hi + OFF_WO + wg * 8192 + (8 * (lane >> 4) + (lane & 7)) * 128 + (((2 * wq + ((lane >> 3) & 1)) ^ (lane & 7)) << 4));
    TL(45);
    wait_until(ck2, D_X2);
    uint2 v[4];
#pragma unroll
    for (int i = 0; i < 4; i++) v[i] = ldg_u64(((i & 2) ? x2j : x2i) + (i & 1) * 512);
    int wo_n = 0;
    sum4_to_smem(v, x2i, x2j, bso, [&] {
      if (wo_n == 0 && mbar_test(hi + BAR(BAR_FULL + U_WO) + 8 * wg)) {
        wo_n = 1;
#pragma unroll
        for (int ks = 0; ks < 4; ks++) ldsm4t(aw[ks], wa + ks * 2048);
      }
      if (wo_n == 1 && mbar_test(hi + BAR(BAR_FULL + U_WO + 2) + 8 * wg)) {
        wo_n = 2;
#pragma unroll
        for (int ks = 0; ks < 4; ks++) ldsm4t(aw[4 + ks], wa + 16384 + ks * 2048);
      }
    });
    cbar();
    TL(18);
    float e[4][4] = {{0.f, 0.f, 0.f, 0.f}, {0.f, 0.f, 0.f, 0.f}, {0.f, 0.f, 0.f, 0.f}, {0.f, 0.f, 0.f, 0.f}};
    uint32_t b[4][4];
#pragma unroll
    for (int kk = 0; kk < 4; kk++) ldsm4t(b[kk], bsi + kk * 512);
    if (wo_n < 2) {
      if (wo_n == 0) {
        mbar_wait(hi + BAR(BAR_FULL + U_WO) + 8 * wg);
#pragma unroll
        for (int ks = 0; ks < 4; ks++) ldsm4t(aw[ks], wa + ks * 2048);
      }
      mbar_wait(hi + BAR(BAR_FULL + U_WO + 2) + 8 * wg);
#pragma unroll
      for (int ks = 0; ks < 4; ks++) ldsm4t(aw[4 + ks], wa + 16384 + ks * 2048);
    }
#pragma unroll
    for (int ks = 0; ks < 8; ks++) mma16816(e[ks & 3], aw[ks], b[ks >> 1][2 * (ks & 1)], b[ks >> 1][2 * (ks & 1) + 1]);
    stg_u64(o, pack_bf16((e[0][0] + e[1][0]) + (e[2][0] + e[3][0]), (e[0][1] + e[1][1]) + (e[2][1] + e[3][1])),
            pack_bf16((e[0][2] + e[1][2]) + (e[2][2] + e[3][2]), (e[0][3] + e[1][3]) + (e[2][3] + e[3][3])));
    if (lane == 0) mbar_arrive(hi + BAR(BAR_P5D));
  }
  const uint32_t ck3 = clk32();
  TL(19);
  if (cta < NFF) {
    const int mi = lane >> 3, r = lane & 7;
    uint32_t a1[4][4], a2[4][4];
    uint32_t bc[8], bs[8];
    const uint32_t* const mbi = gs->MODB[par] + (512 + 64 * w) * 4 + lane;
#pragma unroll
    for (int i = 0; i < 8; i++) { bs[i] = ldg_rlx1(mbi + i * 32); bc[i] = ldg_rlx1(mbi + 2048 + i * 32); }
    const int lp = (tid >> 2) & 31, kq = tid & 3;
    const int fo = (lp >> 2) + 8 * (kq >> 1), bo = 2 * (lp & 3) + (kq & 1);
    const uint32_t* xb = hold(gs->X3B + ((cta >> 1) & 1) * 4096 + wg * 2048 + (((fb >> 14) & 1) << 10) + (16 * wq + t) * 16 + 2 * g);
    uint32_t* ox[4];
#pragma unroll
    for (int mb = 0; mb < 4; mb++) ox[mb] = hold(inbox(16 * w + 4 * mb + (g >> 1), 4 + (cta >= 56), fb, 16 + 4 * mb, (cta >= 56 ? cta - 56 : cta) * 16 + (g & 1) * 8 + 2 * t));
    const uint32_t gi = hold32(hi + OFF_REDG + tid * 4);
    const uint32_t h1o = hold32(hi + OFF_H1 + fo * 16 + bo * 2), sti = hold32(hi + OFF_REDS + bo * 80), sto = hold32(hi + OFF_REDS + g * 80 + w * 8);
    const uint32_t a1a = hold32(hi + OFF_W1 + (64 * w + 8 * (mi >> 1) + r) * 64 + (((2 * rI + (mi & 1)) ^ (r >> 1)) << 4));
    bool w2ok = false;
    uint32_t a2a[4];
#pragma unroll
    for (int mb = 0; mb < 4; mb++) {
      a2a[mb] = hi + OFF_W2 + w * 2048 + (8 * (mi >> 1) + r) * 128 + (((2 * mb + (mi & 1)) ^ r) << 4);
      a2[mb][0] = a2[mb][1] = a2[mb][2] = a2[mb][3] = 0;
    }
#pragma unroll 1
    while (true) {
      uint32_t mn = 0xffffffffu;
#pragma unroll
      for (int i = 0; i < 8; i++) mn = min3(mn, bs[i], bc[i]);
      if (__all_sync(~0u, mn != 0)) break;
#pragma unroll
      for (int i = 0; i < 8; i++) { bs[i] = ldg_rlx1(mbi + i * 32); bc[i] = ldg_rlx1(mbi + 2048 + i * 32); }
    }
#pragma unroll
    for (int i = 0; i < 8; i++) { bs[i] = movm(bs[i]); bc[i] = hadd2(movm(bc[i]), ONE2); }
    mbar_wait(hi + BAR(BAR_FULL + U_W1) + 8 * wg);
#pragma unroll
    for (int ks = 0; ks < 4; ks++) ldsm4t(a1[ks], a1a + ks * 1024);
    {
      float u[2][4] = {{0.f, 0.f, 0.f, 0.f}, {0.f, 0.f, 0.f, 0.f}}, vv[2][4] = {{0.f, 0.f, 0.f, 0.f}, {0.f, 0.f, 0.f, 0.f}};
#pragma unroll
      for (int ks = 0; ks < 4; ks++) { mma16816(u[ks & 1], a1[ks], bc[2 * ks], bc[2 * ks + 1]); mma16816(vv[ks & 1], a1[ks], bs[2 * ks], bs[2 * ks + 1]); }
      sts4f(hi + OFF_REDU + tid * 16, u[0][0] + u[1][0], u[0][1] + u[1][1], u[0][2] + u[1][2], u[0][3] + u[1][3]);
      sts4f(hi + OFF_REDV + tid * 16, vv[0][0] + vv[1][0], vv[0][1] + vv[1][1], vv[0][2] + vv[1][2], vv[0][3] + vv[1][3]);
    }
    if (wg) asm volatile("bar.arrive 1, 256;" ::: "memory"); else cbar();
    float U = 0.f, V = 0.f;
    bool uv = wg;
    TL(46);
    wait_until(ck3, D_X3B);
    float G[2][4], S[2][4];
    bool ok;
#pragma unroll 1
    do {
      uint2 x[4];
#pragma unroll
      for (int ks = 0; ks < 4; ks++) x[ks] = ldg_u64(xb + ks * 64);
      if (!uv) {
        uv = true;
        float a[8], b[8];
#pragma unroll
        for (int i = 0; i < 8; i++) { a[i] = ldsf(gi + (OFF_REDU - OFF_REDG) + i * 512); b[i] = ldsf(gi + (OFF_REDV - OFF_REDG) + i * 512); }
        U = ((a[0] + a[1]) + (a[2] + a[3])) + ((a[4] + a[5]) + (a[6] + a[7]));
        V = ((b[0] + b[1]) + (b[2] + b[3])) + ((b[4] + b[5]) + (b[6] + b[7]));
      }
      if (!w2ok && mbar_test(hi + BAR(BAR_FULL + U_W2) + 8 * wg)) {
        w2ok = true;
#pragma unroll
        for (int mb = 0; mb < 4; mb++) ldsm4t(a2[mb], a2a[mb]);
      }
#pragma unroll
      for (int ks = 0; ks < 4; ks++) tie(x[ks]);
      ok = __all_sync(~0u, min(min3(x[0].y, x[1].y, x[2].y), x[3].y) != 0);
#pragma unroll
      for (int i = 0; i < 4; i++) G[0][i] = G[1][i] = S[0][i] = S[1][i] = 0.f;
#pragma unroll
      for (int ks = 0; ks < 4; ks++) {
        const uint32_t s0[4] = {x[ks].x, ONE2, x[ks].y, ONE2};
        mma16816(S[ks & 1], s0, x[ks].x, x[ks].y);
        mma16816(G[ks & 1], a1[ks], hmul2(x[ks].x, bc[2 * ks]), hmul2(x[ks].y, bc[2 * ks + 1]));
      }
    } while (!ok);
    TL(21);
    if ((g >> 1) == t) sts2f(sto, (g & 1) ? S[0][3] + S[1][3] : S[0][2] + S[1][2], (g & 1) ? S[0][1] + S[1][1] : S[0][0] + S[1][0]);
    sts4f(hi + OFF_REDG + tid * 16, G[0][0] + G[1][0], G[0][1] + G[1][1], G[0][2] + G[1][2], G[0][3] + G[1][3]);
    if (wg) asm volatile("bar.arrive 3, 256;" ::: "memory"); else asm volatile("bar.sync 3, 256;" ::: "memory");
    TL(39);
    if (tid < 128) {
      float gv[8];
      float4 sv[4];
#pragma unroll
      for (int i = 0; i < 4; i++) sv[i] = ldsf4(sti + i * 16);
#pragma unroll
      for (int i = 0; i < 8; i++) gv[i] = ldsf(gi + i * 512);
      const float s1 = ((sv[0].x + sv[0].z) + (sv[1].x + sv[1].z)) + ((sv[2].x + sv[2].z) + (sv[3].x + sv[3].z));
      const float s2 = ((sv[0].y + sv[0].w) + (sv[1].y + sv[1].w)) + ((sv[2].y + sv[2].w) + (sv[3].y + sv[3].w));
      const float gs_ = ((gv[0] + gv[1]) + (gv[2] + gv[3])) + ((gv[4] + gv[5]) + (gv[6] + gv[7]));
      const float mu = s1 * (1.f / 512.f);
      const float rs = rsq(fmaxf(s2 * (1.f / 512.f) - mu * mu, 0.f) + 1e-5f);
      const float hv = fmaxf(rs * (gs_ - mu * U) + V, 0.f);
      asm volatile("st.shared.u16 [%0], %1;" ::"r"(h1o), "h"(__bfloat16_as_ushort(__float2bfloat16(hv))) : "memory");
    }
    if (!w2ok) {
      mbar_wait(hi + BAR(BAR_FULL + U_W2) + 8 * wg);
#pragma unroll
      for (int mb = 0; mb < 4; mb++) ldsm4t(a2[mb], a2a[mb]);
    }
    asm volatile("bar.sync 2, 256;" ::: "memory");
    TL(40);
    uint32_t b0, b1;
    ldsm2t(b0, b1, hi + OFF_H1 + (lane & 15) * 16);
#pragma unroll
    for (int mb = 0; mb < 4; mb++) {
      float o[4] = {0.f, 0.f, 0.f, 0.f};
      mma16816(o, a2[mb], b0, b1);
      stg_u64(ox[mb], pack_bf16(o[0], o[1]), pack_bf16(o[2], o[3]));
    }
    TL(22);
    if (lane == 0) mbar_arrive(hi + BAR(BAR_P7D));
  }
}

typedef CUresult (*EncodeTiledFn)(CUtensorMap*, CUtensorMapDataType, cuuint32_t, void*, const cuuint64_t*, const cuuint64_t*,
                                  const cuuint32_t*, const cuuint32_t*, CUtensorMapInterleave, CUtensorMapSwizzle,
                                  CUtensorMapL2promotion, CUtensorMapFloatOOBfill);

void make_map(EncodeTiledFn enc, CUtensorMap* m, const void* base, uint64_t cols, uint64_t rows, uint32_t bc, uint32_t br,
              CUtensorMapSwizzle sw, CUtensorMapL2promotion promo) {
  cuuint64_t dims[2] = {cols, rows};
  cuuint64_t strides[1] = {cols * 2};
  cuuint32_t box[2] = {bc, br};
  cuuint32_t es[2] = {1, 1};
  enc(m, CU_TENSOR_MAP_DATA_TYPE_BFLOAT16, 2, const_cast<void*>(base), dims, strides, box, es, CU_TENSOR_MAP_INTERLEAVE_NONE, sw, promo,
      CU_TENSOR_MAP_FLOAT_OOB_FILL_NONE);
}
void make_map3(EncodeTiledFn enc, CUtensorMap* m, const void* base, uint64_t rows, uint32_t br, uint32_t bb) {
  cuuint64_t dims[3] = {64, rows, 8};
  cuuint64_t strides[2] = {1024, 128};
  cuuint32_t box[3] = {64, br, bb};
  cuuint32_t es[3] = {1, 1, 1};
  enc(m, CU_TENSOR_MAP_DATA_TYPE_BFLOAT16, 3, const_cast<void*>(base), dims, strides, box, es, CU_TENSOR_MAP_INTERLEAVE_NONE,
      CU_TENSOR_MAP_SWIZZLE_128B, CU_TENSOR_MAP_L2_PROMOTION_NONE, CU_TENSOR_MAP_FLOAT_OOB_FILL_NONE);
}

}

extern "C" void kernel_launch(void* const* d_in, const int* in_sizes, int n_in, void* d_out, int out_size) {
  (void)in_sizes; (void)n_in; (void)out_size;
  static EncodeTiledFn enc = nullptr;
  static Scratch* scratch = nullptr;
  if (!enc) {
    void* sp = nullptr;
    cudaGetSymbolAddress(&sp, g_s);
    scratch = (Scratch*)(((uintptr_t)sp + 65535) & ~(uintptr_t)65535);
    void* fn = nullptr;
    cudaDriverEntryPointQueryResult q;
    cudaGetDriverEntryPoint("cuTensorMapEncodeTiled", &fn, cudaEnableDefault, &q);
    enc = (EncodeTiledFn)fn;
    cudaFuncSetAttribute(fused_decode_kernel, cudaFuncAttributeMaxDynamicSharedMemorySize, SMEM_BYTES);
  }
  Params P;
  make_map(enc, &P.ckv, d_in[1], 512, 8 * 4096, 64, 64, CU_TENSOR_MAP_SWIZZLE_128B, CU_TENSOR_MAP_L2_PROMOTION_NONE);
  make_map(enc, &P.wq, d_in[2], 4096, 512, 64, 64, CU_TENSOR_MAP_SWIZZLE_128B, CU_TENSOR_MAP_L2_PROMOTION_NONE);
  make_map(enc, &P.wuk, d_in[3], 4096, 512, 64, 64, CU_TENSOR_MAP_SWIZZLE_128B, CU_TENSOR_MAP_L2_PROMOTION_NONE);
  {
    cuuint64_t dims[5] = {4096, 2, 8, 4, 8};
    cuuint64_t strides[4] = {8 * 8192, 8192, 16 * 8192, 64 * 8192};
    cuuint32_t box[5] = {64, 2, 8, 2, 2};
    cuuint32_t es[5] = {1, 1, 1, 1, 1};
    enc(&P.wuv, CU_TENSOR_MAP_DATA_TYPE_BFLOAT16, 5, d_in[4], dims, strides, box, es, CU_TENSOR_MAP_INTERLEAVE_NONE, CU_TENSOR_MAP_SWIZZLE_128B,
        CU_TENSOR_MAP_L2_PROMOTION_NONE, CU_TENSOR_MAP_FLOAT_OOB_FILL_NONE);
  }
  make_map(enc, &P.wo, d_in[5], 512, 4096, 64, 64, CU_TENSOR_MAP_SWIZZLE_128B, CU_TENSOR_MAP_L2_PROMOTION_NONE);
  make_map(enc, &P.w1, d_in[7], 1792, 512, 2 * FCH, 128, CU_TENSOR_MAP_SWIZZLE_64B, PROMO);
  make_map3(enc, &P.w2, d_in[8], 1792, FCH, 4);
  make_map(enc, &P.wma, d_in[10], 3072, 512, 64, 128, CU_TENSOR_MAP_SWIZZLE_128B, CU_TENSOR_MAP_L2_PROMOTION_NONE);
  make_map(enc, &P.wmod, d_in[10], 3072, 512, 32, 128, CU_TENSOR_MAP_SWIZZLE_64B, PROMO);
  fused_decode_kernel<<<NCTA, NTHREADS, SMEM_BYTES>>>((__nv_bfloat16*)d_out, scratch, (const uint8_t*)d_in[2], (const uint8_t*)d_in[0],
                                                      (const uint8_t*)d_in[9], P);
}
```

```cpp
#include <cuda_runtime.h>
#include <cuda.h>
#include <cuda_bf16.h>
#include <stdint.h>

namespace {

constexpr int NCTA = 128;
constexpr int NTHREADS = 384;
constexpr int FCH = 16;
constexpr int NFF = 1792 / FCH;

constexpr uint32_t SB = 1024;
__host__ __device__ constexpr uint32_t slot(int i) { return SB + i * 8192; }
constexpr uint32_t OFF_R1 = slot(16);
constexpr uint32_t OFF_R2 = slot(20);
constexpr uint32_t OFF_PT = slot(23);
constexpr uint32_t OFF_R0 = slot(24);
constexpr uint32_t OFF_MISC = SB + 229376;
constexpr uint32_t OFF_BARS = OFF_MISC;
constexpr uint32_t OFF_FM = OFF_MISC + 736;
constexpr uint32_t OFF_EPOCH = OFF_MISC + 768;
constexpr uint32_t OFF_BS = OFF_MISC + 1024;
constexpr uint32_t SMEM_BYTES = 229376 + 3072;
constexpr uint32_t OFF_P0S = OFF_R0 + 24576;
constexpr uint32_t OFF_BS2 = OFF_R0 + 30720;
constexpr uint32_t OFF_RED = OFF_BS;
constexpr uint32_t OFF_ALPHA = OFF_BS + 512;
constexpr uint32_t OFF_MREF = OFF_BS + 640;
constexpr uint32_t OFF_MX = OFF_BS + 896;
constexpr uint32_t OFF_FB = OFF_BS + 1024;
__host__ __device__ constexpr int box_slot(int n) { return n < 23 ? n : n - 23; }
constexpr uint32_t OFF_WUV = slot(1);
constexpr uint32_t OFF_XE = slot(21);
constexpr uint32_t OFF_BS4 = slot(0);
constexpr uint32_t OFF_BS5 = slot(0) + 4096;
constexpr uint32_t OFF_WM = slot(17);
constexpr uint32_t OFF_WO = slot(5);
constexpr uint32_t OFF_W1 = slot(9);
constexpr uint32_t OFF_W2 = slot(13);
constexpr uint32_t OFF_REDG = OFF_R0;
constexpr uint32_t OFF_REDS = OFF_R0 + 4096;
constexpr uint32_t OFF_REDU = OFF_R0 + 8192;
constexpr uint32_t OFF_REDV = OFF_R0 + 12288;
constexpr uint32_t OFF_H1 = OFF_R0 + 16384;

constexpr int BAR_FULL = 8;
constexpr int U_WQ = -8, U_WUK = -4, U_WMOD = 40, U_WUV = 42, U_WO = 46, U_W1 = 50, U_W2 = 52, NUNITS = 54;
constexpr int BAR_EMPTY = 62;
constexpr int BAR_GO = 67, BAR_CLR = 68, BAR_EPOCH = 69;
constexpr int BAR_P2E = 70, BAR_P5D = 71, BAR_P7D = 72;
constexpr int BAR_XE = 73;
constexpr int BAR_FM = 74;
constexpr int BAR_WA = 75;
__host__ __device__ constexpr uint32_t BAR(int i) { return OFF_BARS + 8 * i; }
constexpr int PACE_T0 = 608;
constexpr int PACE_DT = 320;
constexpr int PACE_DTE = 328;
constexpr int PACE_DTW = 220;
constexpr int PACE_DT2 = 325;
constexpr int PACE_GAP3 = 140;
constexpr int PACE_DT3 = 400;
constexpr int PACE_DTL = 50;
constexpr int PACE_GAP4 = 100;
constexpr int PACE_DT4 = 440;
constexpr int WIN_PRE = 5;
constexpr int WIN_MID = 8;
constexpr int WIN_END = 6;
constexpr int WIN_TAIL = 5;
constexpr int MOD_AT = 3;
constexpr int D_MOD = 600;
constexpr int D_QP = 1600;
constexpr int QX_AT = 5;
constexpr int D_QX = 1400;
constexpr int CNT_AT = 30;
constexpr int GA_AT = 45;
constexpr int X1_D0 = 1100;
constexpr int D_X2 = 380;
constexpr int D_X3A = 400;
constexpr int D_X3B = 1300;
constexpr int D_GB = 300;
constexpr int D_FIN = 450;
constexpr int D_FIN2 = 2000;
constexpr int CLR_CLK = 220;
constexpr int NPROBE = 3;
constexpr int PAD_D = 0;

struct Scratch {
  uint32_t MODA[1024 * 4];
  uint32_t QP[128 * 256 * 2];
  uint32_t FL[2][128];
  uint32_t QX[2][8 * 32 * 256];
  uint32_t epoch;
  uint32_t pad[31];
  uint32_t cnt;
  alignas(131072) uint32_t X3B[16384];
  uint32_t MODB[16384];
  uint32_t IN[128][16384];
};
__device__ uint8_t g_s[sizeof(Scratch) + 131072];

struct Params {
  CUtensorMap wma, wq, wuk, wmod, ckv, wuv, wo, w1, w2;
};

__device__ __forceinline__ void mbar_init(uint32_t bar, int cnt) { asm volatile("mbarrier.init.shared::cta.b64 [%0], %1;" ::"r"(bar), "r"(cnt)); }
__device__ __forceinline__ void mbar_expect(uint32_t bar, uint32_t bytes) { asm volatile("mbarrier.arrive.expect_tx.shared::cta.b64 _, [%0], %1;" ::"r"(bar), "r"(bytes) : "memory"); }
__device__ __forceinline__ void mbar_arrive(uint32_t bar) { asm volatile("mbarrier.arrive.shared::cta.b64 _, [%0];" ::"r"(bar) : "memory"); }
__device__ __forceinline__ void mbar_arrive_cluster(uint32_t bar) { asm volatile("mbarrier.arrive.shared::cluster.b64 _, [%0];" ::"r"(bar) : "memory"); }
__device__ __forceinline__ bool mbar_test(uint32_t bar) {
  uint32_t ok;
  asm volatile("{\n.reg .pred p;\nmbarrier.test_wait.parity.shared::cta.b64 p, [%1], 0;\nselp.u32 %0,1,0,p;\n}" : "=r"(ok) : "r"(bar) : "memory");
  return ok;
}
__device__ __forceinline__ uint32_t gtime32() { uint32_t c; asm volatile("mov.u32 %0, %%globaltimer_lo;" : "=r"(c) :: "memory"); return c; }
__device__ __forceinline__ uint32_t clk32() { uint32_t c; asm volatile("{\n.reg .u64 t;\nmov.u64 t, %%clock64;\ncvt.u32.u64 %0, t;\n}" : "=r"(c) :: "memory"); return c; }
__device__ __forceinline__ void wait_until(uint32_t c0, int clocks) { if (clocks > 0) while ((int)(clk32() - c0) < clocks) {} }
__device__ __forceinline__ void backoff(int clocks) { if (clocks > 0) wait_until(clk32(), clocks); }
__device__ __forceinline__ uint32_t pin32(uint32_t p) { asm volatile("" : "+r"(p)); return p; }
template <typename T> __device__ __forceinline__ T* pin(T* p) { asm volatile("" : "+l"(p)); return p; }
__device__ __forceinline__ uint32_t hold32(uint32_t p) { asm volatile("shfl.sync.bfly.b32 %0, %0, 0, 0x1f, 0xffffffff;" : "+r"(p) :: "memory"); return p; }
__device__ __forceinline__ float holdf(float p) { return __uint_as_float(hold32(__float_as_uint(p))); }
template <typename T> __device__ __forceinline__ T* hold(T* p) {
  asm volatile("{\n.reg .b32 a, b;\nmov.b64 {a, b}, %0;\nshfl.sync.bfly.b32 a, a, 0, 0x1f, 0xffffffff;\nshfl.sync.bfly.b32 b, b, 0, 0x1f, 0xffffffff;\nmov.b64 %0, {a, b};\n}" : "+l"(p) :: "memory");
  return p;
}
constexpr int SPIN_LIMIT = 1 << 22;
__device__ __forceinline__ void mbar_wait(uint32_t bar) {
  asm volatile("{\n.reg .pred p;\nMW_LOOP:\nmbarrier.try_wait.parity.shared::cta.b64 p, [%0], 0;\n@!p bra MW_LOOP;\n}" ::"r"(bar) : "memory");
}
__device__ __forceinline__ void mbar_wait_b(uint32_t bar) {
  asm volatile("{\n.reg .pred p;\n.reg .u32 c;\nmov.u32 c, 0;\n"
               "MW_LOOP:\nmbarrier.try_wait.parity.shared::cta.b64 p, [%0], 0;\n@p bra MW_DONE;\n"
               "add.u32 c, c, 1;\nsetp.lt.u32 p, c, 1048576;\n@p bra MW_LOOP;\ntrap;\nMW_DONE:\n}"
               ::"r"(bar) : "memory");
}
__device__ __forceinline__ void tma2d(uint32_t dst, const CUtensorMap* m, int c0, int c1, uint32_t bar, uint64_t pol) {
  asm volatile("cp.async.bulk.tensor.2d.shared::cluster.global.mbarrier::complete_tx::bytes.L2::cache_hint [%0], [%1, {%3,%4}], [%2], %5;"
               ::"r"(dst), "l"(m), "r"(bar), "r"(c0), "r"(c1), "l"(pol) : "memory");
}
__device__ __forceinline__ void tma2d_both(uint32_t dst, const CUtensorMap* m, int c0, int c1, uint32_t bar, uint64_t pol) {
  asm volatile("cp.async.bulk.tensor.2d.shared::cluster.global.mbarrier::complete_tx::bytes.multicast::cluster.L2::cache_hint [%0], [%1, {%3,%4}], [%2], %6, %5;"
               ::"r"(dst), "l"(m), "r"(bar), "r"(c0), "r"(c1), "l"(pol), "h"((uint16_t)3) : "memory");
}
__device__ __forceinline__ void tma3d(uint32_t dst, const CUtensorMap* m, int c0, int c1, int c2, uint32_t bar, uint64_t pol) {
  asm volatile("cp.async.bulk.tensor.3d.shared::cluster.global.mbarrier::complete_tx::bytes.L2::cache_hint [%0], [%1, {%3,%4,%5}], [%2], %6;"
               ::"r"(dst), "l"(m), "r"(bar), "r"(c0), "r"(c1), "r"(c2), "l"(pol) : "memory");
}
__device__ __forceinline__ void tma5d(uint32_t dst, const CUtensorMap* m, int c0, int c3, int c4, uint32_t bar, uint64_t pol) {
  asm volatile("cp.async.bulk.tensor.5d.shared::cluster.global.mbarrier::complete_tx::bytes.L2::cache_hint [%0], [%1, {%3,%7,%7,%4,%5}], [%2], %6;"
               ::"r"(dst), "l"(m), "r"(bar), "r"(c0), "r"(c3), "r"(c4), "l"(pol), "r"(0) : "memory");
}
__device__ __forceinline__ void cbar() { asm volatile("bar.sync 1, 256;" ::: "memory"); }
__device__ __forceinline__ void wg0bar() { asm volatile("bar.sync 2, 128;" ::: "memory"); }
__device__ __forceinline__ bool cbar_or(bool p) {
  uint32_t r;
  asm volatile("{\n.reg .pred p, q;\nsetp.ne.u32 p, %1, 0;\nbarrier.cta.red.or.aligned.pred q, 1, 256, p;\nselp.u32 %0, 1, 0, q;\n}" : "=r"(r) : "r"((uint32_t)p) : "memory");
  return r;
}

__device__ __forceinline__ uint32_t ldg_rlx1(const void* p) { uint32_t v; asm volatile("ld.relaxed.gpu.global.u32 %0, [%1];" : "=r"(v) : "l"(p) : "memory"); return v; }
__device__ __forceinline__ void stg4(void* p, uint4 v) { asm volatile("st.relaxed.gpu.global.v4.u32 [%0], {%1,%2,%3,%4};" ::"l"(p), "r"(v.x), "r"(v.y), "r"(v.z), "r"(v.w) : "memory"); }
__device__ __forceinline__ void stg1(void* p, uint32_t a) { asm volatile("st.relaxed.gpu.global.u32 [%0], %1;" ::"l"(p), "r"(a) : "memory"); }
__device__ __forceinline__ uint32_t nz(uint32_t w) { uint32_t r; asm("max.u32 %0, %1, 1;" : "=r"(r) : "r"(w)); return r; }
__device__ __forceinline__ uint32_t min3(uint32_t a, uint32_t b, uint32_t c) { return min(min(a, b), c); }

__device__ __forceinline__ uint32_t pack_bf16(float lo, float hi) { uint32_t r; asm("cvt.rn.bf16x2.f32 %0, %1, %2;" : "=r"(r) : "f"(hi), "f"(lo)); return r; }
__device__ __forceinline__ float bf_lo(uint32_t w) { return __uint_as_float(w << 16); }
__device__ __forceinline__ float bf_hi(uint32_t w) { return __uint_as_float(w & 0xffff0000u); }
__device__ __forceinline__ float ex2(float x) { float r; asm("ex2.approx.ftz.f32 %0, %1;" : "=f"(r) : "f"(x)); return r; }
__device__ __forceinline__ float rcp(float x) { float r; asm("rcp.approx.ftz.f32 %0, %1;" : "=f"(r) : "f"(x)); return r; }
__device__ __forceinline__ float rsq(float x) { float r; asm("rsqrt.approx.ftz.f32 %0, %1;" : "=f"(r) : "f"(x)); return r; }
__device__ __forceinline__ uint32_t silu2(uint32_t c) {
  const float a = bf_lo(c), b = bf_hi(c);
  return pack_bf16(__fdividef(a, 1.f + __expf(-a)), __fdividef(b, 1.f + __expf(-b)));
}
__device__ __forceinline__ uint32_t shl_clamp(uint32_t x, int s) { uint32_t r; asm("shl.b32 %0, %1, %2;" : "=r"(r) : "r"(x), "r"(s)); return r; }

__device__ __forceinline__ void ldsm4(uint32_t (&r)[4], uint32_t a) { asm volatile("ldmatrix.sync.aligned.m8n8.x4.shared.b16 {%0,%1,%2,%3}, [%4];" : "=r"(r[0]), "=r"(r[1]), "=r"(r[2]), "=r"(r[3]) : "r"(a) : "memory"); }
__device__ __forceinline__ void ldsm4t(uint32_t (&r)[4], uint32_t a) { asm volatile("ldmatrix.sync.aligned.m8n8.x4.trans.shared.b16 {%0,%1,%2,%3}, [%4];" : "=r"(r[0]), "=r"(r[1]), "=r"(r[2]), "=r"(r[3]) : "r"(a) : "memory"); }
__device__ __forceinline__ void ldsm2t(uint32_t& r0, uint32_t& r1, uint32_t a) { asm volatile("ldmatrix.sync.aligned.m8n8.x2.trans.shared.b16 {%0,%1}, [%2];" : "=r"(r0), "=r"(r1) : "r"(a) : "memory"); }
__device__ __forceinline__ void stsm4t(uint32_t a, uint32_t r0, uint32_t r1, uint32_t r2, uint32_t r3) { asm volatile("stmatrix.sync.aligned.m8n8.x4.trans.shared.b16 [%0], {%1,%2,%3,%4};" ::"r"(a), "r"(r0), "r"(r1), "r"(r2), "r"(r3) : "memory"); }
__device__ __forceinline__ void stsm2t(uint32_t a, uint32_t r0, uint32_t r1) { asm volatile("stmatrix.sync.aligned.m8n8.x2.trans.shared.b16 [%0], {%1,%2};" ::"r"(a), "r"(r0), "r"(r1) : "memory"); }
__device__ __forceinline__ void mma16816(float (&d)[4], const uint32_t (&a)[4], uint32_t b0, uint32_t b1) {
  asm volatile("mma.sync.aligned.m16n8k16.row.col.f32.bf16.bf16.f32 {%0,%1,%2,%3}, {%4,%5,%6,%7}, {%8,%9}, {%0,%1,%2,%3};"
               : "+f"(d[0]), "+f"(d[1]), "+f"(d[2]), "+f"(d[3]) : "r"(a[0]), "r"(a[1]), "r"(a[2]), "r"(a[3]), "r"(b0), "r"(b1));
}
__device__ __forceinline__ void mma_v(float (&d)[4], const uint4& a, uint32_t b0, uint32_t b1) {
  asm volatile("mma.sync.aligned.m16n8k16.row.col.f32.bf16.bf16.f32 {%0,%1,%2,%3}, {%4,%5,%6,%7}, {%8,%9}, {%0,%1,%2,%3};"
               : "+f"(d[0]), "+f"(d[1]), "+f"(d[2]), "+f"(d[3]) : "r"(a.x), "r"(a.y), "r"(a.z), "r"(a.w), "r"(b0), "r"(b1));
}
__device__ __forceinline__ void sts1(uint32_t a, uint32_t v) { asm volatile("st.shared.u32 [%0], %1;" ::"r"(a), "r"(v) : "memory"); }
__device__ __forceinline__ void sts2(uint32_t a, uint32_t x, uint32_t y) { asm volatile("st.shared.v2.u32 [%0], {%1,%2};" ::"r"(a), "r"(x), "r"(y) : "memory"); }
__device__ __forceinline__ void sts4(uint32_t a, uint4 v) { asm volatile("st.shared.v4.u32 [%0], {%1,%2,%3,%4};" ::"r"(a), "r"(v.x), "r"(v.y), "r"(v.z), "r"(v.w) : "memory"); }
__device__ __forceinline__ void sts4f(uint32_t a, float x, float y, float z, float w) { asm volatile("st.shared.v4.f32 [%0], {%1,%2,%3,%4};" ::"r"(a), "f"(x), "f"(y), "f"(z), "f"(w) : "memory"); }
__device__ __forceinline__ void sts2f(uint32_t a, float x, float y) { asm volatile("st.shared.v2.f32 [%0], {%1,%2};" ::"r"(a), "f"(x), "f"(y) : "memory"); }
__device__ __forceinline__ void stsf(uint32_t a, float v) { asm volatile("st.shared.f32 [%0], %1;" ::"r"(a), "f"(v) : "memory"); }
__device__ __forceinline__ uint32_t lds1(uint32_t a) { uint32_t v; asm volatile("ld.shared.u32 %0, [%1];" : "=r"(v) : "r"(a) : "memory"); return v; }
__device__ __forceinline__ uint2 lds2(uint32_t a) { uint2 v; asm volatile("ld.shared.v2.u32 {%0,%1}, [%2];" : "=r"(v.x), "=r"(v.y) : "r"(a) : "memory"); return v; }
__device__ __forceinline__ float ldsf(uint32_t a) { float v; asm volatile("ld.shared.f32 %0, [%1];" : "=f"(v) : "r"(a) : "memory"); return v; }
__device__ __forceinline__ float2 ldsf2(uint32_t a) { float2 v; asm volatile("ld.shared.v2.f32 {%0,%1}, [%2];" : "=f"(v.x), "=f"(v.y) : "r"(a) : "memory"); return v; }
__device__ __forceinline__ float4 ldsf4(uint32_t a) { float4 v; asm volatile("ld.shared.v4.f32 {%0,%1,%2,%3}, [%4];" : "=f"(v.x), "=f"(v.y), "=f"(v.z), "=f"(v.w) : "r"(a) : "memory"); return v; }
__device__ __forceinline__ uint4 lds4(uint32_t a) { uint4 v; asm volatile("ld.shared.v4.u32 {%0,%1,%2,%3}, [%4];" : "=r"(v.x), "=r"(v.y), "=r"(v.z), "=r"(v.w) : "r"(a) : "memory"); return v; }

__device__ __forceinline__ void wg_fence() { asm volatile("wgmma.fence.sync.aligned;" ::: "memory"); }
__device__ __forceinline__ void wg_commit() { asm volatile("wgmma.commit_group.sync.aligned;" ::: "memory"); }
template <int N> __device__ __forceinline__ void wg_wait() { asm volatile("wgmma.wait_group.sync.aligned %0;" ::"n"(N) : "memory"); }
__host__ __device__ constexpr uint32_t dlo(uint32_t addr) { return (addr >> 4) | 0x10000u; }
constexpr uint32_t ONE2 = 0x3f803f80u;
template <int TA, int ACC> __device__ __forceinline__ void wgmma_ss(float (&d)[16], uint32_t da, uint32_t db) {
  asm volatile("{\n.reg .b64 da, db;\nmov.b64 da, {%16, 0x40000040};\nmov.b64 db, {%17, 0x40000040};\n"
               "wgmma.mma_async.sync.aligned.m64n32k16.f32.bf16.bf16 {%0,%1,%2,%3,%4,%5,%6,%7,%8,%9,%10,%11,%12,%13,%14,%15}, da, db, %18, 1, 1, %19, 0;\n}"
               : "+f"(d[0]), "+f"(d[1]), "+f"(d[2]), "+f"(d[3]), "+f"(d[4]), "+f"(d[5]), "+f"(d[6]), "+f"(d[7]),
                 "+f"(d[8]), "+f"(d[9]), "+f"(d[10]), "+f"(d[11]), "+f"(d[12]), "+f"(d[13]), "+f"(d[14]), "+f"(d[15])
               : "r"(da), "r"(db), "n"(ACC), "n"(TA));
}
template <int TA, int ACC> __device__ __forceinline__ void wgmma_ss(float (&d)[8], uint32_t da, uint32_t db) {
  asm volatile("{\n.reg .b64 da, db;\nmov.b64 da, {%8, 0x40000040};\nmov.b64 db, {%9, 0x40000040};\n"
               "wgmma.mma_async.sync.aligned.m64n16k16.f32.bf16.bf16 {%0,%1,%2,%3,%4,%5,%6,%7}, da, db, %10, 1, 1, %11, 0;\n}"
               : "+f"(d[0]), "+f"(d[1]), "+f"(d[2]), "+f"(d[3]), "+f"(d[4]), "+f"(d[5]), "+f"(d[6]), "+f"(d[7])
               : "r"(da), "r"(db), "n"(ACC), "n"(TA));
}
__device__ __forceinline__ void wgmma_n8(float (&d)[4], uint32_t da, uint32_t db) {
  asm volatile("{\n.reg .b64 da, db;\nmov.b64 da, {%4, 0x40000040};\nmov.b64 db, {%5, 0x40000040};\n"
               "wgmma.mma_async.sync.aligned.m64n8k16.f32.bf16.bf16 {%0,%1,%2,%3}, da, db, 1, 1, 1, 1, 0;\n}"
               : "+f"(d[0]), "+f"(d[1]), "+f"(d[2]), "+f"(d[3]) : "r"(da), "r"(db));
}
template <int K> __device__ __forceinline__ void tie(float (&d)[K]) {
#pragma unroll
  for (int i = 0; i < K; i += 8)
    asm volatile("" : "+f"(d[i]), "+f"(d[i + 1]), "+f"(d[i + 2]), "+f"(d[i + 3]), "+f"(d[i + 4]), "+f"(d[i + 5]), "+f"(d[i + 6]), "+f"(d[i + 7]) :: "memory");
}
__device__ __forceinline__ void tie(uint4& v) { asm volatile("" : "+r"(v.x), "+r"(v.y), "+r"(v.z), "+r"(v.w) :: "memory"); }
__device__ __forceinline__ void tie(uint2& v) { asm volatile("" : "+r"(v.x), "+r"(v.y) :: "memory"); }
template <int N> __device__ __forceinline__ void pad() {
#pragma unroll
  for (int i = 0; i < N; i++) asm volatile("pmevent 0;");
}
template <int I> struct IC { static constexpr int value = I; };
template <int B, int E, typename F> __device__ __forceinline__ void sfor(F&& f) { if constexpr (B < E) { f(IC<B>{}); sfor<B + 1, E>(f); } }

__device__ __forceinline__ uint2 ldg_u64(const void* p) {
  uint2 v; asm volatile("{\n.reg .b64 a;\nld.relaxed.gpu.global.b64 a, [%2];\nmov.b64 {%0,%1}, a;\n}" : "=r"(v.x), "=r"(v.y) : "l"(p) : "memory"); return v;
}
__device__ __forceinline__ uint4 ldg_2u64(const void* p) {
  uint4 v; asm volatile("{\n.reg .b64 a, b;\nld.relaxed.gpu.global.v2.b64 {a, b}, [%4];\nmov.b64 {%0,%1}, a;\nmov.b64 {%2,%3}, b;\n}" : "=r"(v.x), "=r"(v.y), "=r"(v.z), "=r"(v.w) : "l"(p) : "memory"); return v;
}
__device__ __forceinline__ uint4 ldg_u128(const void* p) {
  uint4 v; asm volatile("{\n.reg .b64 a, b;\n.reg .b128 q;\nld.relaxed.gpu.global.b128 q, [%4];\nmov.b128 {a, b}, q;\nmov.b64 {%0,%1}, a;\nmov.b64 {%2,%3}, b;\n}" : "=r"(v.x), "=r"(v.y), "=r"(v.z), "=r"(v.w) : "l"(p) : "memory"); return v;
}
__device__ __forceinline__ void stg_u64(void* p, uint32_t x, uint32_t y) {
  asm volatile("{\n.reg .b64 a;\nmov.b64 a, {%1,%2};\nst.relaxed.gpu.global.b64 [%0], a;\n}" ::"l"(p), "r"(x), "r"(nz(y)) : "memory");
}
__device__ __forceinline__ void stg4_b128(void* p, uint4 v) {
  asm volatile("{\n.reg .b64 a, b;\n.reg .b128 q;\nmov.b64 a, {%1,%2};\nmov.b64 b, {%3,%4};\nmov.b128 q, {a, b};\nst.relaxed.gpu.global.b128 [%0], q;\n}" ::"l"(p), "r"(v.x), "r"(v.y), "r"(v.z), "r"(v.w) : "memory");
}
__device__ __forceinline__ void stg_u128(void* p, uint4 v) {
  asm volatile("{\n.reg .b64 a, b;\n.reg .b128 q;\nmov.b64 a, {%1,%2};\nmov.b64 b, {%3,%4};\nmov.b128 q, {a, b};\nst.relaxed.gpu.global.b128 [%0], q;\n}" ::"l"(p), "r"(v.x), "r"(v.y), "r"(v.z), "r"(nz(v.w)) : "memory");
}
__device__ __forceinline__ uint32_t hmul2(uint32_t a, uint32_t b) { uint32_t r; asm("mul.rn.bf16x2 %0, %1, %2;" : "=r"(r) : "r"(a), "r"(b)); return r; }
__device__ __forceinline__ uint32_t hadd2(uint32_t a, uint32_t b) { uint32_t r; asm("add.rn.bf16x2 %0, %1, %2;" : "=r"(r) : "r"(a), "r"(b)); return r; }
__device__ __forceinline__ uint32_t movm(uint32_t a) { uint32_t d; asm volatile("movmatrix.sync.aligned.m8n8.trans.b16 %0, %1;" : "=r"(d) : "r"(a)); return d; }
__device__ __forceinline__ uint2 ldg_rlx2(const void* p) { uint2 v; asm volatile("ld.relaxed.gpu.global.v2.u32 {%0,%1}, [%2];" : "=r"(v.x), "=r"(v.y) : "l"(p) : "memory"); return v; }
__device__ __forceinline__ uint4 ldg_in4(const void* p) { uint4 v; asm volatile("ld.global.nc.v4.u32 {%0,%1,%2,%3}, [%4];" : "=r"(v.x), "=r"(v.y), "=r"(v.z), "=r"(v.w) : "l"(p) : "memory"); return v; }
__device__ __forceinline__ uint32_t ldg_in1(const void* p) { uint32_t v; asm volatile("ld.global.nc.u32 %0, [%1];" : "=r"(v) : "l"(p)); return v; }

template <typename F> __device__ __forceinline__ void sum4_to_smem(uint2 (&v)[4], const uint32_t* x, const uint32_t* y, uint32_t dst, F&& meanwhile) {
  uint32_t r0, r1;
#pragma unroll 1
  while (true) {
    meanwhile();
#pragma unroll
    for (int i = 0; i < 4; i++) tie(v[i]);
    const bool ok = __all_sync(~0u, min(min3(v[0].y, v[1].y, v[2].y), v[3].y) != 0);
    r0 = pack_bf16((bf_lo(v[0].x) + bf_lo(v[1].x)) + (bf_lo(v[2].x) + bf_lo(v[3].x)), (bf_hi(v[0].x) + bf_hi(v[1].x)) + (bf_hi(v[2].x) + bf_hi(v[3].x)));
    r1 = pack_bf16((bf_lo(v[0].y) + bf_lo(v[1].y)) + (bf_lo(v[2].y) + bf_lo(v[3].y)), (bf_hi(v[0].y) + bf_hi(v[1].y)) + (bf_hi(v[2].y) + bf_hi(v[3].y)));
    sts1(dst, r0);
    sts1(dst + 128, r1);
    if (ok) break;
#pragma unroll
    for (int i = 0; i < 4; i++) v[i] = ldg_u64(((i & 2) ? y : x) + (i & 1) * 512);
  }
}
__device__ __forceinline__ void load_a_t(uint32_t (&a)[8][4], uint32_t box, int wq, int lane) {
  const int mi = lane >> 3, r = lane & 7;
  const uint32_t base = box + (8 * (mi >> 1) + r) * 128 + (((2 * wq + (mi & 1)) ^ r) << 4);
#pragma unroll
  for (int ks = 0; ks < 8; ks++) ldsm4t(a[ks], base + ks * 2048);
}
__device__ __forceinline__ void mma128(float (&d)[4], const uint32_t (&a)[8][4], uint32_t bs) {
  float e[4][4] = {{0.f, 0.f, 0.f, 0.f}, {0.f, 0.f, 0.f, 0.f}, {0.f, 0.f, 0.f, 0.f}, {0.f, 0.f, 0.f, 0.f}};
  uint32_t b[4][4];
#pragma unroll
  for (int kk = 0; kk < 4; kk++) ldsm4t(b[kk], bs + 32 * kk * 16);
#pragma unroll
  for (int kk = 0; kk < 4; kk++) { mma16816(e[(2 * kk) & 3], a[2 * kk], b[kk][0], b[kk][1]); mma16816(e[(2 * kk + 1) & 3], a[2 * kk + 1], b[kk][2], b[kk][3]); }
#pragma unroll
  for (int i = 0; i < 4; i++) d[i] = (e[0][i] + e[1][i]) + (e[2][i] + e[3][i]);
}
template <int NL, typename F> __device__ __forceinline__ void poll_vectors(const uint32_t* p, const uint32_t* q, F&& f) {
  int it = 0;
  bool ok;
  uint4 v[NL];
#pragma unroll
  for (int i = 0; i < NL; i++) v[i] = make_uint4(0, 0, 0, 0);
#pragma unroll 1
  do {
    if (++it > SPIN_LIMIT) __trap();
#pragma unroll
    for (int i = 0; i < NL; i++) if (NL <= 4 || min(v[i].y, v[i].w) == 0) v[i] = ldg_2u64(i < NL / 2 ? p + i * 128 : q + (i - NL / 2) * 128);
    f(v);
    uint32_t m0 = min(v[0].y, v[0].w), m1 = min(v[1].y, v[1].w);
#pragma unroll
    for (int i = 2; i < NL; i += 2) { m0 = min3(m0, v[i].y, v[i].w); m1 = min3(m1, v[i + 1].y, v[i + 1].w); }
    ok = __all_sync(~0u, min(m0, m1) != 0);
  } while (!ok);
}

__global__ void __cluster_dims__(2, 1, 1) __launch_bounds__(NTHREADS, 1)
fused_decode_kernel(__nv_bfloat16* __restrict__ gout, Scratch* __restrict__ gs, const uint8_t* __restrict__ gwq,
                    const uint8_t* __restrict__ gx, const uint8_t* __restrict__ gc,
                    const __grid_constant__ Params P) {
  extern __shared__ __align__(1024) uint8_t smem_raw[];
  const uint32_t hi = pin32((uint32_t)__cvta_generic_to_shared(smem_raw) - SB);
  const int tid = threadIdx.x, lane = tid & 31;
  const int w = __shfl_sync(0xffffffffu, tid >> 5, 0);
  const int cta = blockIdx.x;
  const int g = lane >> 2, t = lane & 3;
  const int hI = cta >> 2, jI = cta & 3;
  const int bI = cta >> 4, pI = (cta >> 1) & 7, rI = cta & 1;

  uint32_t epoch0 = 0;
  if (tid == 320) epoch0 = ldg_rlx1(&gs->epoch);
  const bool p0a = (cta & 7) == 0;
  uint4 cw0, cw1, xr0, xr1;
  uint32_t xc;
  if (w < 8) {
    const uint8_t* src = gwq + (size_t)(128 * jI + (tid >> 4)) * 8192 + hI * 256 + (tid & 15) * 16;
    const uint32_t dst = hi + OFF_R1 + ((tid >> 3) & 1) * 16384 + (tid >> 4) * 128 + (((tid ^ (tid >> 4)) & 7) << 4);
    if (p0a) {
      cw0 = ldg_in4(gc + g * 1024 + w * 128 + t * 32); cw1 = ldg_in4(gc + g * 1024 + w * 128 + t * 32 + 16);
      xr0 = ldg_in4(gx + w * 1024 + lane * 16); xr1 = ldg_in4(gx + w * 1024 + 512 + lane * 16);
      xc = ldg_in1(gx + w * 1024 + (cta & 63) * 16 + lane * 4);
    } else {
#pragma unroll
      for (int i = 0; i < 4; i++) asm volatile("cp.async.cg.shared.global [%0], [%1], 16;" ::"r"(dst + i * 2048), "l"(src + i * 16 * 8192) : "memory");
    }
  }
  auto half_of = [&](int c, int k) { return ((lds1(hi + OFF_FM + (c >> 5) * 4) >> (c & 31)) ^ k) & 1; };
  auto inbox = [&](int c, int k, uint32_t bits, int pos, int off) { return gs->IN[0] + (uint32_t)(c * 16384 + k * 2048 + off + (((bits >> pos) & 1) << 10)); };
  auto front_unit = [&](int k, uint64_t pol) {
    tma2d(hi + OFF_R1 + ((k & 4) + 2 * (k & 1) + ((k >> 1) & 1)) * 8192, k < 4 ? &P.wq : &P.wuk, 128 * hI + 64 * (k & 1), 128 * jI + 64 * ((k >> 1) & 1), hi + BAR(k), pol);
  };
  uint32_t tnext = 0;
  if (tid == 256) {
    tnext = gtime32() + PACE_T0;
    if (hi & 0xffffff) __trap();
    if (p0a) {
#pragma unroll
      for (int i = 0; i < 4; i++) mbar_init(hi + BAR(BAR_WA + i), 1);
      asm volatile("fence.mbarrier_init.release.cluster;" ::: "memory");
      uint64_t pol; asm volatile("createpolicy.fractional.L2::evict_first.b64 %0, 1.0;" : "=l"(pol));
#pragma unroll
      for (int i = 0; i < 4; i++) tma2d(hi + slot(8 + 2 * i), &P.wma, 8 * cta, 128 * i, hi + BAR(BAR_WA + i), pol);
    }
    asm volatile("prefetch.tensormap [%0];" ::"l"(&P.wq) : "memory");
  } else if (tid == 288) {
#pragma unroll
    for (int i = 0; i < BAR_WA; i++)
      mbar_init(hi + BAR(i), (i >= BAR_EMPTY && i < BAR_EMPTY + 5) ? 16 : (i >= BAR_P2E && i <= BAR_P7D) ? 8 : 1);
    asm volatile("fence.mbarrier_init.release.cluster;" ::: "memory");
  }
  __syncthreads();

  if (w == 8) {
    auto twice = [](int n) { return (n & ~1) == U_W1 || (n & ~1) == U_WMOD; };
    if (p0a && lane < 4) mbar_expect(hi + BAR(BAR_WA) + 8 * lane, 16384);
    mbar_expect(hi + BAR(0) + 8 * lane, (lane < 2 && !p0a) ? 0 : 8192);
    if (p0a) tnext -= 2 * PACE_DT;
    if (lane < BAR_EMPTY - 32) mbar_expect(hi + BAR(32) + 8 * lane, twice(32 + lane - BAR_FULL) ? 16384 : 8192);
    __syncwarp();
    const int h = hI, j = jI;
    if (lane == 0) {
      uint64_t pol; asm volatile("createpolicy.fractional.L2::evict_first.b64 %0, 1.0;" : "=l"(pol));
      auto pace = [&](int dt) { while ((int)(gtime32() - tnext) < 0) {} tnext += dt; };
      asm volatile("prefetch.tensormap [%0];" ::"l"(&P.wuk) : "memory");
      asm volatile("prefetch.tensormap [%0];" ::"l"(&P.wmod) : "memory");
      asm volatile("prefetch.tensormap [%0];" ::"l"(&P.ckv) : "memory");
#pragma unroll 1
      for (int k = p0a ? 0 : 2; k < 8; k++) { if (k >= WIN_PRE) mbar_wait(hi + BAR(0) + 8 * (k - WIN_PRE)); pace(PACE_DT); front_unit(k, pol); }
      bool go = false;
      const int row0 = bI * 4096 + (cta & 15) * 64;
#pragma unroll 1
      for (int n = 0; n < 24; n++) {
        if (n == 8) mbar_wait(hi + BAR(BAR_P2E));
        if (n == 23) mbar_wait(hi + BAR(BAR_EMPTY));
        if (!go) go = mbar_test(hi + BAR(BAR_GO));
        mbar_wait(hi + BAR(BAR_FULL) + 8 * (n - (go ? WIN_MID : WIN_PRE)));
        pace(PACE_DT);
        tma2d(hi + slot(box_slot(n)), &P.ckv, (n & 7) * 64, row0 + (n >> 3) * 1024, hi + BAR(BAR_FULL) + 8 * n, pol);
      }
      asm volatile("prefetch.tensormap [%0];" ::"l"(&P.wuv) : "memory");
      asm volatile("prefetch.tensormap [%0];" ::"l"(&P.wo) : "memory");
      asm volatile("prefetch.tensormap [%0];" ::"l"(&P.w1) : "memory");
      asm volatile("prefetch.tensormap [%0];" ::"l"(&P.w2) : "memory");
      const int row1 = bI * 4096 + (24 + pI) * 64;
      tnext += rI * (PACE_DT / 2) - PACE_DT / 4;
#pragma unroll 1
      for (int n = 24 + rI; n < 40; n += 2) {
        const int c = n - 23;
        const int m = c >= 2 * WIN_END ? n - 2 * WIN_END : 23 - (2 * WIN_END - c) / 2;
        mbar_wait(hi + BAR(BAR_FULL) + 8 * m);
        mbar_wait(hi + BAR(BAR_EMPTY) + (c & ~7));
        pace(PACE_DTE);
        tma2d_both(hi + slot(c), &P.ckv, (n & 7) * 64, row1 + (n >> 3) * 512, hi + BAR(BAR_FULL) + 8 * n, pol);
      }
      mbar_wait(hi + BAR(BAR_EMPTY + 2));
      const bool late = cta >= 96;
      auto unit = [&](int i) { return (!late || i < U_WMOD || i >= U_W1) ? i : i < U_W1 - 2 ? i + 2 : i - 8; };
      if (late) tnext += 2 * PACE_DTW;
#pragma unroll 1
      for (int i = U_WMOD; i < (cta < NFF ? NUNITS : U_W1); i++) {
        const int n = unit(i), c = i - 39, u = n & 1;
        mbar_wait(hi + BAR(BAR_FULL) + 8 * (c >= WIN_TAIL ? unit(i - WIN_TAIL) : 39 - 2 * (WIN_TAIL - c)));
        if (n == U_WUV) mbar_wait(hi + BAR(BAR_EMPTY + 3));
        if (n == U_WO) tnext += PACE_GAP3;
        if (n == U_W1) { mbar_wait(hi + BAR(BAR_EMPTY + 4)); tnext += PACE_GAP4; }
        const uint32_t bar = hi + BAR(BAR_FULL) + 8 * n;
        pace(n < U_WUV ? (late ? PACE_DTL : PACE_DTW) : n < U_WO ? PACE_DT2 : n < U_W1 ? PACE_DT3 : PACE_DT4);
        if (twice(n)) tma2d_both(hi + (n < U_WO ? OFF_WM : OFF_W1) + (2 * u + rI) * 8192, n < U_WO ? &P.wmod : &P.w1, (n < U_WO ? 1024 : 0) + 16 * (cta & ~1), 256 * u + 128 * rI, bar, pol);
        else if (n < U_WO) tma5d(hi + slot(n - 41), &P.wuv, 128 * h + 64 * u, (n - U_WUV) & 2, 2 * j, bar, pol);
        else if (n < U_W1) tma2d(hi + slot(n - 41), &P.wo, 128 * j + 64 * u, 128 * h + 32 * ((n - U_WO) & 2), bar, pol);
        else tma3d(hi + OFF_W2 + u * 8192, &P.w2, 0, FCH * cta, 4 * u, bar, pol);
      }
    }
    return;
  }

  if (w == 11) {
    const uint4 z = make_uint4(0, 0, 0, 0);
    uint32_t f = 0, f2 = 0;
    {
      uint32_t* const p = ((lane & 2) ? gs->X3B + 4 * 2048 + cta * 8 : gs->IN[cta] + 4 * 2048 + 960) + ((lane & 1) << 10);
      if (lane < 8) stg4(p + (lane & 4), z);
      __syncwarp();
      uint32_t best = ~0u;
#pragma unroll 1
      for (int i = 0; i < 4 * NPROBE + (int)(hi & 1); i++) {
        uint32_t v = 0;
        const uint32_t c0 = clk32();
        if (lane == (i & 3)) asm volatile("atom.relaxed.gpu.global.exch.b32 %0, [%1], %2;" : "=r"(v) : "l"(p), "r"(i) : "memory");
        v = __shfl_sync(~0u, v, i & 3);
        const uint32_t dt = clk32() - c0 + (v >> 31);
        if (lane == (i & 3)) best = min(best, dt);
      }
      const uint32_t m = __ballot_sync(~0u, best < __shfl_xor_sync(~0u, best, 1));
      f = (m >> 1) & 1; f2 = (m >> 3) & 1;
    }
    mbar_wait(hi + BAR(BAR_EPOCH));
    const uint32_t epoch = lds1(hi + OFF_EPOCH);
    const int par = epoch & 1;
    if (lane == 0) stg1(gs->FL[par] + cta, 1 + f);
    mbar_wait(hi + BAR(BAR_P2E));
#pragma unroll 1
    for (int i = 0; i < 16; i++) {
      const uint32_t c0 = clk32();
      uint32_t* p = gs->IN[cta] + (i >> 1) * 2048 + (((f ^ (i >> 1)) & 1) << 10) + (i & 1) * 512 + lane * 4;
#pragma unroll
      for (int q = 0; q < 4; q++) stg4(p + q * 128, z);
      if (i == 0 && lane < 16) stg4(gs->X3B + cta * 64 + lane * 4, z);
      if (i == 1) stg4(gs->MODB + cta * 128 + lane * 4, z);
      wait_until(c0, CLR_CLK);
    }
    {
      uint32_t u[4];
      do {
#pragma unroll
        for (int i = 0; i < 4; i++) u[i] = ldg_rlx1(gs->FL[par] + 32 * i + lane);
      } while (!__all_sync(~0u, min(min(u[0], u[1]), min(u[2], u[3])) != 0));
      const uint4 m = make_uint4(__ballot_sync(~0u, u[0] == 2), __ballot_sync(~0u, u[1] == 2), __ballot_sync(~0u, u[2] == 2), __ballot_sync(~0u, u[3] == 2));
      if (lane == 0) { sts4(hi + OFF_FM, m); sts1(hi + OFF_FM + 16, f2); }
      __syncwarp();
      const uint2 m2 = lds2(hi + OFF_FM + 8 * rI);
      const uint32_t mh = (lds1(hi + OFF_FM + (hI >> 3) * 4) >> (4 * (hI & 7))) & 15;
#pragma unroll 1
      for (int v = 0; v < 8; v++) {
        const int sh = 8 * t + 2 * (v >> 2) + (bI >> 2);
        uint32_t fb = (((m2.x >> sh) & 0x11) | (((m2.y >> sh) & 0x11) << 1)) ^ ((bI & 1) ? 0x33 : 0);
        fb |= mh << 8;
        fb |= half_of(4 * (8 * jI + v) + (g >> 1), 0) << 12;
        fb |= half_of((16 * rI + 4 * (v & 3) + (lane >> 3)) * 4 + (lane & 2), 0) << 13;
        fb |= ((f2 ^ (v >> 2)) & 1) << 14;
        fb |= (((lds1(hi + OFF_FM + (v >> 1) * 4) >> (16 * (v & 1) + (g >> 1))) & 0x1111) ^ (cta >= 56 ? 0x1111 : 0)) << 16;
        sts1(hi + OFF_FB + (v * 32 + lane) * 4, fb);
      }
      __syncwarp();
      if (lane == 0) mbar_arrive(hi + BAR(BAR_FM));
    }
    asm volatile("fence.acq_rel.gpu;" ::: "memory");
    __syncwarp();
    if (lane == 0) asm volatile("red.relaxed.gpu.global.add.u32 [%0], 1;" ::"l"(&gs->cnt) : "memory");
    mbar_wait(hi + BAR(BAR_GO));
    if (lane == 0) stg1(gs->FL[par ^ 1] + cta, 0u);
#pragma unroll
    for (int i = 0; i < 4; i++) stg4(gs->QP + cta * 512 + (i * 32 + lane) * 4, z);
#pragma unroll
    for (int i = 0; i < 4; i++) stg4(gs->QX[par ^ 1] + cta * 512 + (i * 32 + lane) * 4, z);
    if (lane < 8) stg4(gs->MODA + cta * 32 + lane * 4, z);
    mbar_wait(hi + BAR(BAR_FULL + CNT_AT));
    while ((int)(ldg_rlx1(&gs->cnt) - (epoch + 1) * NCTA) < 0) __nanosleep(100);
    if (lane == 0) mbar_arrive(hi + BAR(BAR_CLR));
    return;
  }
  if (w == 10) {
    const int m0 = 16 * hI + 2 * jI;
    const int bo = lane & 7;
    const uint32_t epoch = __shfl_sync(~0u, epoch0, 0);
    if (lane == 0) { sts1(hi + OFF_EPOCH, epoch); mbar_arrive(hi + BAR(BAR_EPOCH)); }
    pad<PAD_D>();
    mbar_wait_b(hi + BAR(BAR_GO));
    const uint32_t xw0 = hold32(ldg_in1(gx + bo * 1024 + m0 * 2)), xw1 = hold32(ldg_in1(gx + bo * 1024 + m0 * 2 + 16));
    mbar_wait_b(hi + BAR(BAR_CLR));
    const uint32_t* MOD = gs->MODB + (m0 >> 8) * 1024 + ((~(lds1(hi + OFF_FM + 16) ^ (m0 >> 8)) & 1) << 10);
    mbar_wait_b(hi + BAR(BAR_FULL + GA_AT));
    const int mf = m0 + ((g >> 1) & 1) + 8 * (t >> 1), bf = 2 * (g & 1) + (t & 1);
    float ga[4];
    uint32_t gb2;
    {
      uint32_t u[4];
      int it = 0;
      while (true) {
#pragma unroll
        for (int i = 0; i < 4; i++) u[i] = ldg_rlx1(MOD + (m0 + (i & 1) + 8 * (i >> 1)) * 4 + (bo >> 1));
        if (min(min3(u[0], u[1], u[2]), u[3]) != 0) break;
        if (++it > SPIN_LIMIT) __trap();
      }
#pragma unroll
      for (int i = 0; i < 4; i++) ga[i] = (bo & 1) ? bf_hi(u[i]) : bf_lo(u[i]);
    }
    uint32_t x2a, x2b;
    mbar_wait_b(hi + BAR(BAR_FM));
    const uint32_t fo_ = half_of(cta, 0);
    {
      const uint32_t* const pi = hold(inbox(cta, 6, fo_, 0, (4 * (g >> 1) + t) * 8 + (g & 1) * 4));
      uint32_t* const po = hold(gs->X3B + (g >> 2) * 4096 + (cta >> 6) * 2048 + ((g >> 1) & 1) * 1024 + (cta & 63) * 16 + bo * 2);
      const uint32_t one = 0x3f80u << (8 * (g & 2)), s0 = g < 4 ? one : 0u, s1 = g < 4 ? 0u : one;
      const uint32_t e0 = hold32((g & 1) ? 0u : s0), e1 = hold32((g & 1) ? 0u : s1), o0 = hold32((g & 1) ? s0 : 0u), o1 = hold32((g & 1) ? s1 : 0u);
      const float xf[4] = {holdf(bf_lo(xw0)), holdf(bf_hi(xw0)), holdf(bf_lo(xw1)), holdf(bf_hi(xw1))};
#pragma unroll
      for (int i = 0; i < 4; i++) ga[i] = holdf(ga[i]);
      mbar_wait_b(hi + BAR(BAR_P5D));
      backoff(D_X3A);
      float d[4][4];
      poll_vectors<4>(pi, pi + 256, [&](const uint4 (&v)[4]) {
#pragma unroll
        for (int i = 0; i < 4; i++) { d[i][0] = d[i][1] = d[i][2] = d[i][3] = 0.f; mma_v(d[i], v[i], (i & 2) ? o0 : e0, (i & 2) ? o1 : e1); }
      });
      float s[4] = {d[0][0] + d[1][0], d[2][1] + d[3][1], d[0][2] + d[1][2], d[2][3] + d[3][3]};
#pragma unroll
      for (int i = 0; i < 4; i++) s[i] += __shfl_xor_sync(~0u, s[i], 8);
#pragma unroll
      for (int i = 0; i < 4; i++) s[i] += __shfl_xor_sync(~0u, s[i], 16);
      x2a = pack_bf16(xf[0] + ga[0] * s[0], xf[1] + ga[1] * s[1]);
      x2b = pack_bf16(xf[2] + ga[2] * s[2], xf[3] + ga[3] * s[3]);
      stg_u64(po, x2a, x2b);
      mbar_wait(hi + BAR(BAR_P5D));
    }
    {
      const uint32_t ckf = clk32();
      backoff(D_GB);
      int it = 0;
      do { gb2 = ldg_rlx1(MOD + 6 * 2048 + mf * 4 + bf); if (++it > SPIN_LIMIT) __trap(); } while (!__all_sync(~0u, gb2 != 0));
      const uint32_t a0 = __shfl_sync(~0u, x2a, 2 * bf), a1 = __shfl_sync(~0u, x2a, 2 * bf + 1);
      const uint32_t b0 = __shfl_sync(~0u, x2b, 2 * bf), b1 = __shfl_sync(~0u, x2b, 2 * bf + 1);
      const uint32_t y0 = (t & 2) ? b0 : a0, y1 = (t & 2) ? b1 : a1;
      const float r0 = holdf((g & 2) ? bf_hi(y0) : bf_lo(y0)), r1 = holdf((g & 2) ? bf_hi(y1) : bf_lo(y1)), gb0 = holdf(bf_lo(gb2)), gb1 = holdf(bf_hi(gb2));
      const uint32_t* const pi = hold(inbox(cta, 4, fo_, 0, (4 * (g >> 2) + t) * 16 + (g & 3) * 4));
      const uint32_t* const pj = hold(inbox(cta, 5, ~fo_, 0, (4 * (g >> 2) + t) * 16 + (g & 3) * 4));
      __nv_bfloat16* const fo = hold(gout + (2 * bf) * 512 + mf);
      const uint32_t one = (g & 1) ? 0x3f800000u : 0x00003f80u;
      const uint32_t s0 = hold32((g & 2) ? 0u : one), s1 = hold32((g & 2) ? one : 0u);
      if (cta < NFF) { mbar_wait_b(hi + BAR(BAR_P7D)); backoff(D_FIN); } else wait_until(ckf, D_FIN2);
      float d[4][4];
      poll_vectors<NFF / 8>(pi, pj, [&](const uint4 (&v)[NFF / 8]) {
#pragma unroll
        for (int i = 0; i < 4; i++) d[i][0] = d[i][1] = d[i][2] = d[i][3] = 0.f;
#pragma unroll
        for (int i = 0; i < NFF / 8; i++) mma_v(d[i & 3], v[i], s0, s1);
      });
      const bool up = t & 2;
      float v0 = up ? (d[0][2] + d[1][2]) + (d[2][2] + d[3][2]) : (d[0][0] + d[1][0]) + (d[2][0] + d[3][0]);
      float v1 = up ? (d[0][3] + d[1][3]) + (d[2][3] + d[3][3]) : (d[0][1] + d[1][1]) + (d[2][1] + d[3][1]);
      v0 += __shfl_xor_sync(~0u, v0, 16);
      v1 += __shfl_xor_sync(~0u, v1, 16);
      if (g < 4) {
        asm volatile("st.global.u16 [%0], %1;" ::"l"(fo), "h"(__bfloat16_as_ushort(__float2bfloat16(r0 + gb0 * v0))) : "memory");
        asm volatile("st.global.u16 [%0], %1;" ::"l"(fo + 512), "h"(__bfloat16_as_ushort(__float2bfloat16(r1 + gb1 * v1))) : "memory");
      }
    }
    if (cta == 0 && lane == 0) stg1(&gs->epoch, epoch + 1);
    return;
  }

  if (w == 9) {
    uint32_t cf[16][4];
    asm volatile("bar.sync 3, 288;" ::: "memory");
#pragma unroll
    for (int i = 0; i < 16; i++) ldsm4(cf[i], hi + OFF_R0 + (i >> 1) * 1024 + (lane & 7) * 128 + (((4 * (i & 1) + (lane >> 3)) ^ (lane & 7)) << 4));
#pragma unroll
    for (int i = 0; i < 16; i++) cf[i][0] = hold32(cf[i][0]);
    asm volatile("bar.arrive 2, 288;" ::: "memory");
    if (lane == 0) mbar_expect(hi + BAR(BAR_XE), 16384 + 128);
    {
      uint32_t* const mo = gs->MODB + (cta >> 4) * 2048 + (cta & 15) * 64 + lane;
      mbar_wait(hi + BAR(BAR_CLR));
      const uint32_t base = hi + OFF_WM + (8 * (lane >> 4) + (lane & 7)) * 64 + (((2 * rI + ((lane >> 3) & 1)) ^ ((lane & 7) >> 1)) << 4);
      float d[4][4] = {{0.f, 0.f, 0.f, 0.f}, {0.f, 0.f, 0.f, 0.f}, {0.f, 0.f, 0.f, 0.f}, {0.f, 0.f, 0.f, 0.f}};
#pragma unroll
      for (int q = 0; q < 4; q++) {
        if (!(q & 1)) mbar_wait(hi + BAR(BAR_FULL + U_WMOD + (q >> 1)));
        uint32_t a[8][4];
#pragma unroll
        for (int ks = 0; ks < 8; ks++) ldsm4t(a[ks], base + (8 * q + ks) * 1024);
#pragma unroll
        for (int ks = 0; ks < 8; ks++) mma16816(d[ks & 3], a[ks], cf[4 * q + (ks >> 1)][2 * (ks & 1)], cf[4 * q + (ks >> 1)][2 * (ks & 1) + 1]);
      }
      const uint32_t y0 = nz(pack_bf16((d[0][0] + d[1][0]) + (d[2][0] + d[3][0]), (d[0][1] + d[1][1]) + (d[2][1] + d[3][1])));
      const uint32_t y1 = nz(pack_bf16((d[0][2] + d[1][2]) + (d[2][2] + d[3][2]), (d[0][3] + d[1][3]) + (d[2][3] + d[3][3])));
      stg1(mo, y0); stg1(mo + 32, y1);
      stg1(mo + 1024, y0); stg1(mo + 1056, y1);
    }
    return;
  }

  const int wg = w >> 2, wq = w & 3;
  if (!p0a) {
    asm volatile("cp.async.wait_all;" ::: "memory");
    cw0 = ldg_in4(gc + g * 1024 + w * 128 + t * 32); cw1 = ldg_in4(gc + g * 1024 + w * 128 + t * 32 + 16);
  }
  sts4(hi + OFF_R0 + w * 1024 + g * 128 + (((2 * t) ^ g) << 4), make_uint4(silu2(cw0.x), silu2(cw0.y), silu2(cw0.z), silu2(cw0.w)));
  sts4(hi + OFF_R0 + w * 1024 + g * 128 + (((2 * t + 1) ^ g) << 4), make_uint4(silu2(cw1.x), silu2(cw1.y), silu2(cw1.z), silu2(cw1.w)));
  asm volatile("bar.arrive 3, 288;" ::: "memory");
  if (p0a) {
    asm volatile("fence.proxy.async.shared::cta;" ::: "memory");
  {
    float v[16];
    const uint32_t u[8] = {xr0.x, xr0.y, xr0.z, xr0.w, xr1.x, xr1.y, xr1.z, xr1.w};
#pragma unroll
    for (int i = 0; i < 8; i++) { v[2 * i] = bf_lo(u[i]); v[2 * i + 1] = bf_hi(u[i]); }
    float s = (((v[0] + v[1]) + (v[2] + v[3])) + ((v[4] + v[5]) + (v[6] + v[7]))) + (((v[8] + v[9]) + (v[10] + v[11])) + ((v[12] + v[13]) + (v[14] + v[15])));
#pragma unroll
    for (int o = 16; o; o >>= 1) s += __shfl_xor_sync(~0u, s, o);
    const float mu = s * (1.f / 512.f);
    float q0 = 0.f, q1 = 0.f;
#pragma unroll
    for (int i = 0; i < 8; i++) { const float a = v[2 * i] - mu, b = v[2 * i + 1] - mu; q0 += a * a; q1 += b * b; }
    float q = q0 + q1;
#pragma unroll
    for (int o = 16; o; o >>= 1) q += __shfl_xor_sync(~0u, q, o);
    const float rs = rsqrtf(q * (1.f / 512.f) + 1e-5f);
    asm volatile("st.shared.u16 [%0], %1;" ::"r"(hi + OFF_P0S + lane * 32 + w * 2), "h"(__bfloat16_as_ushort(__float2bfloat16((bf_lo(xc) - mu) * rs))) : "memory");
    asm volatile("st.shared.u16 [%0], %1;" ::"r"(hi + OFF_P0S + lane * 32 + 16 + w * 2), "h"(__bfloat16_as_ushort(__float2bfloat16((bf_hi(xc) - mu) * rs))) : "memory");
  }
    cbar();
  }
  if (p0a && wg == 0) {
    uint32_t* const mo = gs->MODA + cta * 32 + wq * 64 + lane;
    const uint32_t xn0 = lds1(hi + OFF_P0S + wq * 256 + lane * 4), xn1 = lds1(hi + OFF_P0S + wq * 256 + 128 + lane * 4);
    float d[4] = {0.f, 0.f, 0.f, 0.f};
    asm volatile("" : "+f"(d[0]), "+f"(d[1]), "+f"(d[2]), "+f"(d[3]) :: "memory");
#pragma unroll 1
    for (int i = 0; i < 4; i++) {
      mbar_wait(hi + BAR(BAR_WA) + 8 * i);
      wg_fence();
#pragma unroll
      for (int ks = 0; ks < 8; ks++) wgmma_n8(d, dlo(slot(8)) + i * 1024 + ks * 128, dlo(OFF_R0) + i * 128 + (ks >> 2) * 64 + (ks & 3) * 2);
      wg_commit();
    }
    wg_wait<0>();
    asm volatile("" : "+f"(d[0]), "+f"(d[1]), "+f"(d[2]), "+f"(d[3]) :: "memory");
    uint32_t y0 = pack_bf16(d[0], d[1]), y1 = pack_bf16(d[2], d[3]);
    if (cta >= 64) { y0 = hmul2(xn0, hadd2(y0, ONE2)); y1 = hmul2(xn1, hadd2(y1, ONE2)); }
    stg1(mo, nz(y0));
    stg1(mo + 32, nz(y1));
  }
  cbar();
  {
    uint32_t* const qpo = pin(gs->QP + (cta * 256 + tid) * 2);
    const uint32_t* const modi = pin(gs->MODA + 512 * jI + tid * 2);
    uint32_t a[8][4];
    mbar_wait(hi + BAR(BAR_FULL + U_WQ) + 8 * wg); mbar_wait(hi + BAR(BAR_FULL + U_WQ + 2) + 8 * wg);
    load_a_t(a, hi + OFF_R1 + wg * 16384, wq, lane);
    mbar_wait(hi + BAR(BAR_FULL + U_WQ + MOD_AT));
    backoff(D_MOD);
    uint2 sa, ca;
    do { sa = ldg_rlx2(modi); ca = ldg_rlx2(modi + 2048); } while (min(min(sa.x, sa.y), min(ca.x, ca.y)) == 0);
    sts2(hi + OFF_BS + tid * 8, hadd2(ca.x, sa.x), hadd2(ca.y, sa.y));
    cbar();
    float d[4];
    mma128(d, a, hi + OFF_BS + lane * 16);
    stg_u64(qpo, pack_bf16(d[0], d[1]), pack_bf16(d[2], d[3]));
  }
  const uint32_t ckq = clk32();
  mbar_wait(hi + BAR(BAR_EPOCH));
  const int par = lds1(hi + OFF_EPOCH) & 1;
  uint32_t* const QX = gs->QX[par];
  {
    uint32_t a[8][4];
    {
      const int mi = lane >> 3, r = lane & 7;
      const int row = 16 * w + 8 * (mi & 1) + r;
      mbar_wait(hi + BAR(BAR_FULL + U_WUK) + 16 * wg); mbar_wait(hi + BAR(BAR_FULL + U_WUK + 1) + 16 * wg);
#pragma unroll
      for (int ks = 0; ks < 8; ks++) {
        const int chunk = 2 * ks + (mi >> 1);
        ldsm4(a[ks], hi + OFF_R2 + (ks >> 2) * 16384 + row * 128 + (((chunk & 7) ^ r) << 4));
      }
    }
    uint32_t* const qxo = pin(QX + ((lane >> 1) * 32 + hI) * 256 + (128 * jI + 16 * w + 8 * (lane & 1)) / 2);
    const uint32_t* const qpi = pin(gs->QP + (hI * 4 * 256 + tid) * 2);
    mbar_wait(hi + BAR(BAR_FULL - 1));
    wait_until(ckq, D_QP);
    uint2 qp[4];
#pragma unroll
    for (int i = 0; i < 4; i++) qp[i] = ldg_u64(qpi + i * 512);
    sum4_to_smem(qp, qpi, qpi + 1024, hi + OFF_BS2 + (16 * w + g) * 16 + t * 4, [] {});
    cbar();
    float d[4];
    mma128(d, a, hi + OFF_BS2 + lane * 16);
    const float sc = 0.08838834764831845f * 1.4426950408889634f;
    const uint32_t stg = hi + OFF_P0S + 4096 + w * 256;
    stsm2t(stg + (lane & 7) * 32 + ((lane >> 3) & 1) * 16, pack_bf16(d[0] * sc, d[1] * sc), pack_bf16(d[2] * sc, d[3] * sc));
    __syncwarp();
    if (lane < 16) stg_u128(qxo, lds4(stg + lane * 16));
    if (lane == 0) mbar_arrive(hi + BAR(BAR_P2E));
  }
  const uint32_t ckx = clk32();
  uint32_t fb = 0;
  {
    const uint32_t* qx = pin(QX + bI * 8192 + w * 1024 + lane * 4);
    mbar_wait(hi + BAR(BAR_FULL + QX_AT));
    wait_until(ckx, D_QX);
    uint4 v[8];
#pragma unroll
    for (int i = 0; i < 8; i++) v[i] = ldg_u128(qx + i * 128);
    asm volatile("bar.sync 2, 288;" ::: "memory");
    while (true) {
      bool all = true;
#pragma unroll
      for (int i = 0; i < 8; i++) all = all && v[i].w != 0;
      if (all) break;
#pragma unroll
      for (int i = 0; i < 8; i++) if (v[i].w == 0) v[i] = ldg_u128(qx + i * 128);
    }
#pragma unroll
    for (int i = 0; i < 8; i++) {
      const int hh = (4 * w + (i >> 1)) ^ (16 * rI), ch = 32 * (i & 1) + lane;
      sts4(hi + OFF_R0 + (ch >> 3) * 4096 + hh * 128 + (((ch & 7) ^ (hh & 7)) << 4), v[i]);
    }
    asm volatile("fence.proxy.async.shared::cta;" ::: "memory");
    cbar();
    if (tid == 0) mbar_arrive(hi + BAR(BAR_GO));
  }

  uint32_t ck1;
  const uint32_t *px, *pm;
  uint32_t *x2o, *x2p;
  {
    float O32[4][16], O16[4][8];
    uint32_t ebar;
    asm("mapa.shared::cluster.u32 %0, %1, %2;" : "=r"(ebar) : "r"(hi + BAR(BAR_EMPTY)), "r"(rI ^ (lane & 1)));
#pragma unroll
    for (int i = 0; i < 16; i++) O32[0][i] = O32[1][i] = O32[2][i] = O32[3][i] = 0.f;
#pragma unroll
    for (int i = 0; i < 4; i++) tie(O32[i]);
    auto pv2 = [&](int T, int WG, auto& O, int mb, int k0, int k1) {
      const int n = 8 * T + 4 * WG + mb;
      const uint32_t da = dlo(SB) + (sizeof(O[0]) == 64 ? n : n - 23) * 512, db = (WG && mb && T == 2) ? dlo(SB) : da + 512, dp = dlo(OFF_PT) + (T & 1) * 256;
#pragma unroll
      for (int ks = k0; ks < k1; ks++) { wgmma_ss<1, 1>(O[mb], da + ks * 128, dp + ks * 2); wgmma_ss<1, 1>(O[mb + 1], db + ks * 128, dp + ks * 2); }
      wg_commit();
    };
    auto pv = [&](int T, int WG, auto& O) { wg_fence(); pv2(T, WG, O, 0, 0, 4); pv2(T, WG, O, 2, 0, 4); };
    auto release = [&](int T, auto& O) {
      wg_wait<0>();
#pragma unroll
      for (int i = 0; i < 4; i++) tie(O[i]);
      if (lane < 2) mbar_arrive_cluster(ebar + 8 * T);
    };
    auto rescale = [&](auto& O) {
#pragma unroll
      for (int jn = 0; jn < (int)(sizeof(O[0]) / 16); jn++) {
        const float2 a = ldsf2(hi + OFF_ALPHA + (8 * jn + 2 * t) * 4);
#pragma unroll
        for (int mb = 0; mb < 4; mb++) { O[mb][4 * jn] *= a.x; O[mb][4 * jn + 1] *= a.y; O[mb][4 * jn + 2] *= a.x; O[mb][4 * jn + 3] *= a.y; }
      }
    };
    uint4 oe[4];
    uint32_t mate;
    asm("mapa.shared::cluster.u32 %0, %1, %2;" : "=r"(mate) : "r"(hi + SB), "r"(rI ^ 1));
    mate -= SB;
    auto split_o = [&] {
#pragma unroll
      for (int mb = 0; mb < 4; mb++)
        oe[mb] = make_uint4(pack_bf16(O32[mb][8], O32[mb][9]), pack_bf16(O32[mb][10], O32[mb][11]), pack_bf16(O32[mb][12], O32[mb][13]), pack_bf16(O32[mb][14], O32[mb][15]));
#pragma unroll
      for (int i = 0; i < 32; i++) asm volatile("mov.b32 %0, %1;" : "=f"(O16[i >> 3][i & 7]) : "f"(O32[i >> 3][i & 7]));
    };
    auto send_o = [&] {
      mbar_wait(hi + BAR(BAR_EMPTY + 2));
#pragma unroll
      for (int mb = 0; mb < 4; mb++)
        asm volatile("st.async.weak.shared::cluster.mbarrier::complete_tx::bytes.v4.b32 [%0], {%1,%2,%3,%4}, [%5];"
                     ::"r"(mate + OFF_XE + mb * 4096 + tid * 16), "r"(oe[mb].x), "r"(oe[mb].y), "r"(oe[mb].z), "r"(oe[mb].w), "r"(mate + BAR(BAR_XE)) : "memory");
    };
    uint32_t bd[2];
    float mnew, anew, bnew;
    bool moved;
    auto fetch_o = [&] {
      asm volatile("{\n.reg .pred p;\nMW_LOOP:\nmbarrier.try_wait.parity.acquire.cluster.shared::cta.b64 p, [%0], 0;\n@!p bra MW_LOOP;\n}" ::"r"(hi + BAR(BAR_XE)) : "memory");
      const float mo = ldsf(hi + OFF_MREF + (lane & 15) * 4), mx = ldsf(hi + OFF_MX + (lane & 15) * 8);
#pragma unroll
      for (int mb = 0; mb < 4; mb++) oe[mb] = lds4(hi + OFF_XE + mb * 4096 + tid * 16);
      mnew = mx - mo > 44.f ? mx : mo;
      moved = __any_sync(~0u, mnew != mo);
      anew = ex2(mo - mnew); bnew = ex2(mx - mnew);
      const uint32_t b = pack_bf16(bnew, 0.f);
      bd[0] = shl_clamp(__shfl_sync(~0u, b, g), 16 * (g - 2 * t));
      bd[1] = shl_clamp(__shfl_sync(~0u, b, g + 8), 16 * (g - 2 * t));
    };
    auto merge_o = [&] {
      if (__builtin_expect(moved, 0)) {
#pragma unroll
        for (int i = 0; i < 4; i++) {
          const float a = __shfl_sync(~0u, anew, 8 * (i >> 1) + 2 * t + (i & 1));
#pragma unroll
          for (int mb = 0; mb < 4; mb++) { O16[mb][4 * (i >> 1) + (i & 1)] *= a; O16[mb][4 * (i >> 1) + 2 + (i & 1)] *= a; }
        }
      }
#pragma unroll
      for (int mb = 0; mb < 4; mb++) {
        mma_v(reinterpret_cast<float (&)[4]>(O16[mb][0]), oe[mb], bd[0], 0u);
        mma_v(reinterpret_cast<float (&)[4]>(O16[mb][4]), oe[mb], 0u, bd[1]);
      }
    };
    uint32_t* x1l[4];
    auto late_addr = [&] {
      mbar_wait(hi + BAR(BAR_FM));
      fb = lds1(hi + OFF_FB + tid * 4);
#pragma unroll
      for (int i = 0; i < 4; i++)
        x1l[i] = hold(inbox((16 * rI + 2 * t) * 4 + 2 * wg + (bI >> 2), bI & 3, fb, 4 * (i & 1) + (i >> 1), pI * 128 + (wq * 8 + g) * 2));
      px = hold(inbox((cta & ~1) + wg, wq, (fb >> (8 + (jI & 2) + wg)) ^ wq, 0, t * 128 + rI * 64 + 4 * g));
      pm = hold(inbox(cta & ~1, 6, fb, 8 + (jI & 2), 512 + (w * 8 + t) * 8));
      x2o = hold(inbox(4 * hI + (jI >> 1) + (~jI & 2), 7, ~fb, 8 + (jI >> 1) + (~jI & 2), (jI & 1) * 512 + tid * 2));
      x2p = hold(inbox(4 * hI + (jI >> 1) + (jI & 2), 7, ~fb, 8 + (jI >> 1) + (jI & 2), (jI & 1) * 512 + tid * 2));
    };
    auto put_late = [&](int jj) {
#pragma unroll
      for (int i = 0; i < 4; i++) {
        const int jn = i >> 1, e = i & 1, r = 4 * jn + e;
        stg_u64(x1l[i] + (8 * jn + e) * 4 * 16384 + jj * 64, pack_bf16(O16[2 * jj][r], O16[2 * jj][r + 2]), pack_bf16(O16[2 * jj + 1][r], O16[2 * jj + 1][r + 2]));
      }
    };
    auto last_products = [&](int WG) {
      wg_fence();
      pv2(4, WG, O16, 0, 0, 4);
      ck1 = clk32();
      pv2(4, WG, O16, 2, 0, 3);
      wg_wait<1>();
      tie(O16[0]); tie(O16[1]);
      put_late(0);
      __syncwarp();
      wg_fence();
      pv2(4, WG, O16, 2, 3, 4);
      wg_wait<0>();
      tie(O16[2]); tie(O16[3]);
      put_late(1);
      if (lane < 2) mbar_arrive_cluster(ebar + 32);
    };

    if (wg == 0) {
      float S32[16], S16[8];
      float m_run = -INFINITY;
      float mh[8];
#pragma unroll
      for (int i = 0; i < 16; i++) S32[i] = S16[i & 7] = mh[i & 7] = 0.f;
      const uint32_t ptl = hold32(hi + OFF_PT + (8 * (lane >> 4) + (lane & 7)) * 128 + (((2 * wq + ((lane >> 3) & 1)) ^ (lane & 7)) << 4));
      auto landed = [&](int T) { return __ballot_sync(~0u, mbar_test(hi + BAR(BAR_FULL + 8 * T) + 8 * (lane & 7))); };
      auto softmax = [&](int T, auto& O, auto& S) {
        constexpr int NJ = sizeof(S) / 16;
        wg_wait<0>();
        tie(S);
        auto update = [&] {
            float mx[2 * NJ];
#pragma unroll
            for (int jn = 0; jn < NJ; jn++) { mx[2 * jn] = fmaxf(S[4 * jn], S[4 * jn + 2]); mx[2 * jn + 1] = fmaxf(S[4 * jn + 1], S[4 * jn + 3]); }
            float a4[4], a2[2], a1;
            if constexpr (NJ == 4) {
              const bool up = lane & 16;
#pragma unroll
              for (int i = 0; i < 4; i++) { const float send = up ? mx[i] : mx[4 + i]; const float keep = up ? mx[4 + i] : mx[i]; a4[i] = fmaxf(keep, __shfl_xor_sync(~0u, send, 16)); }
            } else {
#pragma unroll
              for (int i = 0; i < 4; i++) { a4[i] = fmaxf(mx[i], __shfl_xor_sync(~0u, mx[i], 16)); if (lane & 16) a4[i] = -INFINITY; }
            }
            {
              const bool up = lane & 8;
#pragma unroll
              for (int i = 0; i < 2; i++) { const float send = up ? a4[i] : a4[2 + i]; const float keep = up ? a4[2 + i] : a4[i]; a2[i] = fmaxf(keep, __shfl_xor_sync(~0u, send, 8)); }
            }
            {
              const bool up = lane & 4;
              const float send = up ? a2[0] : a2[1]; const float keep = up ? a2[1] : a2[0];
              a1 = fmaxf(keep, __shfl_xor_sync(~0u, send, 4));
            }
            stsf(hi + OFF_RED + (wq * 32 + 8 * (g >> 1) + 2 * t + (g & 1)) * 4, a1);
            wg0bar();
            const float mt = fmaxf(fmaxf(ldsf(hi + OFF_RED + lane * 4), ldsf(hi + OFF_RED + 128 + lane * 4)),
                                   fmaxf(ldsf(hi + OFF_RED + 256 + lane * 4), ldsf(hi + OFF_RED + 384 + lane * 4)));
            const float m_new = fmaxf(m_run, ceilf(mt));
            if (wq == 0) { stsf(hi + OFF_MREF + (T == 4 ? 128 : 0) + lane * 4, m_new); stsf(hi + OFF_ALPHA + lane * 4, ex2(m_run - m_new)); }
            m_run = m_new;
#pragma unroll
            for (int i = 0; i < 2 * NJ; i++) mh[i] = __shfl_sync(~0u, m_new, 8 * (i >> 1) + 2 * t + (i & 1));
            if (T > 0) { wg0bar(); rescale(O); }
        };
        auto write_p = [&] {
          uint32_t pk[2 * NJ];
          float x[4 * NJ];
#pragma unroll
          for (int i = 0; i < 4 * NJ; i++) x[i] = S[i] - mh[2 * (i >> 2) + (i & 1)];
#pragma unroll
          for (int i = 0; i < 2 * NJ; i++) pk[i] = pack_bf16(ex2(x[2 * i]), ex2(x[2 * i + 1]));
#pragma unroll
          for (int hf = 0; hf < NJ / 2; hf++) stsm4t(ptl + (T & 1) * 4096 + hf * 2048, pk[4 * hf], pk[4 * hf + 1], pk[4 * hf + 2], pk[4 * hf + 3]);
          asm volatile("fence.proxy.async.shared::cta;" ::: "memory");
          if constexpr (NJ == 4) {
#pragma unroll
            for (int i = 0; i < 8; i++) x[i] = fmaxf(x[i], x[i + 8]);
          }
          return cbar_or(fmaxf(fmaxf(fmaxf(x[0], x[1]), fmaxf(x[2], x[3])), fmaxf(fmaxf(x[4], x[5]), fmaxf(x[6], x[7]))) > 56.f);
        };
        if constexpr (NJ == 4) {
          bool over = T == 0;
#pragma unroll 1
          do {
            if (over) update();
            over = write_p();
          } while (__builtin_expect(over, 0));
        } else {
#pragma unroll 1
          while (__builtin_expect(write_p(), 0)) update();
        }
      };
      uint32_t have = 0;
#pragma unroll
      for (int i = 0; i < 4; i++) x1l[i] = nullptr;
      px = pm = x2o = x2p = nullptr;
#pragma unroll 1
      for (int T = 0; T < 3; T++) {
        sfor<0, 8>([&](auto jc) {
          constexpr int jj = decltype(jc)::value;
          const uint32_t da = dlo(SB) + box_slot(8 * T + jj) * 512, db = dlo(OFF_R0) + jj * 256;
          mbar_wait(hi + BAR(BAR_FULL) + 64 * T + 8 * jj);
          wg_fence();
          wgmma_ss<0, jj != 0>(S32, da, db);
#pragma unroll
          for (int ks = 1; ks < 4; ks++) wgmma_ss<0, 1>(S32, da + ks * 2, db + ks * 2);
          wg_commit();
        });
        softmax(T, O32, S32);
        pv(T, 0, O32);
        have = landed(3);
        release(T, O32);
        if (T == 1) late_addr();
      }
      split_o();
#pragma unroll 1
      for (int T = 3;; T++) {
        sfor<0, 8>([&](auto jc) {
          constexpr int jj = decltype(jc)::value;
          const uint32_t da = dlo(SB) + (8 * T + jj - 23) * 512, db = dlo(OFF_R0) + jj * 256;
          if (!((have >> jj) & 1)) mbar_wait(hi + BAR(BAR_FULL) + 64 * T + 8 * jj);
          wg_fence();
          wgmma_ss<0, jj != 0>(S16, da, db);
#pragma unroll
          for (int ks = 1; ks < 4; ks++) wgmma_ss<0, 1>(S16, da + ks * 2, db + ks * 2);
          wg_commit();
          if (jj == 2 && T == 3) send_o();
        });
        softmax(T, O16, S16);
        if (T == 4) break;
        pv(3, 0, O16);
        have = landed(4);
        fetch_o();
        if (wq == 0) stsf(hi + OFF_MREF + 128 + lane * 4, mnew);
        mbar_wait(hi + BAR(BAR_XE));
        release(3, O16);
        merge_o();
        if (__builtin_expect(moved, 0)) {
          m_run = mnew;
#pragma unroll
          for (int i = 0; i < 4; i++) mh[i] = __shfl_sync(~0u, mnew, 8 * (i >> 1) + 2 * t + (i & 1));
        }
      }
      last_products(0);
    } else {
      float ls[2] = {0.f, 0.f};
      const int hr = 4 * wq + (lane >> 3);
      const uint32_t ptl = hi + OFF_PT + (tid & 127) * 16;
      auto sum8 = [](const uint4& v) { return ((bf_lo(v.x) + bf_hi(v.x)) + (bf_lo(v.y) + bf_hi(v.y))) + ((bf_lo(v.z) + bf_hi(v.z)) + (bf_lo(v.w) + bf_hi(v.w))); };
      auto row_sum = [](float l) { l += __shfl_xor_sync(~0u, l, 1); l += __shfl_xor_sync(~0u, l, 2); return l + __shfl_xor_sync(~0u, l, 4); };
      auto get_p = [&](auto& O) {
        if (__builtin_expect(cbar_or(false), 0)) {
          cbar_or(false);
          rescale(O);
          ls[0] *= ldsf(hi + OFF_ALPHA + hr * 4);
          if (sizeof(O[0]) == 64) ls[1] *= ldsf(hi + OFF_ALPHA + 64 + hr * 4);
        }
      };
#pragma unroll 1
      for (int T = 0; T < 3; T++) {
        get_p(O32);
        pv(T, 1, O32);
        ls[0] += sum8(lds4(ptl + (T & 1) * 4096));
        ls[1] += sum8(lds4(ptl + (T & 1) * 4096 + 2048));
        release(T, O32);
      }
      split_o();
      send_o();
      {
        const float l = row_sum(ls[1]);
        if (!(lane & 7))
          asm volatile("st.async.weak.shared::cluster.mbarrier::complete_tx::bytes.v2.b32 [%0], {%1,%2}, [%3];"
                       ::"r"(mate + OFF_MX + hr * 8), "r"(lds1(hi + OFF_MREF + 64 + hr * 4)), "r"(__float_as_uint(l)), "r"(mate + BAR(BAR_XE)) : "memory");
      }
      get_p(O16);
      pv(3, 1, O16);
      ls[0] += sum8(lds4(ptl + 4096));
      fetch_o();
      const float lx = ldsf(hi + OFF_MX + hr * 8 + 4) * __shfl_sync(~0u, bnew, hr);
      ls[0] = ls[0] * __shfl_sync(~0u, anew, hr) + ((lane & 7) ? 0.f : lx);
      release(3, O16);
      merge_o();
      late_addr();
      uint32_t* const mlo = hold(inbox((16 * rI + hr) * 4 + (lane & 2), 6, fb, 13, 512 + (cta >> 1) * 8 + (lane & 1) * 4));
      mbar_wait(hi + BAR(BAR_CLR));
      get_p(O16);
      {
        const uint32_t m = lds1(hi + OFF_MREF + 128 + hr * 4), l = nz(__float_as_uint(row_sum(ls[0] + sum8(lds4(ptl)))));
        if (!(lane & 4)) stg4_b128(mlo, make_uint4(m, l, m, l));
      }
      last_products(1);
    }
  }

  uint32_t aw[8][4];
  {
    wait_until(ck1, X1_D0);
    uint2 ml[2];
    uint4 v[4];
#pragma unroll
    for (int i = 0; i < 4; i++) v[i] = ldg_2u64(px + (i >> 1) * 512 + (i & 1) * 32);
#pragma unroll
    for (int i = 0; i < 2; i++) ml[i] = ldg_u64(pm + i * 32);
    uint32_t sel[4][2] = {{0u, 0u}, {0u, 0u}, {0u, 0u}, {0u, 0u}};
    float Ls = 0.f;
    bool w_ok = false;
    const uint32_t bso = hold32(hi + OFF_BS4 + w * 320 + (16 * (t >> 1) + 8 * (g >> 2) + 4 * (g & 1) + 2 * (t & 1) + ((g >> 1) & 1)) * 8), bsi = hold32(hi + OFF_BS4 + g * 320 + t * 16);
    const uint32_t lso = hold32(hi + OFF_BS4 + w * 320 + 256 + t * 4), lsi = hold32(hi + OFF_BS4 + t * 640 + 256);
    const uint32_t wa = hold32(hi + OFF_WUV + wg * 8192 + (lane >> 4) * 4096 + (lane & 7) * 128 + (((2 * wq + ((lane >> 3) & 1)) ^ (lane & 7)) << 4));
    mbar_wait(hi + BAR(BAR_FULL + U_WUV) + 8 * wg);
#pragma unroll
    for (int ks = 0; ks < 4; ks++) { ldsm4t(aw[ks], wa + ks * 1024); aw[4 + ks][0] = aw[4 + ks][1] = aw[4 + ks][2] = aw[4 + ks][3] = 0; }
    bool wv_ok = false;
    float e0[4], e1[4];
#pragma unroll 1
    while (true) {
      if (!wv_ok && mbar_test(hi + BAR(BAR_FULL + U_WUV + 2) + 8 * wg)) {
        wv_ok = true;
#pragma unroll
        for (int ks = 0; ks < 4; ks++) ldsm4t(aw[4 + ks], wa + 16384 + ks * 1024);
      }
#pragma unroll
      for (int i = 0; i < 4; i++) tie(v[i]);
      tie(ml[0]); tie(ml[1]);
      const bool ok = __all_sync(~0u, w_ok && min(min3(min3(v[0].y, v[0].w, v[1].y), v[1].w, v[2].y), min3(v[2].w, v[3].y, v[3].w)) != 0);
#pragma unroll
      for (int i = 0; i < 4; i++) e0[i] = e1[i] = 0.f;
      mma_v(e0, v[0], sel[0][0], sel[0][1]); mma_v(e1, v[2], sel[2][0], sel[2][1]);
      mma_v(e0, v[1], sel[1][0], sel[1][1]); mma_v(e1, v[3], sel[3][0], sel[3][1]);
      if (ok) break;
#pragma unroll
      for (int i = 0; i < 4; i++) if (v[i].y == 0 || v[i].w == 0) v[i] = ldg_2u64(px + (i >> 1) * 512 + (i & 1) * 32);
      if (!w_ok) {
        if (__all_sync(~0u, min(ml[0].y, ml[1].y) != 0)) {
          w_ok = true;
          float M = fmaxf(__uint_as_float(ml[0].x), __uint_as_float(ml[1].x));
          M = fmaxf(M, __shfl_xor_sync(~0u, M, 1)); M = fmaxf(M, __shfl_xor_sync(~0u, M, 2));
          const uint32_t wb[2] = {pack_bf16(ex2(__uint_as_float(ml[0].x) - M), 0.f), pack_bf16(ex2(__uint_as_float(ml[1].x) - M), 0.f)};
#pragma unroll
          for (int i = 0; i < 4; i++) { sel[i][0] = shl_clamp(wb[i >> 1], 16 * g - 64 * (i & 1)); sel[i][1] = shl_clamp(wb[i >> 1], 16 * g - 64 * (i & 1) - 32); }
          Ls = bf_lo(wb[0]) * __uint_as_float(ml[0].y) + bf_lo(wb[1]) * __uint_as_float(ml[1].y);
        } else {
#pragma unroll
          for (int i = 0; i < 2; i++) ml[i] = ldg_u64(pm + i * 32);
        }
      }
    }
    stsf(lso, Ls);
    sts2(bso, pack_bf16(e0[0] + e1[0], e0[1] + e1[1]), pack_bf16(e0[2] + e1[2], e0[3] + e1[3]));
    cbar();
    float o[4][4] = {{0.f, 0.f, 0.f, 0.f}, {0.f, 0.f, 0.f, 0.f}, {0.f, 0.f, 0.f, 0.f}, {0.f, 0.f, 0.f, 0.f}};
    uint4 b[4];
#pragma unroll
    for (int kk = 0; kk < 4; kk++) b[kk] = lds4(bsi + kk * 64);
    const float4 la = ldsf4(lsi), lb = ldsf4(lsi + 320);
    if (!wv_ok) {
      mbar_wait(hi + BAR(BAR_FULL + U_WUV + 2) + 8 * wg);
#pragma unroll
      for (int ks = 0; ks < 4; ks++) ldsm4t(aw[4 + ks], wa + 16384 + ks * 1024);
    }
#pragma unroll
    for (int kk = 0; kk < 4; kk++) { mma16816(o[(2 * kk) & 3], aw[2 * kk], b[kk].x, b[kk].y); mma16816(o[(2 * kk + 1) & 3], aw[2 * kk + 1], b[kk].z, b[kk].w); }
    const float ia = rcp((la.x + la.y) + (la.z + la.w)), ib = rcp((lb.x + lb.y) + (lb.z + lb.w));
    const uint32_t y0 = pack_bf16(((o[0][0] + o[1][0]) + (o[2][0] + o[3][0])) * ia, ((o[0][1] + o[1][1]) + (o[2][1] + o[3][1])) * ib);
    const uint32_t y1 = pack_bf16(((o[0][2] + o[1][2]) + (o[2][2] + o[3][2])) * ia, ((o[0][3] + o[1][3]) + (o[2][3] + o[3][3])) * ib);
    stg_u64(x2o, y0, y1);
    stg_u64(x2p, y0, y1);
  }
  const uint32_t ck2 = clk32();
  {
    uint32_t* const o = hold(inbox(4 * (8 * jI + w) + (g >> 1), 6, fb, 12, (g & 1) * 256 + hI * 8 + 2 * t));
    const uint32_t* const x2i = hold(inbox(cta & ~1, 7, ~fb, 8 + (jI & 2), tid * 2));
    const uint32_t* const x2j = hold(inbox(cta | 1, 7, ~fb, 8 + (jI | 1), tid * 2));
    const uint32_t bso = hold32(hi + OFF_BS5 + (16 * w + g) * 16 + t * 4), bsi = hold32(hi + OFF_BS5 + lane * 16);
    const uint32_t wa = hold32(hi + OFF_WO + wg * 8192 + (8 * (lane >> 4) + (lane & 7)) * 128 + (((2 * wq + ((lane >> 3) & 1)) ^ (lane & 7)) << 4));
    wait_until(ck2, D_X2);
    uint2 v[4];
#pragma unroll
    for (int i = 0; i < 4; i++) v[i] = ldg_u64(((i & 2) ? x2j : x2i) + (i & 1) * 512);
    int wo_n = 0;
    sum4_to_smem(v, x2i, x2j, bso, [&] {
      if (wo_n == 0 && mbar_test(hi + BAR(BAR_FULL + U_WO) + 8 * wg)) {
        wo_n = 1;
#pragma unroll
        for (int ks = 0; ks < 4; ks++) ldsm4t(aw[ks], wa + ks * 2048);
      }
      if (wo_n == 1 && mbar_test(hi + BAR(BAR_FULL + U_WO + 2) + 8 * wg)) {
        wo_n = 2;
#pragma unroll
        for (int ks = 0; ks < 4; ks++) ldsm4t(aw[4 + ks], wa + 16384 + ks * 2048);
      }
    });
    cbar();
    float e[4][4] = {{0.f, 0.f, 0.f, 0.f}, {0.f, 0.f, 0.f, 0.f}, {0.f, 0.f, 0.f, 0.f}, {0.f, 0.f, 0.f, 0.f}};
    uint32_t b[4][4];
#pragma unroll
    for (int kk = 0; kk < 4; kk++) ldsm4t(b[kk], bsi + kk * 512);
    if (wo_n < 2) {
      if (wo_n == 0) {
        mbar_wait(hi + BAR(BAR_FULL + U_WO) + 8 * wg);
#pragma unroll
        for (int ks = 0; ks < 4; ks++) ldsm4t(aw[ks], wa + ks * 2048);
      }
      mbar_wait(hi + BAR(BAR_FULL + U_WO + 2) + 8 * wg);
#pragma unroll
      for (int ks = 0; ks < 4; ks++) ldsm4t(aw[4 + ks], wa + 16384 + ks * 2048);
    }
#pragma unroll
    for (int ks = 0; ks < 8; ks++) mma16816(e[ks & 3], aw[ks], b[ks >> 1][2 * (ks & 1)], b[ks >> 1][2 * (ks & 1) + 1]);
    stg_u64(o, pack_bf16((e[0][0] + e[1][0]) + (e[2][0] + e[3][0]), (e[0][1] + e[1][1]) + (e[2][1] + e[3][1])),
            pack_bf16((e[0][2] + e[1][2]) + (e[2][2] + e[3][2]), (e[0][3] + e[1][3]) + (e[2][3] + e[3][3])));
    if (lane == 0) mbar_arrive(hi + BAR(BAR_P5D));
  }
  const uint32_t ck3 = clk32();
  if (cta < NFF) {
    const int mi = lane >> 3, r = lane & 7;
    uint32_t a1[4][4], a2[4][4];
    uint32_t bc[8], bs[8];
    const uint32_t* const mbi = gs->MODB + (2 + wg) * 2048 + ((~((fb >> 14)) & 1) << 10) + 256 * wq + lane;
#pragma unroll
    for (int i = 0; i < 8; i++) { bs[i] = ldg_rlx1(mbi + i * 32); bc[i] = ldg_rlx1(mbi + 4096 + i * 32); }
    const int lp = (tid >> 2) & 31, kq = tid & 3;
    const int fo = (lp >> 2) + 8 * (kq >> 1), bo = 2 * (lp & 3) + (kq & 1);
    const uint32_t* xb = hold(gs->X3B + ((cta >> 1) & 1) * 4096 + wg * 2048 + (((fb >> 14) & 1) << 10) + (16 * wq + t) * 16 + 2 * g);
    uint32_t* ox[4];
#pragma unroll
    for (int mb = 0; mb < 4; mb++) ox[mb] = hold(inbox(16 * w + 4 * mb + (g >> 1), 4 + (cta >= 56), fb, 16 + 4 * mb, (cta >= 56 ? cta - 56 : cta) * 16 + (g & 1) * 8 + 2 * t));
    const uint32_t gi = hold32(hi + OFF_REDG + tid * 4);
    const uint32_t h1o = hold32(hi + OFF_H1 + fo * 16 + bo * 2), sti = hold32(hi + OFF_REDS + bo * 80), sto = hold32(hi + OFF_REDS + g * 80 + w * 8);
    const uint32_t a1a = hold32(hi + OFF_W1 + (64 * w + 8 * (mi >> 1) + r) * 64 + (((2 * rI + (mi & 1)) ^ (r >> 1)) << 4));
    bool w2ok = false;
    uint32_t a2a[4];
#pragma unroll
    for (int mb = 0; mb < 4; mb++) {
      a2a[mb] = hi + OFF_W2 + w * 2048 + (8 * (mi >> 1) + r) * 128 + (((2 * mb + (mi & 1)) ^ r) << 4);
      a2[mb][0] = a2[mb][1] = a2[mb][2] = a2[mb][3] = 0;
    }
#pragma unroll 1
    while (true) {
      uint32_t mn = 0xffffffffu;
#pragma unroll
      for (int i = 0; i < 8; i++) mn = min3(mn, bs[i], bc[i]);
      if (__all_sync(~0u, mn != 0)) break;
#pragma unroll
      for (int i = 0; i < 8; i++) { bs[i] = ldg_rlx1(mbi + i * 32); bc[i] = ldg_rlx1(mbi + 4096 + i * 32); }
    }
#pragma unroll
    for (int i = 0; i < 8; i++) { bs[i] = movm(bs[i]); bc[i] = hadd2(movm(bc[i]), ONE2); }
    mbar_wait(hi + BAR(BAR_FULL + U_W1) + 8 * wg);
#pragma unroll
    for (int ks = 0; ks < 4; ks++) ldsm4t(a1[ks], a1a + ks * 1024);
    {
      float u[2][4] = {{0.f, 0.f, 0.f, 0.f}, {0.f, 0.f, 0.f, 0.f}}, vv[2][4] = {{0.f, 0.f, 0.f, 0.f}, {0.f, 0.f, 0.f, 0.f}};
#pragma unroll
      for (int ks = 0; ks < 4; ks++) { mma16816(u[ks & 1], a1[ks], bc[2 * ks], bc[2 * ks + 1]); mma16816(vv[ks & 1], a1[ks], bs[2 * ks], bs[2 * ks + 1]); }
      sts4f(hi + OFF_REDU + tid * 16, u[0][0] + u[1][0], u[0][1] + u[1][1], u[0][2] + u[1][2], u[0][3] + u[1][3]);
      sts4f(hi + OFF_REDV + tid * 16, vv[0][0] + vv[1][0], vv[0][1] + vv[1][1], vv[0][2] + vv[1][2], vv[0][3] + vv[1][3]);
    }
    if (wg) asm volatile("bar.arrive 1, 256;" ::: "memory"); else cbar();
    float U = 0.f, V = 0.f;
    bool uv = wg;
    wait_until(ck3, D_X3B);
    float G[2][4], S[2][4];
    bool ok;
#pragma unroll 1
    do {
      uint2 x[4];
#pragma unroll
      for (int ks = 0; ks < 4; ks++) x[ks] = ldg_u64(xb + ks * 64);
      if (!uv) {
        uv = true;
        float a[8], b[8];
#pragma unroll
        for (int i = 0; i < 8; i++) { a[i] = ldsf(gi + (OFF_REDU - OFF_REDG) + i * 512); b[i] = ldsf(gi + (OFF_REDV - OFF_REDG) + i * 512); }
        U = ((a[0] + a[1]) + (a[2] + a[3])) + ((a[4] + a[5]) + (a[6] + a[7]));
        V = ((b[0] + b[1]) + (b[2] + b[3])) + ((b[4] + b[5]) + (b[6] + b[7]));
      }
      if (!w2ok && mbar_test(hi + BAR(BAR_FULL + U_W2) + 8 * wg)) {
        w2ok = true;
#pragma unroll
        for (int mb = 0; mb < 4; mb++) ldsm4t(a2[mb], a2a[mb]);
      }
#pragma unroll
      for (int ks = 0; ks < 4; ks++) tie(x[ks]);
      ok = __all_sync(~0u, min(min3(x[0].y, x[1].y, x[2].y), x[3].y) != 0);
#pragma unroll
      for (int i = 0; i < 4; i++) G[0][i] = G[1][i] = S[0][i] = S[1][i] = 0.f;
#pragma unroll
      for (int ks = 0; ks < 4; ks++) {
        const uint32_t s0[4] = {x[ks].x, ONE2, x[ks].y, ONE2};
        mma16816(S[ks & 1], s0, x[ks].x, x[ks].y);
        mma16816(G[ks & 1], a1[ks], hmul2(x[ks].x, bc[2 * ks]), hmul2(x[ks].y, bc[2 * ks + 1]));
      }
    } while (!ok);
    if ((g >> 1) == t) sts2f(sto, (g & 1) ? S[0][3] + S[1][3] : S[0][2] + S[1][2], (g & 1) ? S[0][1] + S[1][1] : S[0][0] + S[1][0]);
    sts4f(hi + OFF_REDG + tid * 16, G[0][0] + G[1][0], G[0][1] + G[1][1], G[0][2] + G[1][2], G[0][3] + G[1][3]);
    if (wg) asm volatile("bar.arrive 3, 256;" ::: "memory"); else asm volatile("bar.sync 3, 256;" ::: "memory");
    if (tid < 128) {
      float gv[8];
      float4 sv[4];
#pragma unroll
      for (int i = 0; i < 4; i++) sv[i] = ldsf4(sti + i * 16);
#pragma unroll
      for (int i = 0; i < 8; i++) gv[i] = ldsf(gi + i * 512);
      const float s1 = ((sv[0].x + sv[0].z) + (sv[1].x + sv[1].z)) + ((sv[2].x + sv[2].z) + (sv[3].x + sv[3].z));
      const float s2 = ((sv[0].y + sv[0].w) + (sv[1].y + sv[1].w)) + ((sv[2].y + sv[2].w) + (sv[3].y + sv[3].w));
      const float gs_ = ((gv[0] + gv[1]) + (gv[2] + gv[3])) + ((gv[4] + gv[5]) + (gv[6] + gv[7]));
      const float mu = s1 * (1.f / 512.f);
      const float rs = rsq(fmaxf(s2 * (1.f / 512.f) - mu * mu, 0.f) + 1e-5f);
      const float hv = fmaxf(rs * (gs_ - mu * U) + V, 0.f);
      asm volatile("st.shared.u16 [%0], %1;" ::"r"(h1o), "h"(__bfloat16_as_ushort(__float2bfloat16(hv))) : "memory");
    }
    if (!w2ok) {
      mbar_wait(hi + BAR(BAR_FULL + U_W2) + 8 * wg);
#pragma unroll
      for (int mb = 0; mb < 4; mb++) ldsm4t(a2[mb], a2a[mb]);
    }
    asm volatile("bar.sync 2, 256;" ::: "memory");
    uint32_t b0, b1;
    ldsm2t(b0, b1, hi + OFF_H1 + (lane & 15) * 16);
#pragma unroll
    for (int mb = 0; mb < 4; mb++) {
      float o[4] = {0.f, 0.f, 0.f, 0.f};
      mma16816(o, a2[mb], b0, b1);
      stg_u64(ox[mb], pack_bf16(o[0], o[1]), pack_bf16(o[2], o[3]));
    }
    if (lane == 0) mbar_arrive(hi + BAR(BAR_P7D));
  }
}

typedef CUresult (*EncodeTiledFn)(CUtensorMap*, CUtensorMapDataType, cuuint32_t, void*, const cuuint64_t*, const cuuint64_t*,
                                  const cuuint32_t*, const cuuint32_t*, CUtensorMapInterleave, CUtensorMapSwizzle,
                                  CUtensorMapL2promotion, CUtensorMapFloatOOBfill);

void make_map(EncodeTiledFn enc, CUtensorMap* m, const void* base, uint64_t cols, uint64_t rows, uint32_t bc, uint32_t br,
              CUtensorMapSwizzle sw, CUtensorMapL2promotion promo) {
  cuuint64_t dims[2] = {cols, rows};
  cuuint64_t strides[1] = {cols * 2};
  cuuint32_t box[2] = {bc, br};
  cuuint32_t es[2] = {1, 1};
  enc(m, CU_TENSOR_MAP_DATA_TYPE_BFLOAT16, 2, const_cast<void*>(base), dims, strides, box, es, CU_TENSOR_MAP_INTERLEAVE_NONE, sw, promo,
      CU_TENSOR_MAP_FLOAT_OOB_FILL_NONE);
}
void make_map3(EncodeTiledFn enc, CUtensorMap* m, const void* base, uint64_t rows, uint32_t br, uint32_t bb) {
  cuuint64_t dims[3] = {64, rows, 8};
  cuuint64_t strides[2] = {1024, 128};
  cuuint32_t box[3] = {64, br, bb};
  cuuint32_t es[3] = {1, 1, 1};
  enc(m, CU_TENSOR_MAP_DATA_TYPE_BFLOAT16, 3, const_cast<void*>(base), dims, strides, box, es, CU_TENSOR_MAP_INTERLEAVE_NONE,
      CU_TENSOR_MAP_SWIZZLE_128B, CU_TENSOR_MAP_L2_PROMOTION_NONE, CU_TENSOR_MAP_FLOAT_OOB_FILL_NONE);
}

}

extern "C" void kernel_launch(void* const* d_in, const int* in_sizes, int n_in, void* d_out, int out_size) {
  (void)in_sizes; (void)n_in; (void)out_size;
  static EncodeTiledFn enc = nullptr;
  static Scratch* scratch = nullptr;
  if (!enc) {
    void* sp = nullptr;
    cudaGetSymbolAddress(&sp, g_s);
    scratch = (Scratch*)(((uintptr_t)sp + 131071) & ~(uintptr_t)131071);
    void* fn = nullptr;
    cudaDriverEntryPointQueryResult q;
    cudaGetDriverEntryPoint("cuTensorMapEncodeTiled", &fn, cudaEnableDefault, &q);
    enc = (EncodeTiledFn)fn;
    cudaFuncSetAttribute(fused_decode_kernel, cudaFuncAttributeMaxDynamicSharedMemorySize, SMEM_BYTES);
  }
  Params P;
  make_map(enc, &P.ckv, d_in[1], 512, 8 * 4096, 64, 64, CU_TENSOR_MAP_SWIZZLE_128B, CU_TENSOR_MAP_L2_PROMOTION_NONE);
  make_map(enc, &P.wq, d_in[2], 4096, 512, 64, 64, CU_TENSOR_MAP_SWIZZLE_128B, CU_TENSOR_MAP_L2_PROMOTION_NONE);
  make_map(enc, &P.wuk, d_in[3], 4096, 512, 64, 64, CU_TENSOR_MAP_SWIZZLE_128B, CU_TENSOR_MAP_L2_PROMOTION_NONE);
  {
    cuuint64_t dims[5] = {4096, 2, 8, 4, 8};
    cuuint64_t strides[4] = {8 * 8192, 8192, 16 * 8192, 64 * 8192};
    cuuint32_t box[5] = {64, 2, 8, 2, 2};
    cuuint32_t es[5] = {1, 1, 1, 1, 1};
    enc(&P.wuv, CU_TENSOR_MAP_DATA_TYPE_BFLOAT16, 5, d_in[4], dims, strides, box, es, CU_TENSOR_MAP_INTERLEAVE_NONE, CU_TENSOR_MAP_SWIZZLE_128B,
        CU_TENSOR_MAP_L2_PROMOTION_NONE, CU_TENSOR_MAP_FLOAT_OOB_FILL_NONE);
  }
  make_map(enc, &P.wo, d_in[5], 512, 4096, 64, 64, CU_TENSOR_MAP_SWIZZLE_128B, CU_TENSOR_MAP_L2_PROMOTION_NONE);
  make_map(enc, &P.w1, d_in[7], 1792, 512, 2 * FCH, 128, CU_TENSOR_MAP_SWIZZLE_64B, CU_TENSOR_MAP_L2_PROMOTION_NONE);
  make_map3(enc, &P.w2, d_in[8], 1792, FCH, 4);
  make_map(enc, &P.wma, d_in[10], 3072, 512, 64, 128, CU_TENSOR_MAP_SWIZZLE_128B, CU_TENSOR_MAP_L2_PROMOTION_NONE);
  make_map(enc, &P.wmod, d_in[10], 3072, 512, 32, 128, CU_TENSOR_MAP_SWIZZLE_64B, CU_TENSOR_MAP_L2_PROMOTION_NONE);
  fused_decode_kernel<<<NCTA, NTHREADS, SMEM_BYTES>>>((__nv_bfloat16*)d_out, scratch, (const uint8_t*)d_in[2], (const uint8_t*)d_in[0],
                                                      (const uint8_t*)d_in[9], P);
}
```

```cpp
#include <cuda_runtime.h>
#include <cuda.h>
#include <cuda_bf16.h>
#include <stdint.h>

namespace {

constexpr int NCTA = 128;
constexpr int NTHREADS = 384;
constexpr int FCH = 16;
constexpr int NFF = 1792 / FCH;

constexpr uint32_t SB = 1024;
__host__ __device__ constexpr uint32_t slot(int i) { return SB + i * 8192; }
constexpr uint32_t OFF_R1 = slot(16);
constexpr uint32_t OFF_R2 = slot(20);
constexpr uint32_t OFF_PT = slot(23);
constexpr uint32_t OFF_R0 = slot(24);
constexpr uint32_t OFF_MISC = SB + 229376;
constexpr uint32_t OFF_BARS = OFF_MISC;
constexpr uint32_t OFF_FM = OFF_MISC + 736;
constexpr uint32_t OFF_EPOCH = OFF_MISC + 768;
constexpr uint32_t OFF_BS = OFF_MISC + 1024;
constexpr uint32_t SMEM_BYTES = 229376 + 3072;
constexpr uint32_t OFF_P0S = OFF_R0 + 24576;
constexpr uint32_t OFF_BS2 = OFF_R0 + 30720;
constexpr uint32_t OFF_RED = OFF_BS;
constexpr uint32_t OFF_ALPHA = OFF_BS + 512;
constexpr uint32_t OFF_MREF = OFF_BS + 640;
constexpr uint32_t OFF_MX = OFF_BS + 896;
constexpr uint32_t OFF_FB = OFF_BS + 1024;
__host__ __device__ constexpr int box_slot(int n) { return n < 23 ? n : n - 23; }
constexpr uint32_t OFF_WUV = slot(21), OFF_WUV2 = slot(0);
constexpr uint32_t OFF_XE = OFF_R0 + 2048;
constexpr uint32_t OFF_BS4 = slot(2);
constexpr uint32_t OFF_BS5 = slot(2) + 4096;
constexpr uint32_t OFF_WM = slot(17);
constexpr uint32_t OFF_WO = slot(5);
constexpr uint32_t OFF_W1 = slot(9);
constexpr uint32_t OFF_W2 = slot(13);
constexpr uint32_t OFF_REDG = OFF_R0;
constexpr uint32_t OFF_REDS = OFF_R0 + 4096;
constexpr uint32_t OFF_REDU = OFF_R0 + 8192;
constexpr uint32_t OFF_REDV = OFF_R0 + 12288;
constexpr uint32_t OFF_H1 = OFF_R0 + 16384;

constexpr int BAR_FULL = 8;
constexpr int U_WQ = -8, U_WUK = -4, U_WMOD = 40, U_WUV = 42, U_WO = 46, U_W1 = 50, U_W2 = 52, NUNITS = 54;
constexpr int BAR_EMPTY = 62;
constexpr int BAR_GO = 67, BAR_CLR = 68, BAR_EPOCH = 69;
constexpr int BAR_P2E = 70, BAR_P5D = 71, BAR_P7D = 72;
constexpr int BAR_XE = 73;
constexpr int BAR_FM = 74;
constexpr int BAR_P0D = 75;
constexpr int BAR_WA = 76;
__host__ __device__ constexpr uint32_t BAR(int i) { return OFF_BARS + 8 * i; }
constexpr int PACE_T0 = 672;
constexpr int PACE_DT = 320;
constexpr int PACE_DTE = 324;
constexpr int PACE_DTW = 150;
constexpr int PACE_DT2 = 266;
constexpr int PACE_GAP3 = 444;
constexpr int PACE_DT3 = 400;
constexpr int PACE_DTL = 0;
constexpr int PACE_GAP4 = 0;
constexpr int PACE_DT4 = 500;
constexpr int WIN_PRE = 5;
constexpr int WIN_MID = 8;
constexpr int WIN_END = 7;
constexpr int WIN_TAIL = 6;
constexpr int MOD_AT = 3;
constexpr int D_MOD = 600;
constexpr int D_QP = 1600;
constexpr int QX_AT = 7;
constexpr int D_QX = 1600;
constexpr int CNT_AT = 30;
constexpr int GA_AT = 45;
constexpr int X1_D0 = 1100;
constexpr int D_X2 = 380;
constexpr int D_X3A = 400;
constexpr int D_X3B = 1300;
constexpr int D_GB = 300;
constexpr int D_FIN = 450;
constexpr int D_FIN2 = 2000;
constexpr int CLR_CLK = 180;
constexpr int NPROBE = 3;

struct Scratch {
  uint32_t MODA[1024 * 4];
  uint32_t QP[128 * 256 * 2];
  uint32_t FL[2][128];
  uint32_t QX[2][8 * 32 * 256];
  uint32_t epoch;
  uint32_t pad[31];
  uint32_t cnt;
  alignas(131072) uint32_t X3B[16384];
  uint32_t MODB[16384];
  uint32_t IN[128][16384];
};
__device__ uint8_t g_s[sizeof(Scratch) + 131072];

struct Params {
  CUtensorMap wma, wq, wuk, wmod, ckv, wuv, wo, w1, w2;
};

__device__ __forceinline__ void mbar_init(uint32_t bar, int cnt) { asm volatile("mbarrier.init.shared::cta.b64 [%0], %1;" ::"r"(bar), "r"(cnt)); }
__device__ __forceinline__ void mbar_expect(uint32_t bar, uint32_t bytes) { asm volatile("mbarrier.arrive.expect_tx.shared::cta.b64 _, [%0], %1;" ::"r"(bar), "r"(bytes) : "memory"); }
__device__ __forceinline__ void mbar_arrive(uint32_t bar) { asm volatile("mbarrier.arrive.shared::cta.b64 _, [%0];" ::"r"(bar) : "memory"); }
__device__ __forceinline__ void mbar_arrive_cluster(uint32_t bar) { asm volatile("mbarrier.arrive.shared::cluster.b64 _, [%0];" ::"r"(bar) : "memory"); }
__device__ __forceinline__ bool mbar_test(uint32_t bar) {
  uint32_t ok;
  asm volatile("{\n.reg .pred p;\nmbarrier.test_wait.parity.shared::cta.b64 p, [%1], 0;\nselp.u32 %0,1,0,p;\n}" : "=r"(ok) : "r"(bar) : "memory");
  return ok;
}
__device__ __forceinline__ uint32_t gtime32() { uint32_t c; asm volatile("mov.u32 %0, %%globaltimer_lo;" : "=r"(c) :: "memory"); return c; }
__device__ __forceinline__ uint32_t clk32() { uint32_t c; asm volatile("{\n.reg .u64 t;\nmov.u64 t, %%clock64;\ncvt.u32.u64 %0, t;\n}" : "=r"(c) :: "memory"); return c; }
__device__ __forceinline__ void wait_until(uint32_t c0, int clocks) { if (clocks > 0) while ((int)(clk32() - c0) < clocks) {} }
__device__ __forceinline__ void backoff(int clocks) { if (clocks > 0) wait_until(clk32(), clocks); }
__device__ __forceinline__ uint32_t pin32(uint32_t p) { asm volatile("" : "+r"(p)); return p; }
template <typename T> __device__ __forceinline__ T* pin(T* p) { asm volatile("" : "+l"(p)); return p; }
__device__ __forceinline__ uint32_t hold32(uint32_t p) { asm volatile("shfl.sync.bfly.b32 %0, %0, 0, 0x1f, 0xffffffff;" : "+r"(p) :: "memory"); return p; }
__device__ __forceinline__ float holdf(float p) { return __uint_as_float(hold32(__float_as_uint(p))); }
template <typename T> __device__ __forceinline__ T* hold(T* p) {
  asm volatile("{\n.reg .b32 a, b;\nmov.b64 {a, b}, %0;\nshfl.sync.bfly.b32 a, a, 0, 0x1f, 0xffffffff;\nshfl.sync.bfly.b32 b, b, 0, 0x1f, 0xffffffff;\nmov.b64 %0, {a, b};\n}" : "+l"(p) :: "memory");
  return p;
}
constexpr int SPIN_LIMIT = 1 << 22;
__device__ __forceinline__ void mbar_wait(uint32_t bar) {
  asm volatile("{\n.reg .pred p;\nMW_LOOP:\nmbarrier.try_wait.parity.shared::cta.b64 p, [%0], 0;\n@!p bra MW_LOOP;\n}" ::"r"(bar) : "memory");
}
__device__ __forceinline__ void mbar_wait_b(uint32_t bar) {
  asm volatile("{\n.reg .pred p;\n.reg .u32 c;\nmov.u32 c, 0;\n"
               "MW_LOOP:\nmbarrier.try_wait.parity.shared::cta.b64 p, [%0], 0;\n@p bra MW_DONE;\n"
               "add.u32 c, c, 1;\nsetp.lt.u32 p, c, 1048576;\n@p bra MW_LOOP;\ntrap;\nMW_DONE:\n}"
               ::"r"(bar) : "memory");
}
__device__ __forceinline__ void tma2d(uint32_t dst, const CUtensorMap* m, int c0, int c1, uint32_t bar, uint64_t pol) {
  asm volatile("cp.async.bulk.tensor.2d.shared::cluster.global.mbarrier::complete_tx::bytes.L2::cache_hint [%0], [%1, {%3,%4}], [%2], %5;"
               ::"r"(dst), "l"(m), "r"(bar), "r"(c0), "r"(c1), "l"(pol) : "memory");
}
__device__ __forceinline__ void tma2d_both(uint32_t dst, const CUtensorMap* m, int c0, int c1, uint32_t bar, uint64_t pol) {
  asm volatile("cp.async.bulk.tensor.2d.shared::cluster.global.mbarrier::complete_tx::bytes.multicast::cluster.L2::cache_hint [%0], [%1, {%3,%4}], [%2], %6, %5;"
               ::"r"(dst), "l"(m), "r"(bar), "r"(c0), "r"(c1), "l"(pol), "h"((uint16_t)3) : "memory");
}
__device__ __forceinline__ void tma3d(uint32_t dst, const CUtensorMap* m, int c0, int c1, int c2, uint32_t bar, uint64_t pol) {
  asm volatile("cp.async.bulk.tensor.3d.shared::cluster.global.mbarrier::complete_tx::bytes.L2::cache_hint [%0], [%1, {%3,%4,%5}], [%2], %6;"
               ::"r"(dst), "l"(m), "r"(bar), "r"(c0), "r"(c1), "r"(c2), "l"(pol) : "memory");
}
__device__ __forceinline__ void tma5d(uint32_t dst, const CUtensorMap* m, int c0, int c3, int c4, uint32_t bar, uint64_t pol) {
  asm volatile("cp.async.bulk.tensor.5d.shared::cluster.global.mbarrier::complete_tx::bytes.L2::cache_hint [%0], [%1, {%3,%7,%7,%4,%5}], [%2], %6;"
               ::"r"(dst), "l"(m), "r"(bar), "r"(c0), "r"(c3), "r"(c4), "l"(pol), "r"(0) : "memory");
}
__device__ __forceinline__ void cbar() { asm volatile("bar.sync 1, 256;" ::: "memory"); }
__device__ __forceinline__ void wg0bar() { asm volatile("bar.sync 2, 128;" ::: "memory"); }
__device__ __forceinline__ bool cbar_or(bool p) {
  uint32_t r;
  asm volatile("{\n.reg .pred p, q;\nsetp.ne.u32 p, %1, 0;\nbarrier.cta.red.or.aligned.pred q, 1, 256, p;\nselp.u32 %0, 1, 0, q;\n}" : "=r"(r) : "r"((uint32_t)p) : "memory");
  return r;
}

__device__ __forceinline__ uint32_t ldg_rlx1(const void* p) { uint32_t v; asm volatile("ld.relaxed.gpu.global.u32 %0, [%1];" : "=r"(v) : "l"(p) : "memory"); return v; }
__device__ __forceinline__ void stg4(void* p, uint4 v) { asm volatile("st.relaxed.gpu.global.v4.u32 [%0], {%1,%2,%3,%4};" ::"l"(p), "r"(v.x), "r"(v.y), "r"(v.z), "r"(v.w) : "memory"); }
__device__ __forceinline__ void stg1(void* p, uint32_t a) { asm volatile("st.relaxed.gpu.global.u32 [%0], %1;" ::"l"(p), "r"(a) : "memory"); }
__device__ __forceinline__ uint32_t nz(uint32_t w) { uint32_t r; asm("max.u32 %0, %1, 1;" : "=r"(r) : "r"(w)); return r; }
__device__ __forceinline__ uint32_t min3(uint32_t a, uint32_t b, uint32_t c) { return min(min(a, b), c); }

__device__ __forceinline__ uint32_t pack_bf16(float lo, float hi) { uint32_t r; asm("cvt.rn.bf16x2.f32 %0, %1, %2;" : "=r"(r) : "f"(hi), "f"(lo)); return r; }
__device__ __forceinline__ float bf_lo(uint32_t w) { return __uint_as_float(w << 16); }
__device__ __forceinline__ float bf_hi(uint32_t w) { return __uint_as_float(w & 0xffff0000u); }
__device__ __forceinline__ float ex2(float x) { float r; asm("ex2.approx.ftz.f32 %0, %1;" : "=f"(r) : "f"(x)); return r; }
__device__ __forceinline__ float rcp(float x) { float r; asm("rcp.approx.ftz.f32 %0, %1;" : "=f"(r) : "f"(x)); return r; }
__device__ __forceinline__ float rsq(float x) { float r; asm("rsqrt.approx.ftz.f32 %0, %1;" : "=f"(r) : "f"(x)); return r; }
__device__ __forceinline__ uint32_t silu2(uint32_t c) {
  const float a = bf_lo(c), b = bf_hi(c);
  return pack_bf16(__fdividef(a, 1.f + __expf(-a)), __fdividef(b, 1.f + __expf(-b)));
}
__device__ __forceinline__ uint32_t shl_clamp(uint32_t x, int s) { uint32_t r; asm("shl.b32 %0, %1, %2;" : "=r"(r) : "r"(x), "r"(s)); return r; }

__device__ __forceinline__ void ldsm4(uint32_t (&r)[4], uint32_t a) { asm volatile("ldmatrix.sync.aligned.m8n8.x4.shared.b16 {%0,%1,%2,%3}, [%4];" : "=r"(r[0]), "=r"(r[1]), "=r"(r[2]), "=r"(r[3]) : "r"(a) : "memory"); }
__device__ __forceinline__ void ldsm4t(uint32_t (&r)[4], uint32_t a) { asm volatile("ldmatrix.sync.aligned.m8n8.x4.trans.shared.b16 {%0,%1,%2,%3}, [%4];" : "=r"(r[0]), "=r"(r[1]), "=r"(r[2]), "=r"(r[3]) : "r"(a) : "memory"); }
__device__ __forceinline__ void ldsm2t(uint32_t& r0, uint32_t& r1, uint32_t a) { asm volatile("ldmatrix.sync.aligned.m8n8.x2.trans.shared.b16 {%0,%1}, [%2];" : "=r"(r0), "=r"(r1) : "r"(a) : "memory"); }
__device__ __forceinline__ void stsm4t(uint32_t a, uint32_t r0, uint32_t r1, uint32_t r2, uint32_t r3) { asm volatile("stmatrix.sync.aligned.m8n8.x4.trans.shared.b16 [%0], {%1,%2,%3,%4};" ::"r"(a), "r"(r0), "r"(r1), "r"(r2), "r"(r3) : "memory"); }
__device__ __forceinline__ void stsm2t(uint32_t a, uint32_t r0, uint32_t r1) { asm volatile("stmatrix.sync.aligned.m8n8.x2.trans.shared.b16 [%0], {%1,%2};" ::"r"(a), "r"(r0), "r"(r1) : "memory"); }
__device__ __forceinline__ void mma16816(float (&d)[4], const uint32_t (&a)[4], uint32_t b0, uint32_t b1) {
  asm volatile("mma.sync.aligned.m16n8k16.row.col.f32.bf16.bf16.f32 {%0,%1,%2,%3}, {%4,%5,%6,%7}, {%8,%9}, {%0,%1,%2,%3};"
               : "+f"(d[0]), "+f"(d[1]), "+f"(d[2]), "+f"(d[3]) : "r"(a[0]), "r"(a[1]), "r"(a[2]), "r"(a[3]), "r"(b0), "r"(b1));
}
__device__ __forceinline__ void mma_v(float (&d)[4], const uint4& a, uint32_t b0, uint32_t b1) {
  asm volatile("mma.sync.aligned.m16n8k16.row.col.f32.bf16.bf16.f32 {%0,%1,%2,%3}, {%4,%5,%6,%7}, {%8,%9}, {%0,%1,%2,%3};"
               : "+f"(d[0]), "+f"(d[1]), "+f"(d[2]), "+f"(d[3]) : "r"(a.x), "r"(a.y), "r"(a.z), "r"(a.w), "r"(b0), "r"(b1));
}
__device__ __forceinline__ void sts1(uint32_t a, uint32_t v) { asm volatile("st.shared.u32 [%0], %1;" ::"r"(a), "r"(v) : "memory"); }
__device__ __forceinline__ void sts2(uint32_t a, uint32_t x, uint32_t y) { asm volatile("st.shared.v2.u32 [%0], {%1,%2};" ::"r"(a), "r"(x), "r"(y) : "memory"); }
__device__ __forceinline__ void sts4(uint32_t a, uint4 v) { asm volatile("st.shared.v4.u32 [%0], {%1,%2,%3,%4};" ::"r"(a), "r"(v.x), "r"(v.y), "r"(v.z), "r"(v.w) : "memory"); }
__device__ __forceinline__ void sts4f(uint32_t a, float x, float y, float z, float w) { asm volatile("st.shared.v4.f32 [%0], {%1,%2,%3,%4};" ::"r"(a), "f"(x), "f"(y), "f"(z), "f"(w) : "memory"); }
__device__ __forceinline__ void sts2f(uint32_t a, float x, float y) { asm volatile("st.shared.v2.f32 [%0], {%1,%2};" ::"r"(a), "f"(x), "f"(y) : "memory"); }
__device__ __forceinline__ void stsf(uint32_t a, float v) { asm volatile("st.shared.f32 [%0], %1;" ::"r"(a), "f"(v) : "memory"); }
__device__ __forceinline__ uint32_t lds1(uint32_t a) { uint32_t v; asm volatile("ld.shared.u32 %0, [%1];" : "=r"(v) : "r"(a) : "memory"); return v; }
__device__ __forceinline__ uint2 lds2(uint32_t a) { uint2 v; asm volatile("ld.shared.v2.u32 {%0,%1}, [%2];" : "=r"(v.x), "=r"(v.y) : "r"(a) : "memory"); return v; }
__device__ __forceinline__ float ldsf(uint32_t a) { float v; asm volatile("ld.shared.f32 %0, [%1];" : "=f"(v) : "r"(a) : "memory"); return v; }
__device__ __forceinline__ float2 ldsf2(uint32_t a) { float2 v; asm volatile("ld.shared.v2.f32 {%0,%1}, [%2];" : "=f"(v.x), "=f"(v.y) : "r"(a) : "memory"); return v; }
__device__ __forceinline__ float4 ldsf4(uint32_t a) { float4 v; asm volatile("ld.shared.v4.f32 {%0,%1,%2,%3}, [%4];" : "=f"(v.x), "=f"(v.y), "=f"(v.z), "=f"(v.w) : "r"(a) : "memory"); return v; }
__device__ __forceinline__ uint4 lds4(uint32_t a) { uint4 v; asm volatile("ld.shared.v4.u32 {%0,%1,%2,%3}, [%4];" : "=r"(v.x), "=r"(v.y), "=r"(v.z), "=r"(v.w) : "r"(a) : "memory"); return v; }

__device__ __forceinline__ void wg_fence() { asm volatile("wgmma.fence.sync.aligned;" ::: "memory"); }
__device__ __forceinline__ void wg_commit() { asm volatile("wgmma.commit_group.sync.aligned;" ::: "memory"); }
template <int N> __device__ __forceinline__ void wg_wait() { asm volatile("wgmma.wait_group.sync.aligned %0;" ::"n"(N) : "memory"); }
__host__ __device__ constexpr uint32_t dlo(uint32_t addr) { return (addr >> 4) | 0x10000u; }
constexpr uint32_t ONE2 = 0x3f803f80u;
template <int TA, int ACC> __device__ __forceinline__ void wgmma_ss(float (&d)[16], uint32_t da, uint32_t db) {
  asm volatile("{\n.reg .b64 da, db;\nmov.b64 da, {%16, 0x40000040};\nmov.b64 db, {%17, 0x40000040};\n"
               "wgmma.mma_async.sync.aligned.m64n32k16.f32.bf16.bf16 {%0,%1,%2,%3,%4,%5,%6,%7,%8,%9,%10,%11,%12,%13,%14,%15}, da, db, %18, 1, 1, %19, 0;\n}"
               : "+f"(d[0]), "+f"(d[1]), "+f"(d[2]), "+f"(d[3]), "+f"(d[4]), "+f"(d[5]), "+f"(d[6]), "+f"(d[7]),
                 "+f"(d[8]), "+f"(d[9]), "+f"(d[10]), "+f"(d[11]), "+f"(d[12]), "+f"(d[13]), "+f"(d[14]), "+f"(d[15])
               : "r"(da), "r"(db), "n"(ACC), "n"(TA));
}
template <int TA, int ACC> __device__ __forceinline__ void wgmma_ss(float (&d)[8], uint32_t da, uint32_t db) {
  asm volatile("{\n.reg .b64 da, db;\nmov.b64 da, {%8, 0x40000040};\nmov.b64 db, {%9, 0x40000040};\n"
               "wgmma.mma_async.sync.aligned.m64n16k16.f32.bf16.bf16 {%0,%1,%2,%3,%4,%5,%6,%7}, da, db, %10, 1, 1, %11, 0;\n}"
               : "+f"(d[0]), "+f"(d[1]), "+f"(d[2]), "+f"(d[3]), "+f"(d[4]), "+f"(d[5]), "+f"(d[6]), "+f"(d[7])
               : "r"(da), "r"(db), "n"(ACC), "n"(TA));
}
__device__ __forceinline__ void wgmma_n8(float (&d)[4], uint32_t da, uint32_t db) {
  asm volatile("{\n.reg .b64 da, db;\nmov.b64 da, {%4, 0x40000040};\nmov.b64 db, {%5, 0x40000040};\n"
               "wgmma.mma_async.sync.aligned.m64n8k16.f32.bf16.bf16 {%0,%1,%2,%3}, da, db, 1, 1, 1, 1, 0;\n}"
               : "+f"(d[0]), "+f"(d[1]), "+f"(d[2]), "+f"(d[3]) : "r"(da), "r"(db));
}
template <int K> __device__ __forceinline__ void tie(float (&d)[K]) {
#pragma unroll
  for (int i = 0; i < K; i += 8)
    asm volatile("" : "+f"(d[i]), "+f"(d[i + 1]), "+f"(d[i + 2]), "+f"(d[i + 3]), "+f"(d[i + 4]), "+f"(d[i + 5]), "+f"(d[i + 6]), "+f"(d[i + 7]) :: "memory");
}
__device__ __forceinline__ void tie(uint4& v) { asm volatile("" : "+r"(v.x), "+r"(v.y), "+r"(v.z), "+r"(v.w) :: "memory"); }
__device__ __forceinline__ void tie(uint2& v) { asm volatile("" : "+r"(v.x), "+r"(v.y) :: "memory"); }
template <int I> struct IC { static constexpr int value = I; };
template <int B, int E, typename F> __device__ __forceinline__ void sfor(F&& f) { if constexpr (B < E) { f(IC<B>{}); sfor<B + 1, E>(f); } }

__device__ __forceinline__ uint2 ldg_u64(const void* p) {
  uint2 v; asm volatile("{\n.reg .b64 a;\nld.relaxed.gpu.global.b64 a, [%2];\nmov.b64 {%0,%1}, a;\n}" : "=r"(v.x), "=r"(v.y) : "l"(p) : "memory"); return v;
}
__device__ __forceinline__ uint4 ldg_2u64(const void* p) {
  uint4 v; asm volatile("{\n.reg .b64 a, b;\nld.relaxed.gpu.global.v2.b64 {a, b}, [%4];\nmov.b64 {%0,%1}, a;\nmov.b64 {%2,%3}, b;\n}" : "=r"(v.x), "=r"(v.y), "=r"(v.z), "=r"(v.w) : "l"(p) : "memory"); return v;
}
__device__ __forceinline__ uint4 ldg_u128(const void* p) {
  uint4 v; asm volatile("{\n.reg .b64 a, b;\n.reg .b128 q;\nld.relaxed.gpu.global.b128 q, [%4];\nmov.b128 {a, b}, q;\nmov.b64 {%0,%1}, a;\nmov.b64 {%2,%3}, b;\n}" : "=r"(v.x), "=r"(v.y), "=r"(v.z), "=r"(v.w) : "l"(p) : "memory"); return v;
}
__device__ __forceinline__ void stg_u64(void* p, uint32_t x, uint32_t y) {
  asm volatile("{\n.reg .b64 a;\nmov.b64 a, {%1,%2};\nst.relaxed.gpu.global.b64 [%0], a;\n}" ::"l"(p), "r"(x), "r"(nz(y)) : "memory");
}
__device__ __forceinline__ void stg4_b128(void* p, uint4 v) {
  asm volatile("{\n.reg .b64 a, b;\n.reg .b128 q;\nmov.b64 a, {%1,%2};\nmov.b64 b, {%3,%4};\nmov.b128 q, {a, b};\nst.relaxed.gpu.global.b128 [%0], q;\n}" ::"l"(p), "r"(v.x), "r"(v.y), "r"(v.z), "r"(v.w) : "memory");
}
__device__ __forceinline__ void stg_u128(void* p, uint4 v) {
  asm volatile("{\n.reg .b64 a, b;\n.reg .b128 q;\nmov.b64 a, {%1,%2};\nmov.b64 b, {%3,%4};\nmov.b128 q, {a, b};\nst.relaxed.gpu.global.b128 [%0], q;\n}" ::"l"(p), "r"(v.x), "r"(v.y), "r"(v.z), "r"(nz(v.w)) : "memory");
}
__device__ __forceinline__ uint32_t hmul2(uint32_t a, uint32_t b) { uint32_t r; asm("mul.rn.bf16x2 %0, %1, %2;" : "=r"(r) : "r"(a), "r"(b)); return r; }
__device__ __forceinline__ uint32_t hadd2(uint32_t a, uint32_t b) { uint32_t r; asm("add.rn.bf16x2 %0, %1, %2;" : "=r"(r) : "r"(a), "r"(b)); return r; }
__device__ __forceinline__ uint32_t movm(uint32_t a) { uint32_t d; asm volatile("movmatrix.sync.aligned.m8n8.trans.b16 %0, %1;" : "=r"(d) : "r"(a)); return d; }
__device__ __forceinline__ uint2 ldg_rlx2(const void* p) { uint2 v; asm volatile("ld.relaxed.gpu.global.v2.u32 {%0,%1}, [%2];" : "=r"(v.x), "=r"(v.y) : "l"(p) : "memory"); return v; }
__device__ __forceinline__ uint4 ldg_in4(const void* p) { uint4 v; asm volatile("ld.global.nc.v4.u32 {%0,%1,%2,%3}, [%4];" : "=r"(v.x), "=r"(v.y), "=r"(v.z), "=r"(v.w) : "l"(p) : "memory"); return v; }
__device__ __forceinline__ uint32_t ldg_in1(const void* p) { uint32_t v; asm volatile("ld.global.nc.u32 %0, [%1];" : "=r"(v) : "l"(p)); return v; }

template <typename F> __device__ __forceinline__ void sum4_to_smem(uint2 (&v)[4], const uint32_t* x, const uint32_t* y, uint32_t dst, F&& meanwhile) {
  uint32_t r0, r1;
#pragma unroll 1
  while (true) {
    meanwhile();
#pragma unroll
    for (int i = 0; i < 4; i++) tie(v[i]);
    const bool ok = __all_sync(~0u, min(min3(v[0].y, v[1].y, v[2].y), v[3].y) != 0);
    r0 = pack_bf16((bf_lo(v[0].x) + bf_lo(v[1].x)) + (bf_lo(v[2].x) + bf_lo(v[3].x)), (bf_hi(v[0].x) + bf_hi(v[1].x)) + (bf_hi(v[2].x) + bf_hi(v[3].x)));
    r1 = pack_bf16((bf_lo(v[0].y) + bf_lo(v[1].y)) + (bf_lo(v[2].y) + bf_lo(v[3].y)), (bf_hi(v[0].y) + bf_hi(v[1].y)) + (bf_hi(v[2].y) + bf_hi(v[3].y)));
    sts1(dst, r0);
    sts1(dst + 128, r1);
    if (ok) break;
#pragma unroll
    for (int i = 0; i < 4; i++) v[i] = ldg_u64(((i & 2) ? y : x) + (i & 1) * 512);
  }
}
__device__ __forceinline__ void load_a_t(uint32_t (&a)[8][4], uint32_t box, int wq, int lane) {
  const int mi = lane >> 3, r = lane & 7;
  const uint32_t base = box + (8 * (mi >> 1) + r) * 128 + (((2 * wq + (mi & 1)) ^ r) << 4);
#pragma unroll
  for (int ks = 0; ks < 8; ks++) ldsm4t(a[ks], base + ks * 2048);
}
__device__ __forceinline__ void mma128(float (&d)[4], const uint32_t (&a)[8][4], uint32_t bs) {
  float e[4][4] = {{0.f, 0.f, 0.f, 0.f}, {0.f, 0.f, 0.f, 0.f}, {0.f, 0.f, 0.f, 0.f}, {0.f, 0.f, 0.f, 0.f}};
  uint32_t b[4][4];
#pragma unroll
  for (int kk = 0; kk < 4; kk++) ldsm4t(b[kk], bs + 32 * kk * 16);
#pragma unroll
  for (int kk = 0; kk < 4; kk++) { mma16816(e[(2 * kk) & 3], a[2 * kk], b[kk][0], b[kk][1]); mma16816(e[(2 * kk + 1) & 3], a[2 * kk + 1], b[kk][2], b[kk][3]); }
#pragma unroll
  for (int i = 0; i < 4; i++) d[i] = (e[0][i] + e[1][i]) + (e[2][i] + e[3][i]);
}
template <int NL, typename F> __device__ __forceinline__ void poll_vectors(const uint32_t* p, const uint32_t* q, F&& f) {
  int it = 0;
  bool ok;
  uint4 v[NL];
#pragma unroll
  for (int i = 0; i < NL; i++) v[i] = make_uint4(0, 0, 0, 0);
#pragma unroll 1
  do {
    if (++it > SPIN_LIMIT) __trap();
#pragma unroll
    for (int i = 0; i < NL; i++) if (NL <= 4 || min(v[i].y, v[i].w) == 0) v[i] = ldg_2u64(i < NL / 2 ? p + i * 128 : q + (i - NL / 2) * 128);
    f(v);
    uint32_t m0 = min(v[0].y, v[0].w), m1 = min(v[1].y, v[1].w);
#pragma unroll
    for (int i = 2; i < NL; i += 2) { m0 = min3(m0, v[i].y, v[i].w); m1 = min3(m1, v[i + 1].y, v[i + 1].w); }
    ok = __all_sync(~0u, min(m0, m1) != 0);
  } while (!ok);
}

__global__ void __cluster_dims__(2, 1, 1) __launch_bounds__(NTHREADS, 1)
fused_decode_kernel(__nv_bfloat16* __restrict__ gout, Scratch* __restrict__ gs, const uint8_t* __restrict__ gwq,
                    const uint8_t* __restrict__ gx, const uint8_t* __restrict__ gc,
                    const __grid_constant__ Params P) {
  extern __shared__ __align__(1024) uint8_t smem_raw[];
  const uint32_t hi = pin32((uint32_t)__cvta_generic_to_shared(smem_raw) - SB);
  const int tid = threadIdx.x, lane = tid & 31;
  const int w = __shfl_sync(0xffffffffu, tid >> 5, 0);
  const int cta = blockIdx.x;
  const int g = lane >> 2, t = lane & 3;
  const int hI = cta >> 2, jI = cta & 3;
  const int bI = cta >> 4, pI = (cta >> 1) & 7, rI = cta & 1;

  uint32_t epoch0 = 0;
  if (tid == 320) epoch0 = ldg_rlx1(&gs->epoch);
  const bool p0a = (cta & 7) == 0;
  uint4 cw0, cw1, xr0, xr1;
  uint32_t xc;
  if (w < 8) {
    const uint8_t* src = gwq + (size_t)(128 * jI + (tid >> 4)) * 8192 + hI * 256 + (tid & 15) * 16;
    const uint32_t dst = hi + OFF_R1 + ((tid >> 3) & 1) * 16384 + (tid >> 4) * 128 + (((tid ^ (tid >> 4)) & 7) << 4);
    if (p0a) {
      cw0 = ldg_in4(gc + g * 1024 + w * 128 + t * 32); cw1 = ldg_in4(gc + g * 1024 + w * 128 + t * 32 + 16);
      xr0 = ldg_in4(gx + w * 1024 + lane * 16); xr1 = ldg_in4(gx + w * 1024 + 512 + lane * 16);
      xc = ldg_in1(gx + w * 1024 + (cta & 63) * 16 + lane * 4);
    } else {
#pragma unroll
      for (int i = 0; i < 4; i++) asm volatile("cp.async.cg.shared.global [%0], [%1], 16;" ::"r"(dst + i * 2048), "l"(src + i * 16 * 8192) : "memory");
    }
  }
  auto half_of = [&](int c, int k) { return ((lds1(hi + OFF_FM + (c >> 5) * 4) >> (c & 31)) ^ k) & 1; };
  auto inbox = [&](int c, int k, uint32_t bits, int pos, int off) { return gs->IN[0] + (uint32_t)(c * 16384 + k * 2048 + off + (((bits >> pos) & 1) << 10)); };
  auto front_unit = [&](int k, uint64_t pol) {
    tma2d(hi + OFF_R1 + ((k & 4) + 2 * (k & 1) + ((k >> 1) & 1)) * 8192, k < 4 ? &P.wq : &P.wuk, 128 * hI + 64 * (k & 1), 128 * jI + 64 * ((k >> 1) & 1), hi + BAR(k), pol);
  };
  uint32_t tnext = 0;
  if (tid == 256) {
    tnext = gtime32() + PACE_T0;
    if (hi & 0xffffff) __trap();
    if (p0a) {
#pragma unroll
      for (int i = 0; i < 4; i++) mbar_init(hi + BAR(BAR_WA + i), 1);
      asm volatile("fence.mbarrier_init.release.cluster;" ::: "memory");
      uint64_t pol; asm volatile("createpolicy.fractional.L2::evict_first.b64 %0, 1.0;" : "=l"(pol));
#pragma unroll
      for (int i = 0; i < 4; i++) tma2d(hi + slot(8 + 2 * i), &P.wma, 8 * cta, 128 * i, hi + BAR(BAR_WA + i), pol);
    }
    asm volatile("prefetch.tensormap [%0];" ::"l"(&P.wq) : "memory");
  } else if (tid == 288) {
#pragma unroll
    for (int i = 0; i < BAR_WA; i++)
      mbar_init(hi + BAR(i), (i >= BAR_EMPTY && i < BAR_EMPTY + 5) ? 16 : (i >= BAR_P2E && i <= BAR_P7D) ? 8 : i == BAR_P0D ? 4 : 1);
    asm volatile("fence.mbarrier_init.release.cluster;" ::: "memory");
  }
  __syncthreads();

  if (w == 8) {
    auto twice = [](int n) { return (n & ~1) == U_W1 || (n & ~1) == U_WMOD; };
    if (p0a && lane < 4) mbar_expect(hi + BAR(BAR_WA) + 8 * lane, 16384);
    mbar_expect(hi + BAR(0) + 8 * lane, (lane < 2 && !p0a) ? 0 : 8192);
    if (p0a) tnext -= 2 * PACE_DT;
    if (lane < BAR_EMPTY - 32) mbar_expect(hi + BAR(32) + 8 * lane, twice(32 + lane - BAR_FULL) ? 16384 : 8192);
    __syncwarp();
    const int h = hI, j = jI;
    if (lane == 0) {
      uint64_t pol; asm volatile("createpolicy.fractional.L2::evict_first.b64 %0, 1.0;" : "=l"(pol));
      auto pace = [&](int dt) { while ((int)(gtime32() - tnext) < 0) {} tnext += dt; };
      asm volatile("prefetch.tensormap [%0];" ::"l"(&P.wuk) : "memory");
      asm volatile("prefetch.tensormap [%0];" ::"l"(&P.wmod) : "memory");
      asm volatile("prefetch.tensormap [%0];" ::"l"(&P.ckv) : "memory");
#pragma unroll 1
      for (int k = p0a ? 0 : 2; k < 8; k++) { if (k >= WIN_PRE) mbar_wait(hi + BAR(0) + 8 * (k - WIN_PRE)); pace(PACE_DT); front_unit(k, pol); }
      bool go = false;
      const int row0 = bI * 4096 + (cta & 15) * 64;
#pragma unroll 1
      for (int n = 0; n < 24; n++) {
        if (n == 8 && p0a) mbar_wait(hi + BAR(BAR_P0D));
        if (n == 16) mbar_wait(hi + BAR(BAR_P2E));
        if (n == 23) mbar_wait(hi + BAR(BAR_EMPTY));
        if (!go) go = mbar_test(hi + BAR(BAR_GO));
        mbar_wait(hi + BAR(BAR_FULL) + 8 * (n - (go ? WIN_MID : WIN_PRE)));
        pace(PACE_DT);
        tma2d(hi + slot(box_slot(n)), &P.ckv, (n & 7) * 64, row0 + (n >> 3) * 1024, hi + BAR(BAR_FULL) + 8 * n, pol);
      }
      asm volatile("prefetch.tensormap [%0];" ::"l"(&P.wuv) : "memory");
      asm volatile("prefetch.tensormap [%0];" ::"l"(&P.wo) : "memory");
      asm volatile("prefetch.tensormap [%0];" ::"l"(&P.w1) : "memory");
      asm volatile("prefetch.tensormap [%0];" ::"l"(&P.w2) : "memory");
      const int row1 = bI * 4096 + (24 + pI) * 64;
      tnext += rI * (PACE_DT / 2) - PACE_DT / 4;
#pragma unroll 1
      for (int n = 24 + rI; n < 40; n += 2) {
        const int c = n - 23;
        const int m = c >= 2 * WIN_END ? n - 2 * WIN_END : 23 - (2 * WIN_END - c) / 2;
        mbar_wait(hi + BAR(BAR_FULL) + 8 * m);
        mbar_wait(hi + BAR(BAR_EMPTY) + (c & ~7));
        pace(PACE_DTE);
        tma2d_both(hi + slot(c), &P.ckv, (n & 7) * 64, row1 + (n >> 3) * 512, hi + BAR(BAR_FULL) + 8 * n, pol);
      }
      mbar_wait(hi + BAR(BAR_EMPTY + 2));
      const bool late = cta >= 96;
      auto unit = [&](int i) { return (!late || i < U_WMOD || i >= U_W1) ? i : i < U_W1 - 2 ? i + 2 : i - 8; };
      if (late) tnext += 2 * PACE_DTW;
#pragma unroll 1
      for (int i = U_WMOD; i < (cta < NFF ? NUNITS : U_W1); i++) {
        const int n = unit(i), c = i - 39, u = n & 1;
        mbar_wait(hi + BAR(BAR_FULL) + 8 * (c >= WIN_TAIL ? unit(i - WIN_TAIL) : 39 - 2 * (WIN_TAIL - c)));
        if (n == U_WUV + 3) mbar_wait(hi + BAR(BAR_EMPTY + 3));
        if (n == U_WO) tnext += PACE_GAP3;
        if (n == U_W1) { mbar_wait(hi + BAR(BAR_EMPTY + 4)); tnext += PACE_GAP4; }
        const uint32_t bar = hi + BAR(BAR_FULL) + 8 * n;
        pace(n < U_WUV ? (late ? PACE_DTL : PACE_DTW) : n < U_WO ? PACE_DT2 : n < U_W1 ? PACE_DT3 : PACE_DT4);
        if (twice(n)) tma2d_both(hi + (n < U_WO ? OFF_WM : OFF_W1) + (2 * u + rI) * 8192, n < U_WO ? &P.wmod : &P.w1, (n < U_WO ? 1024 : 0) + 16 * (cta & ~1), 256 * u + 128 * rI, bar, pol);
        else if (n < U_WO) tma5d(hi + slot(n < U_WUV + 2 ? n - 21 : n - 44), &P.wuv, 128 * h + 64 * u, (n - U_WUV) & 2, 2 * j, bar, pol);
        else if (n < U_W1) tma2d(hi + slot(n - 41), &P.wo, 128 * j + 64 * u, 128 * h + 32 * ((n - U_WO) & 2), bar, pol);
        else tma3d(hi + OFF_W2 + u * 8192, &P.w2, 0, FCH * cta, 4 * u, bar, pol);
      }
    }
    return;
  }

  if (w == 11) {
    const uint4 z = make_uint4(0, 0, 0, 0);
    uint32_t f = 0, f2 = 0;
    {
      uint32_t* const p = ((lane & 2) ? gs->X3B + 4 * 2048 + cta * 8 : gs->IN[cta] + 4 * 2048 + 960) + ((lane & 1) << 10);
      if (lane < 8) stg4(p + (lane & 4), z);
      __syncwarp();
      uint32_t best = ~0u;
#pragma unroll 1
      for (int i = 0; i < 4 * NPROBE + (int)(hi & 1); i++) {
        uint32_t v = 0;
        const uint32_t c0 = clk32();
        if (lane == (i & 3)) asm volatile("atom.relaxed.gpu.global.exch.b32 %0, [%1], %2;" : "=r"(v) : "l"(p), "r"(i) : "memory");
        v = __shfl_sync(~0u, v, i & 3);
        const uint32_t dt = clk32() - c0 + (v >> 31);
        if (lane == (i & 3)) best = min(best, dt);
      }
      const uint32_t m = __ballot_sync(~0u, best < __shfl_xor_sync(~0u, best, 1));
      f = (m >> 1) & 1; f2 = (m >> 3) & 1;
    }
    mbar_wait(hi + BAR(BAR_EPOCH));
    const uint32_t epoch = lds1(hi + OFF_EPOCH);
    const int par = epoch & 1;
    if (lane == 0) stg1(gs->FL[par] + cta, 1 + f);
    mbar_wait(hi + BAR(BAR_P2E));
#pragma unroll 1
    for (int i = 0; i < 16; i++) {
      const uint32_t c0 = clk32();
      uint32_t* p = gs->IN[cta] + (i >> 1) * 2048 + (((f ^ (i >> 1)) & 1) << 10) + (i & 1) * 512 + lane * 4;
#pragma unroll
      for (int q = 0; q < 4; q++) stg4(p + q * 128, z);
      if (i == 0 && lane < 16) stg4(gs->X3B + cta * 64 + lane * 4, z);
      if (i == 1) stg4(gs->MODB + cta * 128 + lane * 4, z);
      wait_until(c0, CLR_CLK);
    }
    {
      uint32_t u[4];
      do {
#pragma unroll
        for (int i = 0; i < 4; i++) u[i] = ldg_rlx1(gs->FL[par] + 32 * i + lane);
      } while (!__all_sync(~0u, min(min(u[0], u[1]), min(u[2], u[3])) != 0));
      const uint4 m = make_uint4(__ballot_sync(~0u, u[0] == 2), __ballot_sync(~0u, u[1] == 2), __ballot_sync(~0u, u[2] == 2), __ballot_sync(~0u, u[3] == 2));
      if (lane == 0) { sts4(hi + OFF_FM, m); sts1(hi + OFF_FM + 16, f2); }
      __syncwarp();
      const uint2 m2 = lds2(hi + OFF_FM + 8 * rI);
      const uint32_t mh = (lds1(hi + OFF_FM + (hI >> 3) * 4) >> (4 * (hI & 7))) & 15;
#pragma unroll 1
      for (int v = 0; v < 8; v++) {
        const int sh = 8 * t + 2 * (v >> 2) + (bI >> 2);
        uint32_t fb = (((m2.x >> sh) & 0x11) | (((m2.y >> sh) & 0x11) << 1)) ^ ((bI & 1) ? 0x33 : 0);
        fb |= mh << 8;
        fb |= half_of(4 * (8 * jI + v) + (g >> 1), 0) << 12;
        fb |= half_of((16 * rI + 4 * (v & 3) + (lane >> 3)) * 4 + (lane & 2), 0) << 13;
        fb |= ((f2 ^ (v >> 2)) & 1) << 14;
        fb |= (((lds1(hi + OFF_FM + (v >> 1) * 4) >> (16 * (v & 1) + (g >> 1))) & 0x1111) ^ (cta >= 56 ? 0x1111 : 0)) << 16;
        sts1(hi + OFF_FB + (v * 32 + lane) * 4, fb);
      }
      __syncwarp();
      if (lane == 0) mbar_arrive(hi + BAR(BAR_FM));
    }
    asm volatile("fence.acq_rel.gpu;" ::: "memory");
    __syncwarp();
    if (lane == 0) asm volatile("red.relaxed.gpu.global.add.u32 [%0], 1;" ::"l"(&gs->cnt) : "memory");
    mbar_wait(hi + BAR(BAR_GO));
    if (lane == 0) stg1(gs->FL[par ^ 1] + cta, 0u);
#pragma unroll
    for (int i = 0; i < 4; i++) stg4(gs->QP + cta * 512 + (i * 32 + lane) * 4, z);
#pragma unroll
    for (int i = 0; i < 4; i++) stg4(gs->QX[par ^ 1] + cta * 512 + (i * 32 + lane) * 4, z);
    if (lane < 8) stg4(gs->MODA + cta * 32 + lane * 4, z);
    mbar_wait(hi + BAR(BAR_FULL + CNT_AT));
    while ((int)(ldg_rlx1(&gs->cnt) - (epoch + 1) * NCTA) < 0) __nanosleep(100);
    if (lane == 0) mbar_arrive(hi + BAR(BAR_CLR));
    return;
  }
  if (w == 10) {
    const int m0 = 16 * hI + 2 * jI;
    const int bo = lane & 7;
    const uint32_t epoch = __shfl_sync(~0u, epoch0, 0);
    if (lane == 0) { sts1(hi + OFF_EPOCH, epoch); mbar_arrive(hi + BAR(BAR_EPOCH)); }
    mbar_wait_b(hi + BAR(BAR_GO));
    const uint32_t xw0 = hold32(ldg_in1(gx + bo * 1024 + m0 * 2)), xw1 = hold32(ldg_in1(gx + bo * 1024 + m0 * 2 + 16));
    mbar_wait_b(hi + BAR(BAR_CLR));
    const uint32_t* MOD = gs->MODB + (m0 >> 8) * 1024 + ((~(lds1(hi + OFF_FM + 16) ^ (m0 >> 8)) & 1) << 10);
    mbar_wait_b(hi + BAR(BAR_FULL + GA_AT));
    const int mf = m0 + ((g >> 1) & 1) + 8 * (t >> 1), bf = 2 * (g & 1) + (t & 1);
    float ga[4];
    uint32_t gb2;
    {
      uint32_t u[4];
      int it = 0;
      while (true) {
#pragma unroll
        for (int i = 0; i < 4; i++) u[i] = ldg_rlx1(MOD + (m0 + (i & 1) + 8 * (i >> 1)) * 4 + (bo >> 1));
        if (min(min3(u[0], u[1], u[2]), u[3]) != 0) break;
        if (++it > SPIN_LIMIT) __trap();
      }
#pragma unroll
      for (int i = 0; i < 4; i++) ga[i] = (bo & 1) ? bf_hi(u[i]) : bf_lo(u[i]);
    }
    uint32_t x2a, x2b;
    mbar_wait_b(hi + BAR(BAR_FM));
    const uint32_t fo_ = half_of(cta, 0);
    {
      const uint32_t* const pi = hold(inbox(cta, 6, fo_, 0, (4 * (g >> 1) + t) * 8 + (g & 1) * 4));
      uint32_t* const po = hold(gs->X3B + (g >> 2) * 4096 + (cta >> 6) * 2048 + ((g >> 1) & 1) * 1024 + (cta & 63) * 16 + bo * 2);
      const uint32_t one = 0x3f80u << (8 * (g & 2)), s0 = g < 4 ? one : 0u, s1 = g < 4 ? 0u : one;
      const uint32_t e0 = hold32((g & 1) ? 0u : s0), e1 = hold32((g & 1) ? 0u : s1), o0 = hold32((g & 1) ? s0 : 0u), o1 = hold32((g & 1) ? s1 : 0u);
      const float xf[4] = {holdf(bf_lo(xw0)), holdf(bf_hi(xw0)), holdf(bf_lo(xw1)), holdf(bf_hi(xw1))};
#pragma unroll
      for (int i = 0; i < 4; i++) ga[i] = holdf(ga[i]);
      mbar_wait_b(hi + BAR(BAR_P5D));
      backoff(D_X3A);
      float d[4][4];
      poll_vectors<4>(pi, pi + 256, [&](const uint4 (&v)[4]) {
#pragma unroll
        for (int i = 0; i < 4; i++) { d[i][0] = d[i][1] = d[i][2] = d[i][3] = 0.f; mma_v(d[i], v[i], (i & 2) ? o0 : e0, (i & 2) ? o1 : e1); }
      });
      float s[4] = {d[0][0] + d[1][0], d[2][1] + d[3][1], d[0][2] + d[1][2], d[2][3] + d[3][3]};
#pragma unroll
      for (int i = 0; i < 4; i++) s[i] += __shfl_xor_sync(~0u, s[i], 8);
#pragma unroll
      for (int i = 0; i < 4; i++) s[i] += __shfl_xor_sync(~0u, s[i], 16);
      x2a = pack_bf16(xf[0] + ga[0] * s[0], xf[1] + ga[1] * s[1]);
      x2b = pack_bf16(xf[2] + ga[2] * s[2], xf[3] + ga[3] * s[3]);
      stg_u64(po, x2a, x2b);
      mbar_wait(hi + BAR(BAR_P5D));
    }
    {
      const uint32_t ckf = clk32();
      backoff(D_GB);
      int it = 0;
      do { gb2 = ldg_rlx1(MOD + 6 * 2048 + mf * 4 + bf); if (++it > SPIN_LIMIT) __trap(); } while (!__all_sync(~0u, gb2 != 0));
      const uint32_t a0 = __shfl_sync(~0u, x2a, 2 * bf), a1 = __shfl_sync(~0u, x2a, 2 * bf + 1);
      const uint32_t b0 = __shfl_sync(~0u, x2b, 2 * bf), b1 = __shfl_sync(~0u, x2b, 2 * bf + 1);
      const uint32_t y0 = (t & 2) ? b0 : a0, y1 = (t & 2) ? b1 : a1;
      const float r0 = holdf((g & 2) ? bf_hi(y0) : bf_lo(y0)), r1 = holdf((g & 2) ? bf_hi(y1) : bf_lo(y1)), gb0 = holdf(bf_lo(gb2)), gb1 = holdf(bf_hi(gb2));
      const uint32_t* const pi = hold(inbox(cta, 4, fo_, 0, (4 * (g >> 2) + t) * 16 + (g & 3) * 4));
      const uint32_t* const pj = hold(inbox(cta, 5, ~fo_, 0, (4 * (g >> 2) + t) * 16 + (g & 3) * 4));
      __nv_bfloat16* const fo = hold(gout + (2 * bf) * 512 + mf);
      const uint32_t one = (g & 1) ? 0x3f800000u : 0x00003f80u;
      const uint32_t s0 = hold32((g & 2) ? 0u : one), s1 = hold32((g & 2) ? one : 0u);
      if (cta < NFF) { mbar_wait_b(hi + BAR(BAR_P7D)); backoff(D_FIN); } else wait_until(ckf, D_FIN2);
      float d[4][4];
      poll_vectors<NFF / 8>(pi, pj, [&](const uint4 (&v)[NFF / 8]) {
#pragma unroll
        for (int i = 0; i < 4; i++) d[i][0] = d[i][1] = d[i][2] = d[i][3] = 0.f;
#pragma unroll
        for (int i = 0; i < NFF / 8; i++) mma_v(d[i & 3], v[i], s0, s1);
      });
      const bool up = t & 2;
      float v0 = up ? (d[0][2] + d[1][2]) + (d[2][2] + d[3][2]) : (d[0][0] + d[1][0]) + (d[2][0] + d[3][0]);
      float v1 = up ? (d[0][3] + d[1][3]) + (d[2][3] + d[3][3]) : (d[0][1] + d[1][1]) + (d[2][1] + d[3][1]);
      v0 += __shfl_xor_sync(~0u, v0, 16);
      v1 += __shfl_xor_sync(~0u, v1, 16);
      if (g < 4) {
        asm volatile("st.global.u16 [%0], %1;" ::"l"(fo), "h"(__bfloat16_as_ushort(__float2bfloat16(r0 + gb0 * v0))) : "memory");
        asm volatile("st.global.u16 [%0], %1;" ::"l"(fo + 512), "h"(__bfloat16_as_ushort(__float2bfloat16(r1 + gb1 * v1))) : "memory");
      }
    }
    if (cta == 0 && lane == 0) stg1(&gs->epoch, epoch + 1);
    return;
  }

  if (w == 9) {
    uint32_t cf[16][4];
    asm volatile("bar.sync 3, 288;" ::: "memory");
#pragma unroll
    for (int i = 0; i < 16; i++) ldsm4(cf[i], hi + OFF_R0 + (i >> 1) * 1024 + (lane & 7) * 128 + (((4 * (i & 1) + (lane >> 3)) ^ (lane & 7)) << 4));
#pragma unroll
    for (int i = 0; i < 16; i++) cf[i][0] = hold32(cf[i][0]);
    asm volatile("bar.arrive 2, 288;" ::: "memory");
    if (lane == 0) mbar_expect(hi + BAR(BAR_XE), 16384 + 128);
    {
      uint32_t* const mo = gs->MODB + (cta >> 4) * 2048 + (cta & 15) * 64 + lane;
      mbar_wait(hi + BAR(BAR_CLR));
      const uint32_t base = hi + OFF_WM + (8 * (lane >> 4) + (lane & 7)) * 64 + (((2 * rI + ((lane >> 3) & 1)) ^ ((lane & 7) >> 1)) << 4);
      float d[4][4] = {{0.f, 0.f, 0.f, 0.f}, {0.f, 0.f, 0.f, 0.f}, {0.f, 0.f, 0.f, 0.f}, {0.f, 0.f, 0.f, 0.f}};
#pragma unroll
      for (int q = 0; q < 4; q++) {
        if (!(q & 1)) mbar_wait(hi + BAR(BAR_FULL + U_WMOD + (q >> 1)));
        uint32_t a[8][4];
#pragma unroll
        for (int ks = 0; ks < 8; ks++) ldsm4t(a[ks], base + (8 * q + ks) * 1024);
#pragma unroll
        for (int ks = 0; ks < 8; ks++) mma16816(d[ks & 3], a[ks], cf[4 * q + (ks >> 1)][2 * (ks & 1)], cf[4 * q + (ks >> 1)][2 * (ks & 1) + 1]);
      }
      const uint32_t y0 = nz(pack_bf16((d[0][0] + d[1][0]) + (d[2][0] + d[3][0]), (d[0][1] + d[1][1]) + (d[2][1] + d[3][1])));
      const uint32_t y1 = nz(pack_bf16((d[0][2] + d[1][2]) + (d[2][2] + d[3][2]), (d[0][3] + d[1][3]) + (d[2][3] + d[3][3])));
      stg1(mo, y0); stg1(mo + 32, y1);
      stg1(mo + 1024, y0); stg1(mo + 1056, y1);
    }
    return;
  }

  const int wg = w >> 2, wq = w & 3;
  if (!p0a) {
    asm volatile("cp.async.wait_all;" ::: "memory");
    cw0 = ldg_in4(gc + g * 1024 + w * 128 + t * 32); cw1 = ldg_in4(gc + g * 1024 + w * 128 + t * 32 + 16);
  }
  sts4(hi + OFF_R0 + w * 1024 + g * 128 + (((2 * t) ^ g) << 4), make_uint4(silu2(cw0.x), silu2(cw0.y), silu2(cw0.z), silu2(cw0.w)));
  sts4(hi + OFF_R0 + w * 1024 + g * 128 + (((2 * t + 1) ^ g) << 4), make_uint4(silu2(cw1.x), silu2(cw1.y), silu2(cw1.z), silu2(cw1.w)));
  asm volatile("bar.arrive 3, 288;" ::: "memory");
  if (p0a) {
    asm volatile("fence.proxy.async.shared::cta;" ::: "memory");
  {
    float v[16];
    const uint32_t u[8] = {xr0.x, xr0.y, xr0.z, xr0.w, xr1.x, xr1.y, xr1.z, xr1.w};
#pragma unroll
    for (int i = 0; i < 8; i++) { v[2 * i] = bf_lo(u[i]); v[2 * i + 1] = bf_hi(u[i]); }
    float s = (((v[0] + v[1]) + (v[2] + v[3])) + ((v[4] + v[5]) + (v[6] + v[7]))) + (((v[8] + v[9]) + (v[10] + v[11])) + ((v[12] + v[13]) + (v[14] + v[15])));
#pragma unroll
    for (int o = 16; o; o >>= 1) s += __shfl_xor_sync(~0u, s, o);
    const float mu = s * (1.f / 512.f);
    float q0 = 0.f, q1 = 0.f;
#pragma unroll
    for (int i = 0; i < 8; i++) { const float a = v[2 * i] - mu, b = v[2 * i + 1] - mu; q0 += a * a; q1 += b * b; }
    float q = q0 + q1;
#pragma unroll
    for (int o = 16; o; o >>= 1) q += __shfl_xor_sync(~0u, q, o);
    const float rs = rsqrtf(q * (1.f / 512.f) + 1e-5f);
    asm volatile("st.shared.u16 [%0], %1;" ::"r"(hi + OFF_P0S + lane * 32 + w * 2), "h"(__bfloat16_as_ushort(__float2bfloat16((bf_lo(xc) - mu) * rs))) : "memory");
    asm volatile("st.shared.u16 [%0], %1;" ::"r"(hi + OFF_P0S + lane * 32 + 16 + w * 2), "h"(__bfloat16_as_ushort(__float2bfloat16((bf_hi(xc) - mu) * rs))) : "memory");
  }
    cbar();
  }
  if (p0a && wg == 0) {
    uint32_t* const mo = gs->MODA + cta * 32 + wq * 64 + lane;
    const uint32_t xn0 = lds1(hi + OFF_P0S + wq * 256 + lane * 4), xn1 = lds1(hi + OFF_P0S + wq * 256 + 128 + lane * 4);
    float d[4] = {0.f, 0.f, 0.f, 0.f};
    asm volatile("" : "+f"(d[0]), "+f"(d[1]), "+f"(d[2]), "+f"(d[3]) :: "memory");
#pragma unroll 1
    for (int i = 0; i < 4; i++) {
      mbar_wait(hi + BAR(BAR_WA) + 8 * i);
      wg_fence();
#pragma unroll
      for (int ks = 0; ks < 8; ks++) wgmma_n8(d, dlo(slot(8)) + i * 1024 + ks * 128, dlo(OFF_R0) + i * 128 + (ks >> 2) * 64 + (ks & 3) * 2);
      wg_commit();
    }
    wg_wait<0>();
    asm volatile("" : "+f"(d[0]), "+f"(d[1]), "+f"(d[2]), "+f"(d[3]) :: "memory");
    uint32_t y0 = pack_bf16(d[0], d[1]), y1 = pack_bf16(d[2], d[3]);
    if (cta >= 64) { y0 = hmul2(xn0, hadd2(y0, ONE2)); y1 = hmul2(xn1, hadd2(y1, ONE2)); }
    stg1(mo, nz(y0));
    stg1(mo + 32, nz(y1));
    if (lane == 0) mbar_arrive(hi + BAR(BAR_P0D));
  }
  cbar();
  {
    uint32_t* const qpo = pin(gs->QP + (cta * 256 + tid) * 2);
    const uint32_t* const modi = pin(gs->MODA + 512 * jI + tid * 2);
    uint32_t a[8][4];
    mbar_wait(hi + BAR(BAR_FULL + U_WQ) + 8 * wg); mbar_wait(hi + BAR(BAR_FULL + U_WQ + 2) + 8 * wg);
    load_a_t(a, hi + OFF_R1 + wg * 16384, wq, lane);
    mbar_wait(hi + BAR(BAR_FULL + U_WQ + MOD_AT));
    backoff(D_MOD);
    uint2 sa, ca;
    do { sa = ldg_rlx2(modi); ca = ldg_rlx2(modi + 2048); } while (min(min(sa.x, sa.y), min(ca.x, ca.y)) == 0);
    sts2(hi + OFF_BS + tid * 8, hadd2(ca.x, sa.x), hadd2(ca.y, sa.y));
    cbar();
    float d[4];
    mma128(d, a, hi + OFF_BS + lane * 16);
    stg_u64(qpo, pack_bf16(d[0], d[1]), pack_bf16(d[2], d[3]));
  }
  const uint32_t ckq = clk32();
  mbar_wait(hi + BAR(BAR_EPOCH));
  const int par = lds1(hi + OFF_EPOCH) & 1;
  uint32_t* const QX = gs->QX[par];
  {
    uint32_t a[8][4];
    {
      const int mi = lane >> 3, r = lane & 7;
      const int row = 16 * w + 8 * (mi & 1) + r;
      mbar_wait(hi + BAR(BAR_FULL + U_WUK) + 16 * wg); mbar_wait(hi + BAR(BAR_FULL + U_WUK + 1) + 16 * wg);
#pragma unroll
      for (int ks = 0; ks < 8; ks++) {
        const int chunk = 2 * ks + (mi >> 1);
        ldsm4(a[ks], hi + OFF_R2 + (ks >> 2) * 16384 + row * 128 + (((chunk & 7) ^ r) << 4));
      }
    }
    uint32_t* const qxo = pin(QX + ((lane >> 1) * 32 + hI) * 256 + (128 * jI + 16 * w + 8 * (lane & 1)) / 2);
    const uint32_t* const qpi = pin(gs->QP + (hI * 4 * 256 + tid) * 2);
    mbar_wait(hi + BAR(BAR_FULL - 1));
    wait_until(ckq, D_QP);
    uint2 qp[4];
#pragma unroll
    for (int i = 0; i < 4; i++) qp[i] = ldg_u64(qpi + i * 512);
    sum4_to_smem(qp, qpi, qpi + 1024, hi + OFF_BS2 + (16 * w + g) * 16 + t * 4, [] {});
    cbar();
    float d[4];
    mma128(d, a, hi + OFF_BS2 + lane * 16);
    const float sc = 0.08838834764831845f * 1.4426950408889634f;
    const uint32_t stg = hi + OFF_P0S + 4096 + w * 256;
    stsm2t(stg + (lane & 7) * 32 + ((lane >> 3) & 1) * 16, pack_bf16(d[0] * sc, d[1] * sc), pack_bf16(d[2] * sc, d[3] * sc));
    __syncwarp();
    if (lane < 16) stg_u128(qxo, lds4(stg + lane * 16));
    if (lane == 0) mbar_arrive(hi + BAR(BAR_P2E));
  }
  const uint32_t ckx = clk32();
  uint32_t fb = 0;
  {
    const uint32_t* qx = pin(QX + bI * 8192 + w * 1024 + lane * 4);
    mbar_wait(hi + BAR(BAR_FULL + QX_AT));
    wait_until(ckx, D_QX);
    uint4 v[8];
#pragma unroll
    for (int i = 0; i < 8; i++) v[i] = ldg_u128(qx + i * 128);
    asm volatile("bar.sync 2, 288;" ::: "memory");
    while (true) {
      bool all = true;
#pragma unroll
      for (int i = 0; i < 8; i++) all = all && v[i].w != 0;
      if (all) break;
#pragma unroll
      for (int i = 0; i < 8; i++) if (v[i].w == 0) v[i] = ldg_u128(qx + i * 128);
    }
#pragma unroll
    for (int i = 0; i < 8; i++) {
      const int hh = (4 * w + (i >> 1)) ^ (16 * rI), ch = 32 * (i & 1) + lane;
      sts4(hi + OFF_R0 + (ch >> 3) * 4096 + hh * 128 + (((ch & 7) ^ (hh & 7)) << 4), v[i]);
    }
    asm volatile("fence.proxy.async.shared::cta;" ::: "memory");
    cbar();
    if (tid == 0) mbar_arrive(hi + BAR(BAR_GO));
  }

  uint32_t ck1;
  const uint32_t *px, *pm;
  uint32_t *x2o, *x2p;
  {
    float O32[4][16], O16[4][8];
    uint32_t ebar;
    asm("mapa.shared::cluster.u32 %0, %1, %2;" : "=r"(ebar) : "r"(hi + BAR(BAR_EMPTY)), "r"(rI ^ (lane & 1)));
#pragma unroll
    for (int i = 0; i < 16; i++) O32[0][i] = O32[1][i] = O32[2][i] = O32[3][i] = 0.f;
#pragma unroll
    for (int i = 0; i < 4; i++) tie(O32[i]);
    auto pv2 = [&](int T, int WG, auto& O, int mb, int k0, int k1) {
      const int n = 8 * T + 4 * WG + mb;
      const uint32_t da = dlo(SB) + (sizeof(O[0]) == 64 ? n : n - 23) * 512, db = (WG && mb && T == 2) ? dlo(SB) : da + 512, dp = dlo(OFF_PT) + (T & 1) * 256;
#pragma unroll
      for (int ks = k0; ks < k1; ks++) { wgmma_ss<1, 1>(O[mb], da + ks * 128, dp + ks * 2); wgmma_ss<1, 1>(O[mb + 1], db + ks * 128, dp + ks * 2); }
      wg_commit();
    };
    auto pv = [&](int T, int WG, auto& O) { wg_fence(); pv2(T, WG, O, 0, 0, 4); pv2(T, WG, O, 2, 0, 4); };
    auto release = [&](int T, auto& O) {
      wg_wait<0>();
#pragma unroll
      for (int i = 0; i < 4; i++) tie(O[i]);
      if (lane < 2) mbar_arrive_cluster(ebar + 8 * T);
    };
    auto rescale = [&](auto& O) {
#pragma unroll
      for (int jn = 0; jn < (int)(sizeof(O[0]) / 16); jn++) {
        const float2 a = ldsf2(hi + OFF_ALPHA + (8 * jn + 2 * t) * 4);
#pragma unroll
        for (int mb = 0; mb < 4; mb++) { O[mb][4 * jn] *= a.x; O[mb][4 * jn + 1] *= a.y; O[mb][4 * jn + 2] *= a.x; O[mb][4 * jn + 3] *= a.y; }
      }
    };
    uint4 oe[4];
    uint32_t mate;
    asm("mapa.shared::cluster.u32 %0, %1, %2;" : "=r"(mate) : "r"(hi + SB), "r"(rI ^ 1));
    mate -= SB;
    auto split_o = [&] {
#pragma unroll
      for (int mb = 0; mb < 4; mb++)
        oe[mb] = make_uint4(pack_bf16(O32[mb][8], O32[mb][9]), pack_bf16(O32[mb][10], O32[mb][11]), pack_bf16(O32[mb][12], O32[mb][13]), pack_bf16(O32[mb][14], O32[mb][15]));
#pragma unroll
      for (int i = 0; i < 32; i++) asm volatile("mov.b32 %0, %1;" : "=f"(O16[i >> 3][i & 7]) : "f"(O32[i >> 3][i & 7]));
    };
    auto send_o = [&] {
      mbar_wait(hi + BAR(BAR_EMPTY + 2));
#pragma unroll
      for (int mb = 0; mb < 4; mb++)
        asm volatile("st.async.weak.shared::cluster.mbarrier::complete_tx::bytes.v4.b32 [%0], {%1,%2,%3,%4}, [%5];"
                     ::"r"(mate + OFF_XE + w * 4096 + mb * 512 + lane * 16), "r"(oe[mb].x), "r"(oe[mb].y), "r"(oe[mb].z), "r"(oe[mb].w), "r"(mate + BAR(BAR_XE)) : "memory");
    };
    uint32_t bd[2];
    float mnew, anew, bnew;
    bool moved;
    auto fetch_o = [&] {
      asm volatile("{\n.reg .pred p;\nMW_LOOP:\nmbarrier.try_wait.parity.acquire.cluster.shared::cta.b64 p, [%0], 0;\n@!p bra MW_LOOP;\n}" ::"r"(hi + BAR(BAR_XE)) : "memory");
      const float mo = ldsf(hi + OFF_MREF + (lane & 15) * 4), mx = ldsf(hi + OFF_MX + (lane & 15) * 8);
#pragma unroll
      for (int mb = 0; mb < 4; mb++) oe[mb] = lds4(hi + OFF_XE + w * 4096 + mb * 512 + lane * 16);
      mnew = mx - mo > 44.f ? mx : mo;
      moved = __any_sync(~0u, mnew != mo);
      anew = ex2(mo - mnew); bnew = ex2(mx - mnew);
      const uint32_t b = pack_bf16(bnew, 0.f);
      bd[0] = shl_clamp(__shfl_sync(~0u, b, g), 16 * (g - 2 * t));
      bd[1] = shl_clamp(__shfl_sync(~0u, b, g + 8), 16 * (g - 2 * t));
    };
    auto merge_o = [&] {
      if (__builtin_expect(moved, 0)) {
#pragma unroll
        for (int i = 0; i < 4; i++) {
          const float a = __shfl_sync(~0u, anew, 8 * (i >> 1) + 2 * t + (i & 1));
#pragma unroll
          for (int mb = 0; mb < 4; mb++) { O16[mb][4 * (i >> 1) + (i & 1)] *= a; O16[mb][4 * (i >> 1) + 2 + (i & 1)] *= a; }
        }
      }
#pragma unroll
      for (int mb = 0; mb < 4; mb++) {
        mma_v(reinterpret_cast<float (&)[4]>(O16[mb][0]), oe[mb], bd[0], 0u);
        mma_v(reinterpret_cast<float (&)[4]>(O16[mb][4]), oe[mb], 0u, bd[1]);
      }
    };
    uint32_t* x1l[4];
    auto late_addr = [&] {
      mbar_wait(hi + BAR(BAR_FM));
      fb = lds1(hi + OFF_FB + tid * 4);
#pragma unroll
      for (int i = 0; i < 4; i++)
        x1l[i] = hold(inbox((16 * rI + 2 * t) * 4 + 2 * wg + (bI >> 2), bI & 3, fb, 4 * (i & 1) + (i >> 1), pI * 128 + (wq * 8 + g) * 2));
      px = hold(inbox((cta & ~1) + wg, wq, (fb >> (8 + (jI & 2) + wg)) ^ wq, 0, t * 128 + rI * 64 + 4 * g));
      pm = hold(inbox(cta & ~1, 6, fb, 8 + (jI & 2), 512 + (w * 8 + t) * 8));
      x2o = hold(inbox(4 * hI + (jI >> 1) + (~jI & 2), 7, ~fb, 8 + (jI >> 1) + (~jI & 2), (jI & 1) * 512 + tid * 2));
      x2p = hold(inbox(4 * hI + (jI >> 1) + (jI & 2), 7, ~fb, 8 + (jI >> 1) + (jI & 2), (jI & 1) * 512 + tid * 2));
    };
    auto put_late = [&](int jj) {
#pragma unroll
      for (int i = 0; i < 4; i++) {
        const int jn = i >> 1, e = i & 1, r = 4 * jn + e;
        stg_u64(x1l[i] + (8 * jn + e) * 4 * 16384 + jj * 64, pack_bf16(O16[2 * jj][r], O16[2 * jj][r + 2]), pack_bf16(O16[2 * jj + 1][r], O16[2 * jj + 1][r + 2]));
      }
    };
    auto last_products = [&](int WG) {
      wg_fence();
      pv2(4, WG, O16, 0, 0, 4);
      ck1 = clk32();
      pv2(4, WG, O16, 2, 0, 3);
      wg_wait<1>();
      tie(O16[0]); tie(O16[1]);
      put_late(0);
      __syncwarp();
      wg_fence();
      pv2(4, WG, O16, 2, 3, 4);
      wg_wait<0>();
      tie(O16[2]); tie(O16[3]);
      put_late(1);
      if (lane < 2) mbar_arrive_cluster(ebar + 32);
    };

    if (wg == 0) {
      float S32[16], S16[8];
      float m_run = -INFINITY;
      float mh[8];
#pragma unroll
      for (int i = 0; i < 16; i++) S32[i] = S16[i & 7] = mh[i & 7] = 0.f;
      const uint32_t ptl = hold32(hi + OFF_PT + (8 * (lane >> 4) + (lane & 7)) * 128 + (((2 * wq + ((lane >> 3) & 1)) ^ (lane & 7)) << 4));
      auto landed = [&](int T) { return __ballot_sync(~0u, mbar_test(hi + BAR(BAR_FULL + 8 * T) + 8 * (lane & 7))); };
      auto softmax = [&](int T, auto& O, auto& S) {
        constexpr int NJ = sizeof(S) / 16;
        wg_wait<0>();
        tie(S);
        auto update = [&] {
            float mx[2 * NJ];
#pragma unroll
            for (int jn = 0; jn < NJ; jn++) { mx[2 * jn] = fmaxf(S[4 * jn], S[4 * jn + 2]); mx[2 * jn + 1] = fmaxf(S[4 * jn + 1], S[4 * jn + 3]); }
            float a4[4], a2[2], a1;
            if constexpr (NJ == 4) {
              const bool up = lane & 16;
#pragma unroll
              for (int i = 0; i < 4; i++) { const float send = up ? mx[i] : mx[4 + i]; const float keep = up ? mx[4 + i] : mx[i]; a4[i] = fmaxf(keep, __shfl_xor_sync(~0u, send, 16)); }
            } else {
#pragma unroll
              for (int i = 0; i < 4; i++) { a4[i] = fmaxf(mx[i], __shfl_xor_sync(~0u, mx[i], 16)); if (lane & 16) a4[i] = -INFINITY; }
            }
            {
              const bool up = lane & 8;
#pragma unroll
              for (int i = 0; i < 2; i++) { const float send = up ? a4[i] : a4[2 + i]; const float keep = up ? a4[2 + i] : a4[i]; a2[i] = fmaxf(keep, __shfl_xor_sync(~0u, send, 8)); }
            }
            {
              const bool up = lane & 4;
              const float send = up ? a2[0] : a2[1]; const float keep = up ? a2[1] : a2[0];
              a1 = fmaxf(keep, __shfl_xor_sync(~0u, send, 4));
            }
            stsf(hi + OFF_RED + (wq * 32 + 8 * (g >> 1) + 2 * t + (g & 1)) * 4, a1);
            wg0bar();
            const float mt = fmaxf(fmaxf(ldsf(hi + OFF_RED + lane * 4), ldsf(hi + OFF_RED + 128 + lane * 4)),
                                   fmaxf(ldsf(hi + OFF_RED + 256 + lane * 4), ldsf(hi + OFF_RED + 384 + lane * 4)));
            const float m_new = fmaxf(m_run, ceilf(mt) + 24.f);
            if (wq == 0) { stsf(hi + OFF_MREF + (T == 4 ? 128 : 0) + lane * 4, m_new); stsf(hi + OFF_ALPHA + lane * 4, ex2(m_run - m_new)); }
            m_run = m_new;
#pragma unroll
            for (int i = 0; i < 2 * NJ; i++) mh[i] = __shfl_sync(~0u, m_new, 8 * (i >> 1) + 2 * t + (i & 1));
            if (T > 0) { wg0bar(); rescale(O); }
        };
        auto write_p = [&] {
          uint32_t pk[2 * NJ];
          float x[4 * NJ];
#pragma unroll
          for (int i = 0; i < 4 * NJ; i++) x[i] = S[i] - mh[2 * (i >> 2) + (i & 1)];
#pragma unroll
          for (int i = 0; i < 2 * NJ; i++) pk[i] = pack_bf16(ex2(x[2 * i]), ex2(x[2 * i + 1]));
#pragma unroll
          for (int hf = 0; hf < NJ / 2; hf++) stsm4t(ptl + (T & 1) * 4096 + hf * 2048, pk[4 * hf], pk[4 * hf + 1], pk[4 * hf + 2], pk[4 * hf + 3]);
          asm volatile("fence.proxy.async.shared::cta;" ::: "memory");
          if constexpr (NJ == 4) {
#pragma unroll
            for (int i = 0; i < 8; i++) x[i] = fmaxf(x[i], x[i + 8]);
          }
          return cbar_or(fmaxf(fmaxf(fmaxf(x[0], x[1]), fmaxf(x[2], x[3])), fmaxf(fmaxf(x[4], x[5]), fmaxf(x[6], x[7]))) > 32.f);
        };
        if constexpr (NJ == 4) {
          bool over = T == 0;
#pragma unroll 1
          do {
            if (over) update();
            over = write_p();
          } while (__builtin_expect(over, 0));
        } else {
#pragma unroll 1
          while (__builtin_expect(write_p(), 0)) update();
        }
      };
      uint32_t have = 0;
#pragma unroll
      for (int i = 0; i < 4; i++) x1l[i] = nullptr;
      px = pm = x2o = x2p = nullptr;
#pragma unroll 1
      for (int T = 0; T < 3; T++) {
        sfor<0, 8>([&](auto jc) {
          constexpr int jj = decltype(jc)::value;
          const uint32_t da = dlo(SB) + box_slot(8 * T + jj) * 512, db = dlo(OFF_R0) + jj * 256;
          mbar_wait(hi + BAR(BAR_FULL) + 64 * T + 8 * jj);
          wg_fence();
          wgmma_ss<0, jj != 0>(S32, da, db);
#pragma unroll
          for (int ks = 1; ks < 4; ks++) wgmma_ss<0, 1>(S32, da + ks * 2, db + ks * 2);
          wg_commit();
        });
        softmax(T, O32, S32);
        pv(T, 0, O32);
        have = landed(3);
        release(T, O32);
        if (T == 1) late_addr();
      }
      split_o();
#pragma unroll 1
      for (int T = 3;; T++) {
        sfor<0, 8>([&](auto jc) {
          constexpr int jj = decltype(jc)::value;
          const uint32_t da = dlo(SB) + (8 * T + jj - 23) * 512, db = dlo(OFF_R0) + jj * 256;
          if (!((have >> jj) & 1)) mbar_wait(hi + BAR(BAR_FULL) + 64 * T + 8 * jj);
          wg_fence();
          wgmma_ss<0, jj != 0>(S16, da, db);
#pragma unroll
          for (int ks = 1; ks < 4; ks++) wgmma_ss<0, 1>(S16, da + ks * 2, db + ks * 2);
          wg_commit();
          if (jj == 2 && T == 3) send_o();
        });
        softmax(T, O16, S16);
        if (T == 4) break;
        pv(3, 0, O16);
        have = landed(4);
        fetch_o();
        if (wq == 0) stsf(hi + OFF_MREF + 128 + lane * 4, mnew);
        mbar_wait(hi + BAR(BAR_XE));
        release(3, O16);
        merge_o();
        if (__builtin_expect(moved, 0)) {
          m_run = mnew;
#pragma unroll
          for (int i = 0; i < 4; i++) mh[i] = __shfl_sync(~0u, mnew, 8 * (i >> 1) + 2 * t + (i & 1));
        }
      }
      last_products(0);
    } else {
      float ls[2] = {0.f, 0.f};
      const int hr = 4 * wq + (lane >> 3);
      const uint32_t ptl = hi + OFF_PT + (tid & 127) * 16;
      auto sum8 = [](const uint4& v) { return ((bf_lo(v.x) + bf_hi(v.x)) + (bf_lo(v.y) + bf_hi(v.y))) + ((bf_lo(v.z) + bf_hi(v.z)) + (bf_lo(v.w) + bf_hi(v.w))); };
      auto row_sum = [](float l) { l += __shfl_xor_sync(~0u, l, 1); l += __shfl_xor_sync(~0u, l, 2); return l + __shfl_xor_sync(~0u, l, 4); };
      auto get_p = [&](auto& O) {
        if (__builtin_expect(cbar_or(false), 0)) {
          cbar_or(false);
          rescale(O);
          ls[0] *= ldsf(hi + OFF_ALPHA + hr * 4);
          if (sizeof(O[0]) == 64) ls[1] *= ldsf(hi + OFF_ALPHA + 64 + hr * 4);
        }
      };
#pragma unroll 1
      for (int T = 0; T < 3; T++) {
        get_p(O32);
        pv(T, 1, O32);
        ls[0] += sum8(lds4(ptl + (T & 1) * 4096));
        ls[1] += sum8(lds4(ptl + (T & 1) * 4096 + 2048));
        release(T, O32);
      }
      split_o();
      send_o();
      {
        const float l = row_sum(ls[1]);
        if (!(lane & 7))
          asm volatile("st.async.weak.shared::cluster.mbarrier::complete_tx::bytes.v2.b32 [%0], {%1,%2}, [%3];"
                       ::"r"(mate + OFF_MX + hr * 8), "r"(lds1(hi + OFF_MREF + 64 + hr * 4)), "r"(__float_as_uint(l)), "r"(mate + BAR(BAR_XE)) : "memory");
      }
      get_p(O16);
      pv(3, 1, O16);
      ls[0] += sum8(lds4(ptl + 4096));
      fetch_o();
      const float lx = ldsf(hi + OFF_MX + hr * 8 + 4) * __shfl_sync(~0u, bnew, hr);
      ls[0] = ls[0] * __shfl_sync(~0u, anew, hr) + ((lane & 7) ? 0.f : lx);
      release(3, O16);
      merge_o();
      late_addr();
      uint32_t* const mlo = hold(inbox((16 * rI + hr) * 4 + (lane & 2), 6, fb, 13, 512 + (cta >> 1) * 8 + (lane & 1) * 4));
      mbar_wait(hi + BAR(BAR_CLR));
      get_p(O16);
      {
        const uint32_t m = lds1(hi + OFF_MREF + 128 + hr * 4), l = nz(__float_as_uint(row_sum(ls[0] + sum8(lds4(ptl)))));
        if (!(lane & 4)) stg4_b128(mlo, make_uint4(m, l, m, l));
      }
      last_products(1);
    }
  }

  uint32_t aw[8][4];
  {
    wait_until(ck1, X1_D0);
    uint2 ml[2];
    uint4 v[4];
#pragma unroll
    for (int i = 0; i < 4; i++) v[i] = ldg_2u64(px + (i >> 1) * 512 + (i & 1) * 32);
#pragma unroll
    for (int i = 0; i < 2; i++) ml[i] = ldg_u64(pm + i * 32);
    uint32_t sel[4][2] = {{0u, 0u}, {0u, 0u}, {0u, 0u}, {0u, 0u}};
    float Ls = 0.f;
    bool w_ok = false;
    const uint32_t bso = hold32(hi + OFF_BS4 + w * 320 + (16 * (t >> 1) + 8 * (g >> 2) + 4 * (g & 1) + 2 * (t & 1) + ((g >> 1) & 1)) * 8), bsi = hold32(hi + OFF_BS4 + g * 320 + t * 16);
    const uint32_t lso = hold32(hi + OFF_BS4 + w * 320 + 256 + t * 4), lsi = hold32(hi + OFF_BS4 + t * 640 + 256);
    const uint32_t wa = hold32(hi + OFF_WUV + wg * 8192 + (lane >> 4) * 4096 + (lane & 7) * 128 + (((2 * wq + ((lane >> 3) & 1)) ^ (lane & 7)) << 4));
    mbar_wait(hi + BAR(BAR_FULL + U_WUV) + 8 * wg);
#pragma unroll
    for (int ks = 0; ks < 4; ks++) { ldsm4t(aw[ks], wa + ks * 1024); aw[4 + ks][0] = aw[4 + ks][1] = aw[4 + ks][2] = aw[4 + ks][3] = 0; }
    bool wv_ok = false;
    float e0[4], e1[4];
#pragma unroll 1
    while (true) {
      if (!wv_ok && mbar_test(hi + BAR(BAR_FULL + U_WUV + 2) + 8 * wg)) {
        wv_ok = true;
#pragma unroll
        for (int ks = 0; ks < 4; ks++) ldsm4t(aw[4 + ks], wa - (OFF_WUV - OFF_WUV2) + ks * 1024);
      }
#pragma unroll
      for (int i = 0; i < 4; i++) tie(v[i]);
      tie(ml[0]); tie(ml[1]);
      const bool ok = __all_sync(~0u, w_ok && min(min3(min3(v[0].y, v[0].w, v[1].y), v[1].w, v[2].y), min3(v[2].w, v[3].y, v[3].w)) != 0);
#pragma unroll
      for (int i = 0; i < 4; i++) e0[i] = e1[i] = 0.f;
      mma_v(e0, v[0], sel[0][0], sel[0][1]); mma_v(e1, v[2], sel[2][0], sel[2][1]);
      mma_v(e0, v[1], sel[1][0], sel[1][1]); mma_v(e1, v[3], sel[3][0], sel[3][1]);
      if (ok) break;
#pragma unroll
      for (int i = 0; i < 4; i++) if (v[i].y == 0 || v[i].w == 0) v[i] = ldg_2u64(px + (i >> 1) * 512 + (i & 1) * 32);
      if (!w_ok) {
        if (__all_sync(~0u, min(ml[0].y, ml[1].y) != 0)) {
          w_ok = true;
          float M = fmaxf(__uint_as_float(ml[0].x), __uint_as_float(ml[1].x));
          M = fmaxf(M, __shfl_xor_sync(~0u, M, 1)); M = fmaxf(M, __shfl_xor_sync(~0u, M, 2));
          const uint32_t wb[2] = {pack_bf16(ex2(__uint_as_float(ml[0].x) - M), 0.f), pack_bf16(ex2(__uint_as_float(ml[1].x) - M), 0.f)};
#pragma unroll
          for (int i = 0; i < 4; i++) { sel[i][0] = shl_clamp(wb[i >> 1], 16 * g - 64 * (i & 1)); sel[i][1] = shl_clamp(wb[i >> 1], 16 * g - 64 * (i & 1) - 32); }
          Ls = bf_lo(wb[0]) * __uint_as_float(ml[0].y) + bf_lo(wb[1]) * __uint_as_float(ml[1].y);
        } else {
#pragma unroll
          for (int i = 0; i < 2; i++) ml[i] = ldg_u64(pm + i * 32);
        }
      }
    }
    stsf(lso, Ls);
    sts2(bso, pack_bf16(e0[0] + e1[0], e0[1] + e1[1]), pack_bf16(e0[2] + e1[2], e0[3] + e1[3]));
    cbar();
    float o[4][4] = {{0.f, 0.f, 0.f, 0.f}, {0.f, 0.f, 0.f, 0.f}, {0.f, 0.f, 0.f, 0.f}, {0.f, 0.f, 0.f, 0.f}};
    uint4 b[4];
#pragma unroll
    for (int kk = 0; kk < 4; kk++) b[kk] = lds4(bsi + kk * 64);
    const float4 la = ldsf4(lsi), lb = ldsf4(lsi + 320);
    if (!wv_ok) {
      mbar_wait(hi + BAR(BAR_FULL + U_WUV + 2) + 8 * wg);
#pragma unroll
      for (int ks = 0; ks < 4; ks++) ldsm4t(aw[4 + ks], wa - (OFF_WUV - OFF_WUV2) + ks * 1024);
    }
#pragma unroll
    for (int kk = 0; kk < 4; kk++) { mma16816(o[(2 * kk) & 3], aw[2 * kk], b[kk].x, b[kk].y); mma16816(o[(2 * kk + 1) & 3], aw[2 * kk + 1], b[kk].z, b[kk].w); }
    const float ia = rcp((la.x + la.y) + (la.z + la.w)), ib = rcp((lb.x + lb.y) + (lb.z + lb.w));
    const uint32_t y0 = pack_bf16(((o[0][0] + o[1][0]) + (o[2][0] + o[3][0])) * ia, ((o[0][1] + o[1][1]) + (o[2][1] + o[3][1])) * ib);
    const uint32_t y1 = pack_bf16(((o[0][2] + o[1][2]) + (o[2][2] + o[3][2])) * ia, ((o[0][3] + o[1][3]) + (o[2][3] + o[3][3])) * ib);
    stg_u64(x2o, y0, y1);
    stg_u64(x2p, y0, y1);
  }
  const uint32_t ck2 = clk32();
  {
    uint32_t* const o = hold(inbox(4 * (8 * jI + w) + (g >> 1), 6, fb, 12, (g & 1) * 256 + hI * 8 + 2 * t));
    const uint32_t* const x2i = hold(inbox(cta & ~1, 7, ~fb, 8 + (jI & 2), tid * 2));
    const uint32_t* const x2j = hold(inbox(cta | 1, 7, ~fb, 8 + (jI | 1), tid * 2));
    const uint32_t bso = hold32(hi + OFF_BS5 + (16 * w + g) * 16 + t * 4), bsi = hold32(hi + OFF_BS5 + lane * 16);
    const uint32_t wa = hold32(hi + OFF_WO + wg * 8192 + (8 * (lane >> 4) + (lane & 7)) * 128 + (((2 * wq + ((lane >> 3) & 1)) ^ (lane & 7)) << 4));
    wait_until(ck2, D_X2);
    uint2 v[4];
#pragma unroll
    for (int i = 0; i < 4; i++) v[i] = ldg_u64(((i & 2) ? x2j : x2i) + (i & 1) * 512);
    int wo_n = 0;
    sum4_to_smem(v, x2i, x2j, bso, [&] {
      if (wo_n == 0 && mbar_test(hi + BAR(BAR_FULL + U_WO) + 8 * wg)) {
        wo_n = 1;
#pragma unroll
        for (int ks = 0; ks < 4; ks++) ldsm4t(aw[ks], wa + ks * 2048);
      }
      if (wo_n == 1 && mbar_test(hi + BAR(BAR_FULL + U_WO + 2) + 8 * wg)) {
        wo_n = 2;
#pragma unroll
        for (int ks = 0; ks < 4; ks++) ldsm4t(aw[4 + ks], wa + 16384 + ks * 2048);
      }
    });
    cbar();
    float e[4][4] = {{0.f, 0.f, 0.f, 0.f}, {0.f, 0.f, 0.f, 0.f}, {0.f, 0.f, 0.f, 0.f}, {0.f, 0.f, 0.f, 0.f}};
    uint32_t b[4][4];
#pragma unroll
    for (int kk = 0; kk < 4; kk++) ldsm4t(b[kk], bsi + kk * 512);
    if (wo_n < 2) {
      if (wo_n == 0) {
        mbar_wait(hi + BAR(BAR_FULL + U_WO) + 8 * wg);
#pragma unroll
        for (int ks = 0; ks < 4; ks++) ldsm4t(aw[ks], wa + ks * 2048);
      }
      mbar_wait(hi + BAR(BAR_FULL + U_WO + 2) + 8 * wg);
#pragma unroll
      for (int ks = 0; ks < 4; ks++) ldsm4t(aw[4 + ks], wa + 16384 + ks * 2048);
    }
#pragma unroll
    for (int ks = 0; ks < 8; ks++) mma16816(e[ks & 3], aw[ks], b[ks >> 1][2 * (ks & 1)], b[ks >> 1][2 * (ks & 1) + 1]);
    stg_u64(o, pack_bf16((e[0][0] + e[1][0]) + (e[2][0] + e[3][0]), (e[0][1] + e[1][1]) + (e[2][1] + e[3][1])),
            pack_bf16((e[0][2] + e[1][2]) + (e[2][2] + e[3][2]), (e[0][3] + e[1][3]) + (e[2][3] + e[3][3])));
    if (lane == 0) mbar_arrive(hi + BAR(BAR_P5D));
  }
  const uint32_t ck3 = clk32();
  if (cta < NFF) {
    const int mi = lane >> 3, r = lane & 7;
    uint32_t a1[4][4], a2[4][4];
    uint32_t bc[8], bs[8];
    const uint32_t* const mbi = gs->MODB + (2 + wg) * 2048 + ((~((fb >> 14)) & 1) << 10) + 256 * wq + lane;
#pragma unroll
    for (int i = 0; i < 8; i++) { bs[i] = ldg_rlx1(mbi + i * 32); bc[i] = ldg_rlx1(mbi + 4096 + i * 32); }
    const int lp = (tid >> 2) & 31, kq = tid & 3;
    const int fo = (lp >> 2) + 8 * (kq >> 1), bo = 2 * (lp & 3) + (kq & 1);
    const uint32_t* xb = hold(gs->X3B + ((cta >> 1) & 1) * 4096 + wg * 2048 + (((fb >> 14) & 1) << 10) + (16 * wq + t) * 16 + 2 * g);
    uint32_t* ox[4];
#pragma unroll
    for (int mb = 0; mb < 4; mb++) ox[mb] = hold(inbox(16 * w + 4 * mb + (g >> 1), 4 + (cta >= 56), fb, 16 + 4 * mb, (cta >= 56 ? cta - 56 : cta) * 16 + (g & 1) * 8 + 2 * t));
    const uint32_t gi = hold32(hi + OFF_REDG + tid * 4);
    const uint32_t h1o = hold32(hi + OFF_H1 + fo * 16 + bo * 2), sti = hold32(hi + OFF_REDS + bo * 80), sto = hold32(hi + OFF_REDS + g * 80 + w * 8);
    const uint32_t a1a = hold32(hi + OFF_W1 + (64 * w + 8 * (mi >> 1) + r) * 64 + (((2 * rI + (mi & 1)) ^ (r >> 1)) << 4));
    bool w2ok = false;
    uint32_t a2a[4];
#pragma unroll
    for (int mb = 0; mb < 4; mb++) {
      a2a[mb] = hi + OFF_W2 + w * 2048 + (8 * (mi >> 1) + r) * 128 + (((2 * mb + (mi & 1)) ^ r) << 4);
      a2[mb][0] = a2[mb][1] = a2[mb][2] = a2[mb][3] = 0;
    }
#pragma unroll 1
    while (true) {
      uint32_t mn = 0xffffffffu;
#pragma unroll
      for (int i = 0; i < 8; i++) mn = min3(mn, bs[i], bc[i]);
      if (__all_sync(~0u, mn != 0)) break;
#pragma unroll
      for (int i = 0; i < 8; i++) { bs[i] = ldg_rlx1(mbi + i * 32); bc[i] = ldg_rlx1(mbi + 4096 + i * 32); }
    }
#pragma unroll
    for (int i = 0; i < 8; i++) { bs[i] = movm(bs[i]); bc[i] = hadd2(movm(bc[i]), ONE2); }
    mbar_wait(hi + BAR(BAR_FULL + U_W1) + 8 * wg);
#pragma unroll
    for (int ks = 0; ks < 4; ks++) ldsm4t(a1[ks], a1a + ks * 1024);
    {
      float u[2][4] = {{0.f, 0.f, 0.f, 0.f}, {0.f, 0.f, 0.f, 0.f}}, vv[2][4] = {{0.f, 0.f, 0.f, 0.f}, {0.f, 0.f, 0.f, 0.f}};
#pragma unroll
      for (int ks = 0; ks < 4; ks++) { mma16816(u[ks & 1], a1[ks], bc[2 * ks], bc[2 * ks + 1]); mma16816(vv[ks & 1], a1[ks], bs[2 * ks], bs[2 * ks + 1]); }
      sts4f(hi + OFF_REDU + tid * 16, u[0][0] + u[1][0], u[0][1] + u[1][1], u[0][2] + u[1][2], u[0][3] + u[1][3]);
      sts4f(hi + OFF_REDV + tid * 16, vv[0][0] + vv[1][0], vv[0][1] + vv[1][1], vv[0][2] + vv[1][2], vv[0][3] + vv[1][3]);
    }
    if (wg) asm volatile("bar.arrive 1, 256;" ::: "memory"); else cbar();
    float U = 0.f, V = 0.f;
    bool uv = wg;
    wait_until(ck3, D_X3B);
    float G[2][4], S[2][4];
    bool ok;
#pragma unroll 1
    do {
      uint2 x[4];
#pragma unroll
      for (int ks = 0; ks < 4; ks++) x[ks] = ldg_u64(xb + ks * 64);
      if (!uv) {
        uv = true;
        float a[8], b[8];
#pragma unroll
        for (int i = 0; i < 8; i++) { a[i] = ldsf(gi + (OFF_REDU - OFF_REDG) + i * 512); b[i] = ldsf(gi + (OFF_REDV - OFF_REDG) + i * 512); }
        U = ((a[0] + a[1]) + (a[2] + a[3])) + ((a[4] + a[5]) + (a[6] + a[7]));
        V = ((b[0] + b[1]) + (b[2] + b[3])) + ((b[4] + b[5]) + (b[6] + b[7]));
      }
      if (!w2ok && mbar_test(hi + BAR(BAR_FULL + U_W2) + 8 * wg)) {
        w2ok = true;
#pragma unroll
        for (int mb = 0; mb < 4; mb++) ldsm4t(a2[mb], a2a[mb]);
      }
#pragma unroll
      for (int ks = 0; ks < 4; ks++) tie(x[ks]);
      ok = __all_sync(~0u, min(min3(x[0].y, x[1].y, x[2].y), x[3].y) != 0);
#pragma unroll
      for (int i = 0; i < 4; i++) G[0][i] = G[1][i] = S[0][i] = S[1][i] = 0.f;
#pragma unroll
      for (int ks = 0; ks < 4; ks++) {
        const uint32_t s0[4] = {x[ks].x, ONE2, x[ks].y, ONE2};
        mma16816(S[ks & 1], s0, x[ks].x, x[ks].y);
        mma16816(G[ks & 1], a1[ks], hmul2(x[ks].x, bc[2 * ks]), hmul2(x[ks].y, bc[2 * ks + 1]));
      }
    } while (!ok);
    if ((g >> 1) == t) sts2f(sto, (g & 1) ? S[0][3] + S[1][3] : S[0][2] + S[1][2], (g & 1) ? S[0][1] + S[1][1] : S[0][0] + S[1][0]);
    sts4f(hi + OFF_REDG + tid * 16, G[0][0] + G[1][0], G[0][1] + G[1][1], G[0][2] + G[1][2], G[0][3] + G[1][3]);
    if (wg) asm volatile("bar.arrive 3, 256;" ::: "memory"); else asm volatile("bar.sync 3, 256;" ::: "memory");
    if (tid < 128) {
      float gv[8];
      float4 sv[4];
#pragma unroll
      for (int i = 0; i < 4; i++) sv[i] = ldsf4(sti + i * 16);
#pragma unroll
      for (int i = 0; i < 8; i++) gv[i] = ldsf(gi + i * 512);
      const float s1 = ((sv[0].x + sv[0].z) + (sv[1].x + sv[1].z)) + ((sv[2].x + sv[2].z) + (sv[3].x + sv[3].z));
      const float s2 = ((sv[0].y + sv[0].w) + (sv[1].y + sv[1].w)) + ((sv[2].y + sv[2].w) + (sv[3].y + sv[3].w));
      const float gs_ = ((gv[0] + gv[1]) + (gv[2] + gv[3])) + ((gv[4] + gv[5]) + (gv[6] + gv[7]));
      const float mu = s1 * (1.f / 512.f);
      const float rs = rsq(fmaxf(s2 * (1.f / 512.f) - mu * mu, 0.f) + 1e-5f);
      const float hv = fmaxf(rs * (gs_ - mu * U) + V, 0.f);
      asm volatile("st.shared.u16 [%0], %1;" ::"r"(h1o), "h"(__bfloat16_as_ushort(__float2bfloat16(hv))) : "memory");
    }
    if (!w2ok) {
      mbar_wait(hi + BAR(BAR_FULL + U_W2) + 8 * wg);
#pragma unroll
      for (int mb = 0; mb < 4; mb++) ldsm4t(a2[mb], a2a[mb]);
    }
    asm volatile("bar.sync 2, 256;" ::: "memory");
    uint32_t b0, b1;
    ldsm2t(b0, b1, hi + OFF_H1 + (lane & 15) * 16);
#pragma unroll
    for (int mb = 0; mb < 4; mb++) {
      float o[4] = {0.f, 0.f, 0.f, 0.f};
      mma16816(o, a2[mb], b0, b1);
      stg_u64(ox[mb], pack_bf16(o[0], o[1]), pack_bf16(o[2], o[3]));
    }
    if (lane == 0) mbar_arrive(hi + BAR(BAR_P7D));
  }
}

typedef CUresult (*EncodeTiledFn)(CUtensorMap*, CUtensorMapDataType, cuuint32_t, void*, const cuuint64_t*, const cuuint64_t*,
                                  const cuuint32_t*, const cuuint32_t*, CUtensorMapInterleave, CUtensorMapSwizzle,
                                  CUtensorMapL2promotion, CUtensorMapFloatOOBfill);

void make_map(EncodeTiledFn enc, CUtensorMap* m, const void* base, uint64_t cols, uint64_t rows, uint32_t bc, uint32_t br,
              CUtensorMapSwizzle sw, CUtensorMapL2promotion promo) {
  cuuint64_t dims[2] = {cols, rows};
  cuuint64_t strides[1] = {cols * 2};
  cuuint32_t box[2] = {bc, br};
  cuuint32_t es[2] = {1, 1};
  enc(m, CU_TENSOR_MAP_DATA_TYPE_BFLOAT16, 2, const_cast<void*>(base), dims, strides, box, es, CU_TENSOR_MAP_INTERLEAVE_NONE, sw, promo,
      CU_TENSOR_MAP_FLOAT_OOB_FILL_NONE);
}
void make_map3(EncodeTiledFn enc, CUtensorMap* m, const void* base, uint64_t rows, uint32_t br, uint32_t bb) {
  cuuint64_t dims[3] = {64, rows, 8};
  cuuint64_t strides[2] = {1024, 128};
  cuuint32_t box[3] = {64, br, bb};
  cuuint32_t es[3] = {1, 1, 1};
  enc(m, CU_TENSOR_MAP_DATA_TYPE_BFLOAT16, 3, const_cast<void*>(base), dims, strides, box, es, CU_TENSOR_MAP_INTERLEAVE_NONE,
      CU_TENSOR_MAP_SWIZZLE_128B, CU_TENSOR_MAP_L2_PROMOTION_NONE, CU_TENSOR_MAP_FLOAT_OOB_FILL_NONE);
}

}

extern "C" void kernel_launch(void* const* d_in, const int* in_sizes, int n_in, void* d_out, int out_size) {
  (void)in_sizes; (void)n_in; (void)out_size;
  static EncodeTiledFn enc = nullptr;
  static Scratch* scratch = nullptr;
  if (!enc) {
    void* sp = nullptr;
    cudaGetSymbolAddress(&sp, g_s);
    scratch = (Scratch*)(((uintptr_t)sp + 131071) & ~(uintptr_t)131071);
    void* fn = nullptr;
    cudaDriverEntryPointQueryResult q;
    cudaGetDriverEntryPoint("cuTensorMapEncodeTiled", &fn, cudaEnableDefault, &q);
    enc = (EncodeTiledFn)fn;
    cudaFuncSetAttribute(fused_decode_kernel, cudaFuncAttributeMaxDynamicSharedMemorySize, SMEM_BYTES);
  }
  Params P;
  make_map(enc, &P.ckv, d_in[1], 512, 8 * 4096, 64, 64, CU_TENSOR_MAP_SWIZZLE_128B, CU_TENSOR_MAP_L2_PROMOTION_NONE);
  make_map(enc, &P.wq, d_in[2], 4096, 512, 64, 64, CU_TENSOR_MAP_SWIZZLE_128B, CU_TENSOR_MAP_L2_PROMOTION_NONE);
  make_map(enc, &P.wuk, d_in[3], 4096, 512, 64, 64, CU_TENSOR_MAP_SWIZZLE_128B, CU_TENSOR_MAP_L2_PROMOTION_NONE);
  {
    cuuint64_t dims[5] = {4096, 2, 8, 4, 8};
    cuuint64_t strides[4] = {8 * 8192, 8192, 16 * 8192, 64 * 8192};
    cuuint32_t box[5] = {64, 2, 8, 2, 2};
    cuuint32_t es[5] = {1, 1, 1, 1, 1};
    enc(&P.wuv, CU_TENSOR_MAP_DATA_TYPE_BFLOAT16, 5, d_in[4], dims, strides, box, es, CU_TENSOR_MAP_INTERLEAVE_NONE, CU_TENSOR_MAP_SWIZZLE_128B,
        CU_TENSOR_MAP_L2_PROMOTION_NONE, CU_TENSOR_MAP_FLOAT_OOB_FILL_NONE);
  }
  make_map(enc, &P.wo, d_in[5], 512, 4096, 64, 64, CU_TENSOR_MAP_SWIZZLE_128B, CU_TENSOR_MAP_L2_PROMOTION_NONE);
  make_map(enc, &P.w1, d_in[7], 1792, 512, 2 * FCH, 128, CU_TENSOR_MAP_SWIZZLE_64B, CU_TENSOR_MAP_L2_PROMOTION_NONE);
  make_map3(enc, &P.w2, d_in[8], 1792, FCH, 4);
  make_map(enc, &P.wma, d_in[10], 3072, 512, 64, 128, CU_TENSOR_MAP_SWIZZLE_128B, CU_TENSOR_MAP_L2_PROMOTION_NONE);
  make_map(enc, &P.wmod, d_in[10], 3072, 512, 32, 128, CU_TENSOR_MAP_SWIZZLE_64B, CU_TENSOR_MAP_L2_PROMOTION_NONE);
  fused_decode_kernel<<<NCTA, NTHREADS, SMEM_BYTES>>>((__nv_bfloat16*)d_out, scratch, (const uint8_t*)d_in[2], (const uint8_t*)d_in[0],
                                                      (const uint8_t*)d_in[9], P);
}
```

```cpp
#include <cuda_runtime.h>
#include <cuda.h>
#include <cuda_bf16.h>
#include <stdint.h>

namespace {

constexpr int NCTA = 128;
constexpr int NTHREADS = 384;
constexpr int FCH = 16;
constexpr int NFF = 1792 / FCH;

constexpr uint32_t SB = 1024;
__host__ __device__ constexpr uint32_t slot(int i) { return SB + i * 8192; }
constexpr uint32_t OFF_R1 = slot(16);
constexpr uint32_t OFF_R2 = slot(20);
constexpr uint32_t OFF_PT = slot(23);
constexpr uint32_t OFF_R0 = slot(24);
constexpr uint32_t OFF_MISC = SB + 229376;
constexpr uint32_t OFF_BARS = OFF_MISC;
constexpr uint32_t OFF_FM = OFF_MISC + 736;
constexpr uint32_t OFF_EPOCH = OFF_MISC + 768;
constexpr uint32_t OFF_BS = OFF_MISC + 1024;
constexpr uint32_t SMEM_BYTES = 229376 + 3072;
constexpr uint32_t OFF_P0S = OFF_R0 + 24576;
constexpr uint32_t OFF_BS2 = OFF_R0 + 30720;
constexpr uint32_t OFF_RED = OFF_BS;
constexpr uint32_t OFF_ALPHA = OFF_BS + 512;
constexpr uint32_t OFF_MREF = OFF_BS + 640;
constexpr uint32_t OFF_MX = OFF_BS + 896;
constexpr uint32_t OFF_FB = OFF_BS + 1024;
__host__ __device__ constexpr int box_slot(int n) { return n < 23 ? n : n - 23; }
constexpr uint32_t OFF_WUV = slot(21), OFF_WUV2 = slot(0);
constexpr uint32_t OFF_XE = OFF_R0 + 2048;
constexpr uint32_t OFF_BS4 = slot(2);
constexpr uint32_t OFF_BS5 = slot(2) + 4096;
constexpr uint32_t OFF_WM = slot(17);
constexpr uint32_t OFF_WO = slot(5);
constexpr uint32_t OFF_W1 = slot(9);
constexpr uint32_t OFF_W2 = slot(13);
constexpr uint32_t OFF_REDG = OFF_R0;
constexpr uint32_t OFF_REDS = OFF_R0 + 4096;
constexpr uint32_t OFF_REDU = OFF_R0 + 8192;
constexpr uint32_t OFF_REDV = OFF_R0 + 12288;
constexpr uint32_t OFF_H1 = OFF_R0 + 16384;

constexpr int BAR_FULL = 8;
constexpr int U_WQ = -8, U_WUK = -4, U_WMOD = 40, U_WUV = 42, U_WO = 46, U_W1 = 50, U_W2 = 52, NUNITS = 54;
constexpr int BAR_EMPTY = 62;
constexpr int BAR_GO = 67, BAR_CLR = 68, BAR_EPOCH = 69;
constexpr int BAR_P2E = 70, BAR_P5D = 71, BAR_P7D = 72;
constexpr int BAR_XE = 73;
constexpr int BAR_FM = 74;
constexpr int BAR_P0D = 75;
constexpr int BAR_X2 = 76;
constexpr int BAR_WA = 77;
__host__ __device__ constexpr uint32_t BAR(int i) { return OFF_BARS + 8 * i; }
constexpr int PACE_T0 = 672;
constexpr int PACE_DT = 320;
constexpr int PACE_DTE = 324;
constexpr int PACE_DTW = 150;
constexpr int PACE_DT2 = 266;
constexpr int PACE_GAP3 = 444;
constexpr int PACE_DT3 = 400;
constexpr int PACE_DTL = 0;
constexpr int PACE_GAP4 = 0;
constexpr int PACE_DT4 = 500;
constexpr int WIN_PRE = 5;
constexpr int WIN_MID = 8;
constexpr int WIN_END = 7;
constexpr int WIN_TAIL = 6;
constexpr int MOD_AT = 3;
constexpr int D_MOD = 600;
constexpr int D_QP = 1600;
constexpr int QX_AT = 7;
constexpr int D_QX = 1600;
constexpr int CNT_AT = 30;
constexpr int GA_AT = 45;
constexpr int X1_D0 = 1100;
constexpr int D_X2 = 300;
constexpr int D_X3A = 400;
constexpr int D_X3B = 1300;
constexpr int D_GB = 300;
constexpr int D_FIN = 450;
constexpr int D_FIN2 = 2000;
constexpr int CLR_CLK = 180;
constexpr int NPROBE = 3;

struct Scratch {
  uint32_t MODA[1024 * 4];
  uint32_t QP[128 * 256 * 2];
  uint32_t FL[2][128];
  uint32_t QX[2][8 * 32 * 256];
  uint32_t epoch;
  uint32_t pad[31];
  uint32_t cnt;
  alignas(131072) uint32_t X3B[16384];
  uint32_t MODB[16384];
  uint32_t IN[128][16384];
};
__device__ uint8_t g_s[sizeof(Scratch) + 131072];

struct Params {
  CUtensorMap wma, wq, wuk, wmod, ckv, wuv, wo, w1, w2;
};

__device__ __forceinline__ void mbar_init(uint32_t bar, int cnt) { asm volatile("mbarrier.init.shared::cta.b64 [%0], %1;" ::"r"(bar), "r"(cnt)); }
__device__ __forceinline__ void mbar_expect(uint32_t bar, uint32_t bytes) { asm volatile("mbarrier.arrive.expect_tx.shared::cta.b64 _, [%0], %1;" ::"r"(bar), "r"(bytes) : "memory"); }
__device__ __forceinline__ void mbar_arrive(uint32_t bar) { asm volatile("mbarrier.arrive.shared::cta.b64 _, [%0];" ::"r"(bar) : "memory"); }
__device__ __forceinline__ void mbar_arrive_cluster(uint32_t bar) { asm volatile("mbarrier.arrive.shared::cluster.b64 _, [%0];" ::"r"(bar) : "memory"); }
__device__ __forceinline__ bool mbar_test(uint32_t bar) {
  uint32_t ok;
  asm volatile("{\n.reg .pred p;\nmbarrier.test_wait.parity.shared::cta.b64 p, [%1], 0;\nselp.u32 %0,1,0,p;\n}" : "=r"(ok) : "r"(bar) : "memory");
  return ok;
}
__device__ __forceinline__ uint32_t gtime32() { uint32_t c; asm volatile("mov.u32 %0, %%globaltimer_lo;" : "=r"(c) :: "memory"); return c; }
__device__ __forceinline__ uint32_t clk32() { uint32_t c; asm volatile("{\n.reg .u64 t;\nmov.u64 t, %%clock64;\ncvt.u32.u64 %0, t;\n}" : "=r"(c) :: "memory"); return c; }
__device__ __forceinline__ void wait_until(uint32_t c0, int clocks) { if (clocks > 0) while ((int)(clk32() - c0) < clocks) {} }
__device__ __forceinline__ void backoff(int clocks) { if (clocks > 0) wait_until(clk32(), clocks); }
__device__ __forceinline__ uint32_t pin32(uint32_t p) { asm volatile("" : "+r"(p)); return p; }
template <typename T> __device__ __forceinline__ T* pin(T* p) { asm volatile("" : "+l"(p)); return p; }
__device__ __forceinline__ uint32_t hold32(uint32_t p) { asm volatile("shfl.sync.bfly.b32 %0, %0, 0, 0x1f, 0xffffffff;" : "+r"(p) :: "memory"); return p; }
__device__ __forceinline__ float holdf(float p) { return __uint_as_float(hold32(__float_as_uint(p))); }
template <typename T> __device__ __forceinline__ T* hold(T* p) {
  asm volatile("{\n.reg .b32 a, b;\nmov.b64 {a, b}, %0;\nshfl.sync.bfly.b32 a, a, 0, 0x1f, 0xffffffff;\nshfl.sync.bfly.b32 b, b, 0, 0x1f, 0xffffffff;\nmov.b64 %0, {a, b};\n}" : "+l"(p) :: "memory");
  return p;
}
constexpr int SPIN_LIMIT = 1 << 22;
__device__ __forceinline__ void mbar_wait(uint32_t bar) {
  asm volatile("{\n.reg .pred p;\nMW_LOOP:\nmbarrier.try_wait.parity.shared::cta.b64 p, [%0], 0;\n@!p bra MW_LOOP;\n}" ::"r"(bar) : "memory");
}
__device__ __forceinline__ void mbar_wait_cluster(uint32_t bar) {
  asm volatile("{\n.reg .pred p;\nMW_LOOP:\nmbarrier.try_wait.parity.acquire.cluster.shared::cta.b64 p, [%0], 0;\n@!p bra MW_LOOP;\n}" ::"r"(bar) : "memory");
}
__device__ __forceinline__ void mbar_wait_b(uint32_t bar) {
  asm volatile("{\n.reg .pred p;\n.reg .u32 c;\nmov.u32 c, 0;\n"
               "MW_LOOP:\nmbarrier.try_wait.parity.shared::cta.b64 p, [%0], 0;\n@p bra MW_DONE;\n"
               "add.u32 c, c, 1;\nsetp.lt.u32 p, c, 1048576;\n@p bra MW_LOOP;\ntrap;\nMW_DONE:\n}"
               ::"r"(bar) : "memory");
}
__device__ __forceinline__ void tma2d(uint32_t dst, const CUtensorMap* m, int c0, int c1, uint32_t bar, uint64_t pol) {
  asm volatile("cp.async.bulk.tensor.2d.shared::cluster.global.mbarrier::complete_tx::bytes.L2::cache_hint [%0], [%1, {%3,%4}], [%2], %5;"
               ::"r"(dst), "l"(m), "r"(bar), "r"(c0), "r"(c1), "l"(pol) : "memory");
}
__device__ __forceinline__ void tma2d_both(uint32_t dst, const CUtensorMap* m, int c0, int c1, uint32_t bar, uint64_t pol) {
  asm volatile("cp.async.bulk.tensor.2d.shared::cluster.global.mbarrier::complete_tx::bytes.multicast::cluster.L2::cache_hint [%0], [%1, {%3,%4}], [%2], %6, %5;"
               ::"r"(dst), "l"(m), "r"(bar), "r"(c0), "r"(c1), "l"(pol), "h"((uint16_t)3) : "memory");
}
__device__ __forceinline__ void tma3d(uint32_t dst, const CUtensorMap* m, int c0, int c1, int c2, uint32_t bar, uint64_t pol) {
  asm volatile("cp.async.bulk.tensor.3d.shared::cluster.global.mbarrier::complete_tx::bytes.L2::cache_hint [%0], [%1, {%3,%4,%5}], [%2], %6;"
               ::"r"(dst), "l"(m), "r"(bar), "r"(c0), "r"(c1), "r"(c2), "l"(pol) : "memory");
}
__device__ __forceinline__ void tma5d(uint32_t dst, const CUtensorMap* m, int c0, int c3, int c4, uint32_t bar, uint64_t pol) {
  asm volatile("cp.async.bulk.tensor.5d.shared::cluster.global.mbarrier::complete_tx::bytes.L2::cache_hint [%0], [%1, {%3,%7,%7,%4,%5}], [%2], %6;"
               ::"r"(dst), "l"(m), "r"(bar), "r"(c0), "r"(c3), "r"(c4), "l"(pol), "r"(0) : "memory");
}
__device__ __forceinline__ void cbar() { asm volatile("bar.sync 1, 256;" ::: "memory"); }
__device__ __forceinline__ void wg0bar() { asm volatile("bar.sync 2, 128;" ::: "memory"); }
__device__ __forceinline__ bool cbar_or(bool p) {
  uint32_t r;
  asm volatile("{\n.reg .pred p, q;\nsetp.ne.u32 p, %1, 0;\nbarrier.cta.red.or.aligned.pred q, 1, 256, p;\nselp.u32 %0, 1, 0, q;\n}" : "=r"(r) : "r"((uint32_t)p) : "memory");
  return r;
}

__device__ __forceinline__ uint32_t ldg_rlx1(const void* p) { uint32_t v; asm volatile("ld.relaxed.gpu.global.u32 %0, [%1];" : "=r"(v) : "l"(p) : "memory"); return v; }
__device__ __forceinline__ void stg4(void* p, uint4 v) { asm volatile("st.relaxed.gpu.global.v4.u32 [%0], {%1,%2,%3,%4};" ::"l"(p), "r"(v.x), "r"(v.y), "r"(v.z), "r"(v.w) : "memory"); }
__device__ __forceinline__ void stg1(void* p, uint32_t a) { asm volatile("st.relaxed.gpu.global.u32 [%0], %1;" ::"l"(p), "r"(a) : "memory"); }
__device__ __forceinline__ uint32_t nz(uint32_t w) { uint32_t r; asm("max.u32 %0, %1, 1;" : "=r"(r) : "r"(w)); return r; }
__device__ __forceinline__ uint32_t min3(uint32_t a, uint32_t b, uint32_t c) { return min(min(a, b), c); }

__device__ __forceinline__ uint32_t pack_bf16(float lo, float hi) { uint32_t r; asm("cvt.rn.bf16x2.f32 %0, %1, %2;" : "=r"(r) : "f"(hi), "f"(lo)); return r; }
__device__ __forceinline__ float bf_lo(uint32_t w) { return __uint_as_float(w << 16); }
__device__ __forceinline__ float bf_hi(uint32_t w) { return __uint_as_float(w & 0xffff0000u); }
__device__ __forceinline__ float ex2(float x) { float r; asm("ex2.approx.ftz.f32 %0, %1;" : "=f"(r) : "f"(x)); return r; }
__device__ __forceinline__ float rcp(float x) { float r; asm("rcp.approx.ftz.f32 %0, %1;" : "=f"(r) : "f"(x)); return r; }
__device__ __forceinline__ float rsq(float x) { float r; asm("rsqrt.approx.ftz.f32 %0, %1;" : "=f"(r) : "f"(x)); return r; }
__device__ __forceinline__ uint32_t silu2(uint32_t c) {
  const float a = bf_lo(c), b = bf_hi(c);
  return pack_bf16(__fdividef(a, 1.f + __expf(-a)), __fdividef(b, 1.f + __expf(-b)));
}
__device__ __forceinline__ uint32_t shl_clamp(uint32_t x, int s) { uint32_t r; asm("shl.b32 %0, %1, %2;" : "=r"(r) : "r"(x), "r"(s)); return r; }

__device__ __forceinline__ void ldsm4(uint32_t (&r)[4], uint32_t a) { asm volatile("ldmatrix.sync.aligned.m8n8.x4.shared.b16 {%0,%1,%2,%3}, [%4];" : "=r"(r[0]), "=r"(r[1]), "=r"(r[2]), "=r"(r[3]) : "r"(a) : "memory"); }
__device__ __forceinline__ void ldsm4t(uint32_t (&r)[4], uint32_t a) { asm volatile("ldmatrix.sync.aligned.m8n8.x4.trans.shared.b16 {%0,%1,%2,%3}, [%4];" : "=r"(r[0]), "=r"(r[1]), "=r"(r[2]), "=r"(r[3]) : "r"(a) : "memory"); }
__device__ __forceinline__ void ldsm2t(uint32_t& r0, uint32_t& r1, uint32_t a) { asm volatile("ldmatrix.sync.aligned.m8n8.x2.trans.shared.b16 {%0,%1}, [%2];" : "=r"(r0), "=r"(r1) : "r"(a) : "memory"); }
__device__ __forceinline__ void stsm4t(uint32_t a, uint32_t r0, uint32_t r1, uint32_t r2, uint32_t r3) { asm volatile("stmatrix.sync.aligned.m8n8.x4.trans.shared.b16 [%0], {%1,%2,%3,%4};" ::"r"(a), "r"(r0), "r"(r1), "r"(r2), "r"(r3) : "memory"); }
__device__ __forceinline__ void stsm2t(uint32_t a, uint32_t r0, uint32_t r1) { asm volatile("stmatrix.sync.aligned.m8n8.x2.trans.shared.b16 [%0], {%1,%2};" ::"r"(a), "r"(r0), "r"(r1) : "memory"); }
__device__ __forceinline__ void mma16816(float (&d)[4], const uint32_t (&a)[4], uint32_t b0, uint32_t b1) {
  asm volatile("mma.sync.aligned.m16n8k16.row.col.f32.bf16.bf16.f32 {%0,%1,%2,%3}, {%4,%5,%6,%7}, {%8,%9}, {%0,%1,%2,%3};"
               : "+f"(d[0]), "+f"(d[1]), "+f"(d[2]), "+f"(d[3]) : "r"(a[0]), "r"(a[1]), "r"(a[2]), "r"(a[3]), "r"(b0), "r"(b1));
}
__device__ __forceinline__ void mma_v(float (&d)[4], const uint4& a, uint32_t b0, uint32_t b1) {
  asm volatile("mma.sync.aligned.m16n8k16.row.col.f32.bf16.bf16.f32 {%0,%1,%2,%3}, {%4,%5,%6,%7}, {%8,%9}, {%0,%1,%2,%3};"
               : "+f"(d[0]), "+f"(d[1]), "+f"(d[2]), "+f"(d[3]) : "r"(a.x), "r"(a.y), "r"(a.z), "r"(a.w), "r"(b0), "r"(b1));
}
__device__ __forceinline__ void sts1(uint32_t a, uint32_t v) { asm volatile("st.shared.u32 [%0], %1;" ::"r"(a), "r"(v) : "memory"); }
__device__ __forceinline__ void sts2(uint32_t a, uint32_t x, uint32_t y) { asm volatile("st.shared.v2.u32 [%0], {%1,%2};" ::"r"(a), "r"(x), "r"(y) : "memory"); }
__device__ __forceinline__ void sts4(uint32_t a, uint4 v) { asm volatile("st.shared.v4.u32 [%0], {%1,%2,%3,%4};" ::"r"(a), "r"(v.x), "r"(v.y), "r"(v.z), "r"(v.w) : "memory"); }
__device__ __forceinline__ void sts4f(uint32_t a, float x, float y, float z, float w) { asm volatile("st.shared.v4.f32 [%0], {%1,%2,%3,%4};" ::"r"(a), "f"(x), "f"(y), "f"(z), "f"(w) : "memory"); }
__device__ __forceinline__ void sts2f(uint32_t a, float x, float y) { asm volatile("st.shared.v2.f32 [%0], {%1,%2};" ::"r"(a), "f"(x), "f"(y) : "memory"); }
__device__ __forceinline__ void stsf(uint32_t a, float v) { asm volatile("st.shared.f32 [%0], %1;" ::"r"(a), "f"(v) : "memory"); }
__device__ __forceinline__ uint32_t lds1(uint32_t a) { uint32_t v; asm volatile("ld.shared.u32 %0, [%1];" : "=r"(v) : "r"(a) : "memory"); return v; }
__device__ __forceinline__ uint2 lds2(uint32_t a) { uint2 v; asm volatile("ld.shared.v2.u32 {%0,%1}, [%2];" : "=r"(v.x), "=r"(v.y) : "r"(a) : "memory"); return v; }
__device__ __forceinline__ float ldsf(uint32_t a) { float v; asm volatile("ld.shared.f32 %0, [%1];" : "=f"(v) : "r"(a) : "memory"); return v; }
__device__ __forceinline__ float2 ldsf2(uint32_t a) { float2 v; asm volatile("ld.shared.v2.f32 {%0,%1}, [%2];" : "=f"(v.x), "=f"(v.y) : "r"(a) : "memory"); return v; }
__device__ __forceinline__ float4 ldsf4(uint32_t a) { float4 v; asm volatile("ld.shared.v4.f32 {%0,%1,%2,%3}, [%4];" : "=f"(v.x), "=f"(v.y), "=f"(v.z), "=f"(v.w) : "r"(a) : "memory"); return v; }
__device__ __forceinline__ uint4 lds4(uint32_t a) { uint4 v; asm volatile("ld.shared.v4.u32 {%0,%1,%2,%3}, [%4];" : "=r"(v.x), "=r"(v.y), "=r"(v.z), "=r"(v.w) : "r"(a) : "memory"); return v; }

__device__ __forceinline__ void wg_fence() { asm volatile("wgmma.fence.sync.aligned;" ::: "memory"); }
__device__ __forceinline__ void wg_commit() { asm volatile("wgmma.commit_group.sync.aligned;" ::: "memory"); }
template <int N> __device__ __forceinline__ void wg_wait() { asm volatile("wgmma.wait_group.sync.aligned %0;" ::"n"(N) : "memory"); }
__host__ __device__ constexpr uint32_t dlo(uint32_t addr) { return (addr >> 4) | 0x10000u; }
constexpr uint32_t ONE2 = 0x3f803f80u;
template <int TA, int ACC> __device__ __forceinline__ void wgmma_ss(float (&d)[16], uint32_t da, uint32_t db) {
  asm volatile("{\n.reg .b64 da, db;\nmov.b64 da, {%16, 0x40000040};\nmov.b64 db, {%17, 0x40000040};\n"
               "wgmma.mma_async.sync.aligned.m64n32k16.f32.bf16.bf16 {%0,%1,%2,%3,%4,%5,%6,%7,%8,%9,%10,%11,%12,%13,%14,%15}, da, db, %18, 1, 1, %19, 0;\n}"
               : "+f"(d[0]), "+f"(d[1]), "+f"(d[2]), "+f"(d[3]), "+f"(d[4]), "+f"(d[5]), "+f"(d[6]), "+f"(d[7]),
                 "+f"(d[8]), "+f"(d[9]), "+f"(d[10]), "+f"(d[11]), "+f"(d[12]), "+f"(d[13]), "+f"(d[14]), "+f"(d[15])
               : "r"(da), "r"(db), "n"(ACC), "n"(TA));
}
template <int TA, int ACC> __device__ __forceinline__ void wgmma_ss(float (&d)[8], uint32_t da, uint32_t db) {
  asm volatile("{\n.reg .b64 da, db;\nmov.b64 da, {%8, 0x40000040};\nmov.b64 db, {%9, 0x40000040};\n"
               "wgmma.mma_async.sync.aligned.m64n16k16.f32.bf16.bf16 {%0,%1,%2,%3,%4,%5,%6,%7}, da, db, %10, 1, 1, %11, 0;\n}"
               : "+f"(d[0]), "+f"(d[1]), "+f"(d[2]), "+f"(d[3]), "+f"(d[4]), "+f"(d[5]), "+f"(d[6]), "+f"(d[7])
               : "r"(da), "r"(db), "n"(ACC), "n"(TA));
}
__device__ __forceinline__ void wgmma_n8(float (&d)[4], uint32_t da, uint32_t db) {
  asm volatile("{\n.reg .b64 da, db;\nmov.b64 da, {%4, 0x40000040};\nmov.b64 db, {%5, 0x40000040};\n"
               "wgmma.mma_async.sync.aligned.m64n8k16.f32.bf16.bf16 {%0,%1,%2,%3}, da, db, 1, 1, 1, 1, 0;\n}"
               : "+f"(d[0]), "+f"(d[1]), "+f"(d[2]), "+f"(d[3]) : "r"(da), "r"(db));
}
template <int K> __device__ __forceinline__ void tie(float (&d)[K]) {
#pragma unroll
  for (int i = 0; i < K; i += 8)
    asm volatile("" : "+f"(d[i]), "+f"(d[i + 1]), "+f"(d[i + 2]), "+f"(d[i + 3]), "+f"(d[i + 4]), "+f"(d[i + 5]), "+f"(d[i + 6]), "+f"(d[i + 7]) :: "memory");
}
__device__ __forceinline__ void tie(uint4& v) { asm volatile("" : "+r"(v.x), "+r"(v.y), "+r"(v.z), "+r"(v.w) :: "memory"); }
__device__ __forceinline__ void tie(uint2& v) { asm volatile("" : "+r"(v.x), "+r"(v.y) :: "memory"); }
template <int I> struct IC { static constexpr int value = I; };
template <int B, int E, typename F> __device__ __forceinline__ void sfor(F&& f) { if constexpr (B < E) { f(IC<B>{}); sfor<B + 1, E>(f); } }

__device__ __forceinline__ uint2 ldg_u64(const void* p) {
  uint2 v; asm volatile("{\n.reg .b64 a;\nld.relaxed.gpu.global.b64 a, [%2];\nmov.b64 {%0,%1}, a;\n}" : "=r"(v.x), "=r"(v.y) : "l"(p) : "memory"); return v;
}
__device__ __forceinline__ uint4 ldg_2u64(const void* p) {
  uint4 v; asm volatile("{\n.reg .b64 a, b;\nld.relaxed.gpu.global.v2.b64 {a, b}, [%4];\nmov.b64 {%0,%1}, a;\nmov.b64 {%2,%3}, b;\n}" : "=r"(v.x), "=r"(v.y), "=r"(v.z), "=r"(v.w) : "l"(p) : "memory"); return v;
}
__device__ __forceinline__ uint4 ldg_u128(const void* p) {
  uint4 v; asm volatile("{\n.reg .b64 a, b;\n.reg .b128 q;\nld.relaxed.gpu.global.b128 q, [%4];\nmov.b128 {a, b}, q;\nmov.b64 {%0,%1}, a;\nmov.b64 {%2,%3}, b;\n}" : "=r"(v.x), "=r"(v.y), "=r"(v.z), "=r"(v.w) : "l"(p) : "memory"); return v;
}
__device__ __forceinline__ void stg_u64(void* p, uint32_t x, uint32_t y) {
  asm volatile("{\n.reg .b64 a;\nmov.b64 a, {%1,%2};\nst.relaxed.gpu.global.b64 [%0], a;\n}" ::"l"(p), "r"(x), "r"(nz(y)) : "memory");
}
__device__ __forceinline__ void stg4_b128(void* p, uint4 v) {
  asm volatile("{\n.reg .b64 a, b;\n.reg .b128 q;\nmov.b64 a, {%1,%2};\nmov.b64 b, {%3,%4};\nmov.b128 q, {a, b};\nst.relaxed.gpu.global.b128 [%0], q;\n}" ::"l"(p), "r"(v.x), "r"(v.y), "r"(v.z), "r"(v.w) : "memory");
}
__device__ __forceinline__ void stg_u128(void* p, uint4 v) {
  asm volatile("{\n.reg .b64 a, b;\n.reg .b128 q;\nmov.b64 a, {%1,%2};\nmov.b64 b, {%3,%4};\nmov.b128 q, {a, b};\nst.relaxed.gpu.global.b128 [%0], q;\n}" ::"l"(p), "r"(v.x), "r"(v.y), "r"(v.z), "r"(nz(v.w)) : "memory");
}
__device__ __forceinline__ uint32_t hmul2(uint32_t a, uint32_t b) { uint32_t r; asm("mul.rn.bf16x2 %0, %1, %2;" : "=r"(r) : "r"(a), "r"(b)); return r; }
__device__ __forceinline__ uint32_t hadd2(uint32_t a, uint32_t b) { uint32_t r; asm("add.rn.bf16x2 %0, %1, %2;" : "=r"(r) : "r"(a), "r"(b)); return r; }
__device__ __forceinline__ uint32_t movm(uint32_t a) { uint32_t d; asm volatile("movmatrix.sync.aligned.m8n8.trans.b16 %0, %1;" : "=r"(d) : "r"(a)); return d; }
__device__ __forceinline__ uint2 ldg_rlx2(const void* p) { uint2 v; asm volatile("ld.relaxed.gpu.global.v2.u32 {%0,%1}, [%2];" : "=r"(v.x), "=r"(v.y) : "l"(p) : "memory"); return v; }
__device__ __forceinline__ uint4 ldg_in4(const void* p) { uint4 v; asm volatile("ld.global.nc.v4.u32 {%0,%1,%2,%3}, [%4];" : "=r"(v.x), "=r"(v.y), "=r"(v.z), "=r"(v.w) : "l"(p) : "memory"); return v; }
__device__ __forceinline__ uint32_t ldg_in1(const void* p) { uint32_t v; asm volatile("ld.global.nc.u32 %0, [%1];" : "=r"(v) : "l"(p)); return v; }

template <int NL, typename F> __device__ __forceinline__ void sum4_to_smem(uint2 (&v)[4], const uint32_t* x, uint32_t dst, F&& meanwhile) {
  uint32_t r0, r1;
#pragma unroll 1
  while (true) {
    meanwhile();
#pragma unroll
    for (int i = 0; i < 4; i++) tie(v[i]);
    const bool ok = __all_sync(~0u, min(min3(v[0].y, v[1].y, v[2].y), v[3].y) != 0);
    r0 = pack_bf16((bf_lo(v[0].x) + bf_lo(v[1].x)) + (bf_lo(v[2].x) + bf_lo(v[3].x)), (bf_hi(v[0].x) + bf_hi(v[1].x)) + (bf_hi(v[2].x) + bf_hi(v[3].x)));
    r1 = pack_bf16((bf_lo(v[0].y) + bf_lo(v[1].y)) + (bf_lo(v[2].y) + bf_lo(v[3].y)), (bf_hi(v[0].y) + bf_hi(v[1].y)) + (bf_hi(v[2].y) + bf_hi(v[3].y)));
    sts1(dst, r0);
    sts1(dst + 128, r1);
    if (ok) break;
#pragma unroll
    for (int i = 0; i < NL; i++) v[i] = ldg_u64(x + i * 512);
  }
}
__device__ __forceinline__ void load_a_t(uint32_t (&a)[8][4], uint32_t box, int wq, int lane) {
  const int mi = lane >> 3, r = lane & 7;
  const uint32_t base = box + (8 * (mi >> 1) + r) * 128 + (((2 * wq + (mi & 1)) ^ r) << 4);
#pragma unroll
  for (int ks = 0; ks < 8; ks++) ldsm4t(a[ks], base + ks * 2048);
}
__device__ __forceinline__ void mma128(float (&d)[4], const uint32_t (&a)[8][4], uint32_t bs) {
  float e[4][4] = {{0.f, 0.f, 0.f, 0.f}, {0.f, 0.f, 0.f, 0.f}, {0.f, 0.f, 0.f, 0.f}, {0.f, 0.f, 0.f, 0.f}};
  uint32_t b[4][4];
#pragma unroll
  for (int kk = 0; kk < 4; kk++) ldsm4t(b[kk], bs + 32 * kk * 16);
#pragma unroll
  for (int kk = 0; kk < 4; kk++) { mma16816(e[(2 * kk) & 3], a[2 * kk], b[kk][0], b[kk][1]); mma16816(e[(2 * kk + 1) & 3], a[2 * kk + 1], b[kk][2], b[kk][3]); }
#pragma unroll
  for (int i = 0; i < 4; i++) d[i] = (e[0][i] + e[1][i]) + (e[2][i] + e[3][i]);
}
template <int NL, typename F> __device__ __forceinline__ void poll_vectors(const uint32_t* p, const uint32_t* q, F&& f) {
  int it = 0;
  bool ok;
  uint4 v[NL];
#pragma unroll
  for (int i = 0; i < NL; i++) v[i] = make_uint4(0, 0, 0, 0);
#pragma unroll 1
  do {
    if (++it > SPIN_LIMIT) __trap();
#pragma unroll
    for (int i = 0; i < NL; i++) if (NL <= 4 || min(v[i].y, v[i].w) == 0) v[i] = ldg_2u64(i < NL / 2 ? p + i * 128 : q + (i - NL / 2) * 128);
    f(v);
    uint32_t m0 = min(v[0].y, v[0].w), m1 = min(v[1].y, v[1].w);
#pragma unroll
    for (int i = 2; i < NL; i += 2) { m0 = min3(m0, v[i].y, v[i].w); m1 = min3(m1, v[i + 1].y, v[i + 1].w); }
    ok = __all_sync(~0u, min(m0, m1) != 0);
  } while (!ok);
}

__global__ void __cluster_dims__(2, 1, 1) __launch_bounds__(NTHREADS, 1)
fused_decode_kernel(__nv_bfloat16* __restrict__ gout, Scratch* __restrict__ gs, const uint8_t* __restrict__ gwq,
                    const uint8_t* __restrict__ gx, const uint8_t* __restrict__ gc,
                    const __grid_constant__ Params P) {
  extern __shared__ __align__(1024) uint8_t smem_raw[];
  const uint32_t hi = pin32((uint32_t)__cvta_generic_to_shared(smem_raw) - SB);
  const int tid = threadIdx.x, lane = tid & 31;
  const int w = __shfl_sync(0xffffffffu, tid >> 5, 0);
  const int cta = blockIdx.x;
  const int g = lane >> 2, t = lane & 3;
  const int hI = cta >> 2, jI = cta & 3;
  const int bI = cta >> 4, pI = (cta >> 1) & 7, rI = cta & 1;

  uint32_t epoch0 = 0;
  if (tid == 320) epoch0 = ldg_rlx1(&gs->epoch);
  const bool p0a = (cta & 7) == 0;
  uint4 cw0, cw1, xr0, xr1;
  uint32_t xc;
  if (w < 8) {
    const uint8_t* src = gwq + (size_t)(128 * jI + (tid >> 4)) * 8192 + hI * 256 + (tid & 15) * 16;
    const uint32_t dst = hi + OFF_R1 + ((tid >> 3) & 1) * 16384 + (tid >> 4) * 128 + (((tid ^ (tid >> 4)) & 7) << 4);
    if (p0a) {
      cw0 = ldg_in4(gc + g * 1024 + w * 128 + t * 32); cw1 = ldg_in4(gc + g * 1024 + w * 128 + t * 32 + 16);
      xr0 = ldg_in4(gx + w * 1024 + lane * 16); xr1 = ldg_in4(gx + w * 1024 + 512 + lane * 16);
      xc = ldg_in1(gx + w * 1024 + (cta & 63) * 16 + lane * 4);
    } else {
#pragma unroll
      for (int i = 0; i < 4; i++) asm volatile("cp.async.cg.shared.global [%0], [%1], 16;" ::"r"(dst + i * 2048), "l"(src + i * 16 * 8192) : "memory");
    }
  }
  auto half_of = [&](int c, int k) { return ((lds1(hi + OFF_FM + (c >> 5) * 4) >> (c & 31)) ^ k) & 1; };
  auto inbox = [&](int c, int k, uint32_t bits, int pos, int off) { return gs->IN[0] + (uint32_t)(c * 16384 + k * 2048 + off + (((bits >> pos) & 1) << 10)); };
  auto front_unit = [&](int k, uint64_t pol) {
    tma2d(hi + OFF_R1 + ((k & 4) + 2 * (k & 1) + ((k >> 1) & 1)) * 8192, k < 4 ? &P.wq : &P.wuk, 128 * hI + 64 * (k & 1), 128 * jI + 64 * ((k >> 1) & 1), hi + BAR(k), pol);
  };
  uint32_t tnext = 0;
  if (tid == 256) {
    tnext = gtime32() + PACE_T0;
    if (hi & 0xffffff) __trap();
    if (p0a) {
#pragma unroll
      for (int i = 0; i < 4; i++) mbar_init(hi + BAR(BAR_WA + i), 1);
      asm volatile("fence.mbarrier_init.release.cluster;" ::: "memory");
      uint64_t pol; asm volatile("createpolicy.fractional.L2::evict_first.b64 %0, 1.0;" : "=l"(pol));
#pragma unroll
      for (int i = 0; i < 4; i++) tma2d(hi + slot(8 + 2 * i), &P.wma, 8 * cta, 128 * i, hi + BAR(BAR_WA + i), pol);
    }
    asm volatile("prefetch.tensormap [%0];" ::"l"(&P.wq) : "memory");
  } else if (tid == 288) {
#pragma unroll
    for (int i = 0; i < BAR_WA; i++)
      mbar_init(hi + BAR(i), (i >= BAR_EMPTY && i < BAR_EMPTY + 5) ? 16 : (i >= BAR_P2E && i <= BAR_P7D) ? 8 : i == BAR_P0D ? 4 : 1);
    asm volatile("fence.mbarrier_init.release.cluster;" ::: "memory");
  }
  __syncthreads();

  if (w == 8) {
    auto twice = [](int n) { return (n & ~1) == U_W1 || (n & ~1) == U_WMOD; };
    if (p0a && lane < 4) mbar_expect(hi + BAR(BAR_WA) + 8 * lane, 16384);
    mbar_expect(hi + BAR(0) + 8 * lane, (lane < 2 && !p0a) ? 0 : 8192);
    if (p0a) tnext -= 2 * PACE_DT;
    if (lane < BAR_EMPTY - 32) mbar_expect(hi + BAR(32) + 8 * lane, twice(32 + lane - BAR_FULL) ? 16384 : 8192);
    __syncwarp();
    const int h = hI, j = jI;
    if (lane == 0) {
      uint64_t pol; asm volatile("createpolicy.fractional.L2::evict_first.b64 %0, 1.0;" : "=l"(pol));
      auto pace = [&](int dt) { while ((int)(gtime32() - tnext) < 0) {} tnext += dt; };
      asm volatile("prefetch.tensormap [%0];" ::"l"(&P.wuk) : "memory");
      asm volatile("prefetch.tensormap [%0];" ::"l"(&P.wmod) : "memory");
      asm volatile("prefetch.tensormap [%0];" ::"l"(&P.ckv) : "memory");
#pragma unroll 1
      for (int k = p0a ? 0 : 2; k < 8; k++) { if (k >= WIN_PRE) mbar_wait(hi + BAR(0) + 8 * (k - WIN_PRE)); pace(PACE_DT); front_unit(k, pol); }
      bool go = false;
      const int row0 = bI * 4096 + (cta & 15) * 64;
#pragma unroll 1
      for (int n = 0; n < 24; n++) {
        if (n == 8 && p0a) mbar_wait(hi + BAR(BAR_P0D));
        if (n == 16) mbar_wait(hi + BAR(BAR_P2E));
        if (n == 23) mbar_wait(hi + BAR(BAR_EMPTY));
        if (!go) go = mbar_test(hi + BAR(BAR_GO));
        mbar_wait(hi + BAR(BAR_FULL) + 8 * (n - (go ? WIN_MID : WIN_PRE)));
        pace(PACE_DT);
        tma2d(hi + slot(box_slot(n)), &P.ckv, (n & 7) * 64, row0 + (n >> 3) * 1024, hi + BAR(BAR_FULL) + 8 * n, pol);
      }
      asm volatile("prefetch.tensormap [%0];" ::"l"(&P.wuv) : "memory");
      asm volatile("prefetch.tensormap [%0];" ::"l"(&P.wo) : "memory");
      asm volatile("prefetch.tensormap [%0];" ::"l"(&P.w1) : "memory");
      asm volatile("prefetch.tensormap [%0];" ::"l"(&P.w2) : "memory");
      const int row1 = bI * 4096 + (24 + pI) * 64;
      tnext += rI * (PACE_DT / 2) - PACE_DT / 4;
#pragma unroll 1
      for (int n = 24 + rI; n < 40; n += 2) {
        const int c = n - 23;
        const int m = c >= 2 * WIN_END ? n - 2 * WIN_END : 23 - (2 * WIN_END - c) / 2;
        mbar_wait(hi + BAR(BAR_FULL) + 8 * m);
        mbar_wait(hi + BAR(BAR_EMPTY) + (c & ~7));
        pace(PACE_DTE);
        tma2d_both(hi + slot(c), &P.ckv, (n & 7) * 64, row1 + (n >> 3) * 512, hi + BAR(BAR_FULL) + 8 * n, pol);
      }
      mbar_wait(hi + BAR(BAR_EMPTY + 2));
      const bool late = cta >= 96;
      auto unit = [&](int i) { return (!late || i < U_WMOD || i >= U_W1) ? i : i < U_W1 - 2 ? i + 2 : i - 8; };
      if (late) tnext += 2 * PACE_DTW;
#pragma unroll 1
      for (int i = U_WMOD; i < (cta < NFF ? NUNITS : U_W1); i++) {
        const int n = unit(i), c = i - 39, u = n & 1;
        mbar_wait(hi + BAR(BAR_FULL) + 8 * (c >= WIN_TAIL ? unit(i - WIN_TAIL) : 39 - 2 * (WIN_TAIL - c)));
        if (n == U_WUV + 3) mbar_wait(hi + BAR(BAR_EMPTY + 3));
        if (n == U_WO) tnext += PACE_GAP3;
        if (n == U_W1) { mbar_wait(hi + BAR(BAR_EMPTY + 4)); tnext += PACE_GAP4; }
        const uint32_t bar = hi + BAR(BAR_FULL) + 8 * n;
        pace(n < U_WUV ? (late ? PACE_DTL : PACE_DTW) : n < U_WO ? PACE_DT2 : n < U_W1 ? PACE_DT3 : PACE_DT4);
        if (twice(n)) tma2d_both(hi + (n < U_WO ? OFF_WM : OFF_W1) + (2 * u + rI) * 8192, n < U_WO ? &P.wmod : &P.w1, (n < U_WO ? 1024 : 0) + 16 * (cta & ~1), 256 * u + 128 * rI, bar, pol);
        else if (n < U_WO) tma5d(hi + slot(n < U_WUV + 2 ? n - 21 : n - 44), &P.wuv, 128 * h + 64 * u, (n - U_WUV) & 2, 2 * j, bar, pol);
        else if (n < U_W1) tma2d(hi + slot(n - 41), &P.wo, 128 * j + 64 * u, 128 * h + 32 * ((n - U_WO) & 2), bar, pol);
        else tma3d(hi + OFF_W2 + u * 8192, &P.w2, 0, FCH * cta, 4 * u, bar, pol);
      }
    }
    return;
  }

  if (w == 11) {
    const uint4 z = make_uint4(0, 0, 0, 0);
    uint32_t f = 0, f2 = 0;
    {
      uint32_t* const p = ((lane & 2) ? gs->X3B + 4 * 2048 + cta * 8 : gs->IN[cta] + 4 * 2048 + 960) + ((lane & 1) << 10);
      if (lane < 8) stg4(p + (lane & 4), z);
      __syncwarp();
      uint32_t best = ~0u;
#pragma unroll 1
      for (int i = 0; i < 4 * NPROBE + (int)(hi & 1); i++) {
        uint32_t v = 0;
        const uint32_t c0 = clk32();
        if (lane == (i & 3)) asm volatile("atom.relaxed.gpu.global.exch.b32 %0, [%1], %2;" : "=r"(v) : "l"(p), "r"(i) : "memory");
        v = __shfl_sync(~0u, v, i & 3);
        const uint32_t dt = clk32() - c0 + (v >> 31);
        if (lane == (i & 3)) best = min(best, dt);
      }
      const uint32_t m = __ballot_sync(~0u, best < __shfl_xor_sync(~0u, best, 1));
      f = (m >> 1) & 1; f2 = (m >> 3) & 1;
    }
    mbar_wait(hi + BAR(BAR_EPOCH));
    const uint32_t epoch = lds1(hi + OFF_EPOCH);
    const int par = epoch & 1;
    if (lane == 0) stg1(gs->FL[par] + cta, 1 + f);
    mbar_wait(hi + BAR(BAR_P2E));
#pragma unroll 1
    for (int i = 0; i < 16; i++) {
      const uint32_t c0 = clk32();
      uint32_t* p = gs->IN[cta] + (i >> 1) * 2048 + (((f ^ (i >> 1)) & 1) << 10) + (i & 1) * 512 + lane * 4;
#pragma unroll
      for (int q = 0; q < 4; q++) stg4(p + q * 128, z);
      if (i == 0 && lane < 16) stg4(gs->X3B + cta * 64 + lane * 4, z);
      if (i == 1) stg4(gs->MODB + cta * 128 + lane * 4, z);
      wait_until(c0, CLR_CLK);
    }
    {
      uint32_t u[4];
      do {
#pragma unroll
        for (int i = 0; i < 4; i++) u[i] = ldg_rlx1(gs->FL[par] + 32 * i + lane);
      } while (!__all_sync(~0u, min(min(u[0], u[1]), min(u[2], u[3])) != 0));
      const uint4 m = make_uint4(__ballot_sync(~0u, u[0] == 2), __ballot_sync(~0u, u[1] == 2), __ballot_sync(~0u, u[2] == 2), __ballot_sync(~0u, u[3] == 2));
      if (lane == 0) { sts4(hi + OFF_FM, m); sts1(hi + OFF_FM + 16, f2); }
      __syncwarp();
      const uint2 m2 = lds2(hi + OFF_FM + 8 * rI);
      const uint32_t mh = (lds1(hi + OFF_FM + (hI >> 3) * 4) >> (4 * (hI & 7))) & 15;
#pragma unroll 1
      for (int v = 0; v < 8; v++) {
        const int sh = 8 * t + 2 * (v >> 2) + (bI >> 2);
        uint32_t fb = (((m2.x >> sh) & 0x11) | (((m2.y >> sh) & 0x11) << 1)) ^ ((bI & 1) ? 0x33 : 0);
        fb |= mh << 8;
        fb |= half_of(4 * (8 * jI + v) + (g >> 1), 0) << 12;
        fb |= half_of((16 * rI + 4 * (v & 3) + (lane >> 3)) * 4 + (lane & 2), 0) << 13;
        fb |= ((f2 ^ (v >> 2)) & 1) << 14;
        fb |= (((lds1(hi + OFF_FM + (v >> 1) * 4) >> (16 * (v & 1) + (g >> 1))) & 0x1111) ^ (cta >= 56 ? 0x1111 : 0)) << 16;
        sts1(hi + OFF_FB + (v * 32 + lane) * 4, fb);
      }
      __syncwarp();
      if (lane == 0) mbar_arrive(hi + BAR(BAR_FM));
    }
    asm volatile("fence.acq_rel.gpu;" ::: "memory");
    __syncwarp();
    if (lane == 0) asm volatile("red.relaxed.gpu.global.add.u32 [%0], 1;" ::"l"(&gs->cnt) : "memory");
    mbar_wait(hi + BAR(BAR_GO));
    if (lane == 0) stg1(gs->FL[par ^ 1] + cta, 0u);
#pragma unroll
    for (int i = 0; i < 4; i++) stg4(gs->QP + cta * 512 + (i * 32 + lane) * 4, z);
#pragma unroll
    for (int i = 0; i < 4; i++) stg4(gs->QX[par ^ 1] + cta * 512 + (i * 32 + lane) * 4, z);
    if (lane < 8) stg4(gs->MODA + cta * 32 + lane * 4, z);
    mbar_wait(hi + BAR(BAR_FULL + CNT_AT));
    while ((int)(ldg_rlx1(&gs->cnt) - (epoch + 1) * NCTA) < 0) __nanosleep(100);
    if (lane == 0) mbar_arrive(hi + BAR(BAR_CLR));
    return;
  }
  if (w == 10) {
    const int m0 = 16 * hI + 2 * jI;
    const int bo = lane & 7;
    const uint32_t epoch = __shfl_sync(~0u, epoch0, 0);
    if (lane == 0) { sts1(hi + OFF_EPOCH, epoch); mbar_arrive(hi + BAR(BAR_EPOCH)); }
    mbar_wait_b(hi + BAR(BAR_GO));
    const uint32_t xw0 = hold32(ldg_in1(gx + bo * 1024 + m0 * 2)), xw1 = hold32(ldg_in1(gx + bo * 1024 + m0 * 2 + 16));
    mbar_wait_b(hi + BAR(BAR_CLR));
    const uint32_t* MOD = gs->MODB + (m0 >> 8) * 1024 + ((~(lds1(hi + OFF_FM + 16) ^ (m0 >> 8)) & 1) << 10);
    mbar_wait_b(hi + BAR(BAR_FULL + GA_AT));
    const int mf = m0 + ((g >> 1) & 1) + 8 * (t >> 1), bf = 2 * (g & 1) + (t & 1);
    float ga[4];
    uint32_t gb2;
    {
      uint32_t u[4];
      int it = 0;
      while (true) {
#pragma unroll
        for (int i = 0; i < 4; i++) u[i] = ldg_rlx1(MOD + (m0 + (i & 1) + 8 * (i >> 1)) * 4 + (bo >> 1));
        if (min(min3(u[0], u[1], u[2]), u[3]) != 0) break;
        if (++it > SPIN_LIMIT) __trap();
      }
#pragma unroll
      for (int i = 0; i < 4; i++) ga[i] = (bo & 1) ? bf_hi(u[i]) : bf_lo(u[i]);
    }
    uint32_t x2a, x2b;
    mbar_wait_b(hi + BAR(BAR_FM));
    const uint32_t fo_ = half_of(cta, 0);
    {
      const uint32_t* const pi = hold(inbox(cta, 6, fo_, 0, (4 * (g >> 1) + t) * 8 + (g & 1) * 4));
      uint32_t* const po = hold(gs->X3B + (g >> 2) * 4096 + (cta >> 6) * 2048 + ((g >> 1) & 1) * 1024 + (cta & 63) * 16 + bo * 2);
      const uint32_t one = 0x3f80u << (8 * (g & 2)), s0 = g < 4 ? one : 0u, s1 = g < 4 ? 0u : one;
      const uint32_t e0 = hold32((g & 1) ? 0u : s0), e1 = hold32((g & 1) ? 0u : s1), o0 = hold32((g & 1) ? s0 : 0u), o1 = hold32((g & 1) ? s1 : 0u);
      const float xf[4] = {holdf(bf_lo(xw0)), holdf(bf_hi(xw0)), holdf(bf_lo(xw1)), holdf(bf_hi(xw1))};
#pragma unroll
      for (int i = 0; i < 4; i++) ga[i] = holdf(ga[i]);
      mbar_wait_b(hi + BAR(BAR_P5D));
      backoff(D_X3A);
      float d[4][4];
      poll_vectors<4>(pi, pi + 256, [&](const uint4 (&v)[4]) {
#pragma unroll
        for (int i = 0; i < 4; i++) { d[i][0] = d[i][1] = d[i][2] = d[i][3] = 0.f; mma_v(d[i], v[i], (i & 2) ? o0 : e0, (i & 2) ? o1 : e1); }
      });
      float s[4] = {d[0][0] + d[1][0], d[2][1] + d[3][1], d[0][2] + d[1][2], d[2][3] + d[3][3]};
#pragma unroll
      for (int i = 0; i < 4; i++) s[i] += __shfl_xor_sync(~0u, s[i], 8);
#pragma unroll
      for (int i = 0; i < 4; i++) s[i] += __shfl_xor_sync(~0u, s[i], 16);
      x2a = pack_bf16(xf[0] + ga[0] * s[0], xf[1] + ga[1] * s[1]);
      x2b = pack_bf16(xf[2] + ga[2] * s[2], xf[3] + ga[3] * s[3]);
      stg_u64(po, x2a, x2b);
      mbar_wait(hi + BAR(BAR_P5D));
    }
    {
      const uint32_t ckf = clk32();
      backoff(D_GB);
      int it = 0;
      do { gb2 = ldg_rlx1(MOD + 6 * 2048 + mf * 4 + bf); if (++it > SPIN_LIMIT) __trap(); } while (!__all_sync(~0u, gb2 != 0));
      const uint32_t a0 = __shfl_sync(~0u, x2a, 2 * bf), a1 = __shfl_sync(~0u, x2a, 2 * bf + 1);
      const uint32_t b0 = __shfl_sync(~0u, x2b, 2 * bf), b1 = __shfl_sync(~0u, x2b, 2 * bf + 1);
      const uint32_t y0 = (t & 2) ? b0 : a0, y1 = (t & 2) ? b1 : a1;
      const float r0 = holdf((g & 2) ? bf_hi(y0) : bf_lo(y0)), r1 = holdf((g & 2) ? bf_hi(y1) : bf_lo(y1)), gb0 = holdf(bf_lo(gb2)), gb1 = holdf(bf_hi(gb2));
      const uint32_t* const pi = hold(inbox(cta, 4, fo_, 0, (4 * (g >> 2) + t) * 16 + (g & 3) * 4));
      const uint32_t* const pj = hold(inbox(cta, 5, ~fo_, 0, (4 * (g >> 2) + t) * 16 + (g & 3) * 4));
      __nv_bfloat16* const fo = hold(gout + (2 * bf) * 512 + mf);
      const uint32_t one = (g & 1) ? 0x3f800000u : 0x00003f80u;
      const uint32_t s0 = hold32((g & 2) ? 0u : one), s1 = hold32((g & 2) ? one : 0u);
      if (cta < NFF) { mbar_wait_b(hi + BAR(BAR_P7D)); backoff(D_FIN); } else wait_until(ckf, D_FIN2);
      float d[4][4];
      poll_vectors<NFF / 8>(pi, pj, [&](const uint4 (&v)[NFF / 8]) {
#pragma unroll
        for (int i = 0; i < 4; i++) d[i][0] = d[i][1] = d[i][2] = d[i][3] = 0.f;
#pragma unroll
        for (int i = 0; i < NFF / 8; i++) mma_v(d[i & 3], v[i], s0, s1);
      });
      const bool up = t & 2;
      float v0 = up ? (d[0][2] + d[1][2]) + (d[2][2] + d[3][2]) : (d[0][0] + d[1][0]) + (d[2][0] + d[3][0]);
      float v1 = up ? (d[0][3] + d[1][3]) + (d[2][3] + d[3][3]) : (d[0][1] + d[1][1]) + (d[2][1] + d[3][1]);
      v0 += __shfl_xor_sync(~0u, v0, 16);
      v1 += __shfl_xor_sync(~0u, v1, 16);
      if (g < 4) {
        asm volatile("st.global.u16 [%0], %1;" ::"l"(fo), "h"(__bfloat16_as_ushort(__float2bfloat16(r0 + gb0 * v0))) : "memory");
        asm volatile("st.global.u16 [%0], %1;" ::"l"(fo + 512), "h"(__bfloat16_as_ushort(__float2bfloat16(r1 + gb1 * v1))) : "memory");
      }
    }
    if (cta == 0 && lane == 0) stg1(&gs->epoch, epoch + 1);
    return;
  }

  if (w == 9) {
    uint32_t cf[16][4];
    asm volatile("bar.sync 3, 288;" ::: "memory");
#pragma unroll
    for (int i = 0; i < 16; i++) ldsm4(cf[i], hi + OFF_R0 + (i >> 1) * 1024 + (lane & 7) * 128 + (((4 * (i & 1) + (lane >> 3)) ^ (lane & 7)) << 4));
#pragma unroll
    for (int i = 0; i < 16; i++) cf[i][0] = hold32(cf[i][0]);
    asm volatile("bar.arrive 2, 288;" ::: "memory");
    if (lane == 0) { mbar_expect(hi + BAR(BAR_XE), 16384 + 128); mbar_expect(hi + BAR(BAR_X2), 2048); }
    {
      uint32_t* const mo = gs->MODB + (cta >> 4) * 2048 + (cta & 15) * 64 + lane;
      mbar_wait(hi + BAR(BAR_CLR));
      const uint32_t base = hi + OFF_WM + (8 * (lane >> 4) + (lane & 7)) * 64 + (((2 * rI + ((lane >> 3) & 1)) ^ ((lane & 7) >> 1)) << 4);
      float d[4][4] = {{0.f, 0.f, 0.f, 0.f}, {0.f, 0.f, 0.f, 0.f}, {0.f, 0.f, 0.f, 0.f}, {0.f, 0.f, 0.f, 0.f}};
#pragma unroll
      for (int q = 0; q < 4; q++) {
        if (!(q & 1)) mbar_wait(hi + BAR(BAR_FULL + U_WMOD + (q >> 1)));
        uint32_t a[8][4];
#pragma unroll
        for (int ks = 0; ks < 8; ks++) ldsm4t(a[ks], base + (8 * q + ks) * 1024);
#pragma unroll
        for (int ks = 0; ks < 8; ks++) mma16816(d[ks & 3], a[ks], cf[4 * q + (ks >> 1)][2 * (ks & 1)], cf[4 * q + (ks >> 1)][2 * (ks & 1) + 1]);
      }
      const uint32_t y0 = nz(pack_bf16((d[0][0] + d[1][0]) + (d[2][0] + d[3][0]), (d[0][1] + d[1][1]) + (d[2][1] + d[3][1])));
      const uint32_t y1 = nz(pack_bf16((d[0][2] + d[1][2]) + (d[2][2] + d[3][2]), (d[0][3] + d[1][3]) + (d[2][3] + d[3][3])));
      stg1(mo, y0); stg1(mo + 32, y1);
      stg1(mo + 1024, y0); stg1(mo + 1056, y1);
    }
    return;
  }

  const int wg = w >> 2, wq = w & 3;
  if (!p0a) {
    asm volatile("cp.async.wait_all;" ::: "memory");
    cw0 = ldg_in4(gc + g * 1024 + w * 128 + t * 32); cw1 = ldg_in4(gc + g * 1024 + w * 128 + t * 32 + 16);
  }
  sts4(hi + OFF_R0 + w * 1024 + g * 128 + (((2 * t) ^ g) << 4), make_uint4(silu2(cw0.x), silu2(cw0.y), silu2(cw0.z), silu2(cw0.w)));
  sts4(hi + OFF_R0 + w * 1024 + g * 128 + (((2 * t + 1) ^ g) << 4), make_uint4(silu2(cw1.x), silu2(cw1.y), silu2(cw1.z), silu2(cw1.w)));
  asm volatile("bar.arrive 3, 288;" ::: "memory");
  if (p0a) {
    asm volatile("fence.proxy.async.shared::cta;" ::: "memory");
  {
    float v[16];
    const uint32_t u[8] = {xr0.x, xr0.y, xr0.z, xr0.w, xr1.x, xr1.y, xr1.z, xr1.w};
#pragma unroll
    for (int i = 0; i < 8; i++) { v[2 * i] = bf_lo(u[i]); v[2 * i + 1] = bf_hi(u[i]); }
    float s = (((v[0] + v[1]) + (v[2] + v[3])) + ((v[4] + v[5]) + (v[6] + v[7]))) + (((v[8] + v[9]) + (v[10] + v[11])) + ((v[12] + v[13]) + (v[14] + v[15])));
#pragma unroll
    for (int o = 16; o; o >>= 1) s += __shfl_xor_sync(~0u, s, o);
    const float mu = s * (1.f / 512.f);
    float q0 = 0.f, q1 = 0.f;
#pragma unroll
    for (int i = 0; i < 8; i++) { const float a = v[2 * i] - mu, b = v[2 * i + 1] - mu; q0 += a * a; q1 += b * b; }
    float q = q0 + q1;
#pragma unroll
    for (int o = 16; o; o >>= 1) q += __shfl_xor_sync(~0u, q, o);
    const float rs = rsqrtf(q * (1.f / 512.f) + 1e-5f);
    asm volatile("st.shared.u16 [%0], %1;" ::"r"(hi + OFF_P0S + lane * 32 + w * 2), "h"(__bfloat16_as_ushort(__float2bfloat16((bf_lo(xc) - mu) * rs))) : "memory");
    asm volatile("st.shared.u16 [%0], %1;" ::"r"(hi + OFF_P0S + lane * 32 + 16 + w * 2), "h"(__bfloat16_as_ushort(__float2bfloat16((bf_hi(xc) - mu) * rs))) : "memory");
  }
    cbar();
  }
  if (p0a && wg == 0) {
    uint32_t* const mo = gs->MODA + cta * 32 + wq * 64 + lane;
    const uint32_t xn0 = lds1(hi + OFF_P0S + wq * 256 + lane * 4), xn1 = lds1(hi + OFF_P0S + wq * 256 + 128 + lane * 4);
    float d[4] = {0.f, 0.f, 0.f, 0.f};
    asm volatile("" : "+f"(d[0]), "+f"(d[1]), "+f"(d[2]), "+f"(d[3]) :: "memory");
#pragma unroll 1
    for (int i = 0; i < 4; i++) {
      mbar_wait(hi + BAR(BAR_WA) + 8 * i);
      wg_fence();
#pragma unroll
      for (int ks = 0; ks < 8; ks++) wgmma_n8(d, dlo(slot(8)) + i * 1024 + ks * 128, dlo(OFF_R0) + i * 128 + (ks >> 2) * 64 + (ks & 3) * 2);
      wg_commit();
    }
    wg_wait<0>();
    asm volatile("" : "+f"(d[0]), "+f"(d[1]), "+f"(d[2]), "+f"(d[3]) :: "memory");
    uint32_t y0 = pack_bf16(d[0], d[1]), y1 = pack_bf16(d[2], d[3]);
    if (cta >= 64) { y0 = hmul2(xn0, hadd2(y0, ONE2)); y1 = hmul2(xn1, hadd2(y1, ONE2)); }
    stg1(mo, nz(y0));
    stg1(mo + 32, nz(y1));
    if (lane == 0) mbar_arrive(hi + BAR(BAR_P0D));
  }
  cbar();
  {
    uint32_t* const qpo = pin(gs->QP + (cta * 256 + tid) * 2);
    const uint32_t* const modi = pin(gs->MODA + 512 * jI + tid * 2);
    uint32_t a[8][4];
    mbar_wait(hi + BAR(BAR_FULL + U_WQ) + 8 * wg); mbar_wait(hi + BAR(BAR_FULL + U_WQ + 2) + 8 * wg);
    load_a_t(a, hi + OFF_R1 + wg * 16384, wq, lane);
    mbar_wait(hi + BAR(BAR_FULL + U_WQ + MOD_AT));
    backoff(D_MOD);
    uint2 sa, ca;
    do { sa = ldg_rlx2(modi); ca = ldg_rlx2(modi + 2048); } while (min(min(sa.x, sa.y), min(ca.x, ca.y)) == 0);
    sts2(hi + OFF_BS + tid * 8, hadd2(ca.x, sa.x), hadd2(ca.y, sa.y));
    cbar();
    float d[4];
    mma128(d, a, hi + OFF_BS + lane * 16);
    stg_u64(qpo, pack_bf16(d[0], d[1]), pack_bf16(d[2], d[3]));
  }
  const uint32_t ckq = clk32();
  mbar_wait(hi + BAR(BAR_EPOCH));
  const int par = lds1(hi + OFF_EPOCH) & 1;
  uint32_t* const QX = gs->QX[par];
  {
    uint32_t a[8][4];
    {
      const int mi = lane >> 3, r = lane & 7;
      const int row = 16 * w + 8 * (mi & 1) + r;
      mbar_wait(hi + BAR(BAR_FULL + U_WUK) + 16 * wg); mbar_wait(hi + BAR(BAR_FULL + U_WUK + 1) + 16 * wg);
#pragma unroll
      for (int ks = 0; ks < 8; ks++) {
        const int chunk = 2 * ks + (mi >> 1);
        ldsm4(a[ks], hi + OFF_R2 + (ks >> 2) * 16384 + row * 128 + (((chunk & 7) ^ r) << 4));
      }
    }
    uint32_t* const qxo = pin(QX + ((lane >> 1) * 32 + hI) * 256 + (128 * jI + 16 * w + 8 * (lane & 1)) / 2);
    const uint32_t* const qpi = pin(gs->QP + (hI * 4 * 256 + tid) * 2);
    mbar_wait(hi + BAR(BAR_FULL - 1));
    wait_until(ckq, D_QP);
    uint2 qp[4];
#pragma unroll
    for (int i = 0; i < 4; i++) qp[i] = ldg_u64(qpi + i * 512);
    sum4_to_smem<4>(qp, qpi, hi + OFF_BS2 + (16 * w + g) * 16 + t * 4, [] {});
    cbar();
    float d[4];
    mma128(d, a, hi + OFF_BS2 + lane * 16);
    const float sc = 0.08838834764831845f * 1.4426950408889634f;
    const uint32_t stg = hi + OFF_P0S + 4096 + w * 256;
    stsm2t(stg + (lane & 7) * 32 + ((lane >> 3) & 1) * 16, pack_bf16(d[0] * sc, d[1] * sc), pack_bf16(d[2] * sc, d[3] * sc));
    __syncwarp();
    if (lane < 16) stg_u128(qxo, lds4(stg + lane * 16));
    if (lane == 0) mbar_arrive(hi + BAR(BAR_P2E));
  }
  const uint32_t ckx = clk32();
  uint32_t fb = 0;
  {
    const uint32_t* qx = pin(QX + bI * 8192 + w * 1024 + lane * 4);
    mbar_wait(hi + BAR(BAR_FULL + QX_AT));
    wait_until(ckx, D_QX);
    uint4 v[8];
#pragma unroll
    for (int i = 0; i < 8; i++) v[i] = ldg_u128(qx + i * 128);
    asm volatile("bar.sync 2, 288;" ::: "memory");
    while (true) {
      bool all = true;
#pragma unroll
      for (int i = 0; i < 8; i++) all = all && v[i].w != 0;
      if (all) break;
#pragma unroll
      for (int i = 0; i < 8; i++) if (v[i].w == 0) v[i] = ldg_u128(qx + i * 128);
    }
#pragma unroll
    for (int i = 0; i < 8; i++) {
      const int hh = (4 * w + (i >> 1)) ^ (16 * rI), ch = 32 * (i & 1) + lane;
      sts4(hi + OFF_R0 + (ch >> 3) * 4096 + hh * 128 + (((ch & 7) ^ (hh & 7)) << 4), v[i]);
    }
    asm volatile("fence.proxy.async.shared::cta;" ::: "memory");
    cbar();
    if (tid == 0) mbar_arrive(hi + BAR(BAR_GO));
  }

  uint32_t ck1;
  const uint32_t *px, *pm;
  uint32_t* x2o;
  {
    float O32[4][16], O16[4][8];
    uint32_t ebar;
    asm("mapa.shared::cluster.u32 %0, %1, %2;" : "=r"(ebar) : "r"(hi + BAR(BAR_EMPTY)), "r"(rI ^ (lane & 1)));
#pragma unroll
    for (int i = 0; i < 16; i++) O32[0][i] = O32[1][i] = O32[2][i] = O32[3][i] = 0.f;
#pragma unroll
    for (int i = 0; i < 4; i++) tie(O32[i]);
    auto pv2 = [&](int T, int WG, auto& O, int mb, int k0, int k1) {
      const int n = 8 * T + 4 * WG + mb;
      const uint32_t da = dlo(SB) + (sizeof(O[0]) == 64 ? n : n - 23) * 512, db = (WG && mb && T == 2) ? dlo(SB) : da + 512, dp = dlo(OFF_PT) + (T & 1) * 256;
#pragma unroll
      for (int ks = k0; ks < k1; ks++) { wgmma_ss<1, 1>(O[mb], da + ks * 128, dp + ks * 2); wgmma_ss<1, 1>(O[mb + 1], db + ks * 128, dp + ks * 2); }
      wg_commit();
    };
    auto pv = [&](int T, int WG, auto& O) { wg_fence(); pv2(T, WG, O, 0, 0, 4); pv2(T, WG, O, 2, 0, 4); };
    auto release = [&](int T, auto& O) {
      wg_wait<0>();
#pragma unroll
      for (int i = 0; i < 4; i++) tie(O[i]);
      if (lane < 2) mbar_arrive_cluster(ebar + 8 * T);
    };
    auto rescale = [&](auto& O) {
#pragma unroll
      for (int jn = 0; jn < (int)(sizeof(O[0]) / 16); jn++) {
        const float2 a = ldsf2(hi + OFF_ALPHA + (8 * jn + 2 * t) * 4);
#pragma unroll
        for (int mb = 0; mb < 4; mb++) { O[mb][4 * jn] *= a.x; O[mb][4 * jn + 1] *= a.y; O[mb][4 * jn + 2] *= a.x; O[mb][4 * jn + 3] *= a.y; }
      }
    };
    uint4 oe[4];
    uint32_t mate;
    asm("mapa.shared::cluster.u32 %0, %1, %2;" : "=r"(mate) : "r"(hi + SB), "r"(rI ^ 1));
    mate -= SB;
    auto split_o = [&] {
#pragma unroll
      for (int mb = 0; mb < 4; mb++)
        oe[mb] = make_uint4(pack_bf16(O32[mb][8], O32[mb][9]), pack_bf16(O32[mb][10], O32[mb][11]), pack_bf16(O32[mb][12], O32[mb][13]), pack_bf16(O32[mb][14], O32[mb][15]));
#pragma unroll
      for (int i = 0; i < 32; i++) asm volatile("mov.b32 %0, %1;" : "=f"(O16[i >> 3][i & 7]) : "f"(O32[i >> 3][i & 7]));
    };
    auto send_o = [&] {
      mbar_wait(hi + BAR(BAR_EMPTY + 2));
#pragma unroll
      for (int mb = 0; mb < 4; mb++)
        asm volatile("st.async.weak.shared::cluster.mbarrier::complete_tx::bytes.v4.b32 [%0], {%1,%2,%3,%4}, [%5];"
                     ::"r"(mate + OFF_XE + w * 4096 + mb * 512 + lane * 16), "r"(oe[mb].x), "r"(oe[mb].y), "r"(oe[mb].z), "r"(oe[mb].w), "r"(mate + BAR(BAR_XE)) : "memory");
    };
    uint32_t bd[2];
    float mnew, anew, bnew;
    bool moved;
    auto fetch_o = [&] {
      mbar_wait_cluster(hi + BAR(BAR_XE));
      const float mo = ldsf(hi + OFF_MREF + (lane & 15) * 4), mx = ldsf(hi + OFF_MX + (lane & 15) * 8);
#pragma unroll
      for (int mb = 0; mb < 4; mb++) oe[mb] = lds4(hi + OFF_XE + w * 4096 + mb * 512 + lane * 16);
      mnew = mx - mo > 44.f ? mx : mo;
      moved = __any_sync(~0u, mnew != mo);
      anew = ex2(mo - mnew); bnew = ex2(mx - mnew);
      const uint32_t b = pack_bf16(bnew, 0.f);
      bd[0] = shl_clamp(__shfl_sync(~0u, b, g), 16 * (g - 2 * t));
      bd[1] = shl_clamp(__shfl_sync(~0u, b, g + 8), 16 * (g - 2 * t));
    };
    auto merge_o = [&] {
      if (__builtin_expect(moved, 0)) {
#pragma unroll
        for (int i = 0; i < 4; i++) {
          const float a = __shfl_sync(~0u, anew, 8 * (i >> 1) + 2 * t + (i & 1));
#pragma unroll
          for (int mb = 0; mb < 4; mb++) { O16[mb][4 * (i >> 1) + (i & 1)] *= a; O16[mb][4 * (i >> 1) + 2 + (i & 1)] *= a; }
        }
      }
#pragma unroll
      for (int mb = 0; mb < 4; mb++) {
        mma_v(reinterpret_cast<float (&)[4]>(O16[mb][0]), oe[mb], bd[0], 0u);
        mma_v(reinterpret_cast<float (&)[4]>(O16[mb][4]), oe[mb], 0u, bd[1]);
      }
    };
    uint32_t* x1l[4];
    auto late_addr = [&] {
      mbar_wait(hi + BAR(BAR_FM));
      fb = lds1(hi + OFF_FB + tid * 4);
#pragma unroll
      for (int i = 0; i < 4; i++)
        x1l[i] = hold(inbox((16 * rI + 2 * t) * 4 + 2 * wg + (bI >> 2), bI & 3, fb, 4 * (i & 1) + (i >> 1), pI * 128 + (wq * 8 + g) * 2));
      px = hold(inbox((cta & ~1) + wg, wq, (fb >> (8 + (jI & 2) + wg)) ^ wq, 0, t * 128 + rI * 64 + 4 * g));
      pm = hold(inbox(cta & ~1, 6, fb, 8 + (jI & 2), 512 + (w * 8 + t) * 8));
      x2o = hold(inbox(4 * hI + (jI >> 1) + (~jI & 2), 7, ~fb, 8 + (jI >> 1) + (~jI & 2), (jI & 1) * 512 + tid * 2));
    };
    auto put_late = [&](int jj) {
#pragma unroll
      for (int i = 0; i < 4; i++) {
        const int jn = i >> 1, e = i & 1, r = 4 * jn + e;
        stg_u64(x1l[i] + (8 * jn + e) * 4 * 16384 + jj * 64, pack_bf16(O16[2 * jj][r], O16[2 * jj][r + 2]), pack_bf16(O16[2 * jj + 1][r], O16[2 * jj + 1][r + 2]));
      }
    };
    auto last_products = [&](int WG) {
      wg_fence();
      pv2(4, WG, O16, 0, 0, 4);
      ck1 = clk32();
      pv2(4, WG, O16, 2, 0, 3);
      wg_wait<1>();
      tie(O16[0]); tie(O16[1]);
      put_late(0);
      __syncwarp();
      wg_fence();
      pv2(4, WG, O16, 2, 3, 4);
      wg_wait<0>();
      tie(O16[2]); tie(O16[3]);
      put_late(1);
      if (lane < 2) mbar_arrive_cluster(ebar + 32);
    };

    if (wg == 0) {
      float S32[16], S16[8];
      float m_run = -INFINITY;
      float mh[8];
#pragma unroll
      for (int i = 0; i < 16; i++) S32[i] = S16[i & 7] = mh[i & 7] = 0.f;
      const uint32_t ptl = hold32(hi + OFF_PT + (8 * (lane >> 4) + (lane & 7)) * 128 + (((2 * wq + ((lane >> 3) & 1)) ^ (lane & 7)) << 4));
      auto landed = [&](int T) { return __ballot_sync(~0u, mbar_test(hi + BAR(BAR_FULL + 8 * T) + 8 * (lane & 7))); };
      auto softmax = [&](int T, auto& O, auto& S) {
        constexpr int NJ = sizeof(S) / 16;
        wg_wait<0>();
        tie(S);
        auto update = [&] {
            float mx[2 * NJ];
#pragma unroll
            for (int jn = 0; jn < NJ; jn++) { mx[2 * jn] = fmaxf(S[4 * jn], S[4 * jn + 2]); mx[2 * jn + 1] = fmaxf(S[4 * jn + 1], S[4 * jn + 3]); }
            float a4[4], a2[2], a1;
            if constexpr (NJ == 4) {
              const bool up = lane & 16;
#pragma unroll
              for (int i = 0; i < 4; i++) { const float send = up ? mx[i] : mx[4 + i]; const float keep = up ? mx[4 + i] : mx[i]; a4[i] = fmaxf(keep, __shfl_xor_sync(~0u, send, 16)); }
            } else {
#pragma unroll
              for (int i = 0; i < 4; i++) { a4[i] = fmaxf(mx[i], __shfl_xor_sync(~0u, mx[i], 16)); if (lane & 16) a4[i] = -INFINITY; }
            }
            {
              const bool up = lane & 8;
#pragma unroll
              for (int i = 0; i < 2; i++) { const float send = up ? a4[i] : a4[2 + i]; const float keep = up ? a4[2 + i] : a4[i]; a2[i] = fmaxf(keep, __shfl_xor_sync(~0u, send, 8)); }
            }
            {
              const bool up = lane & 4;
              const float send = up ? a2[0] : a2[1]; const float keep = up ? a2[1] : a2[0];
              a1 = fmaxf(keep, __shfl_xor_sync(~0u, send, 4));
            }
            stsf(hi + OFF_RED + (wq * 32 + 8 * (g >> 1) + 2 * t + (g & 1)) * 4, a1);
            wg0bar();
            const float mt = fmaxf(fmaxf(ldsf(hi + OFF_RED + lane * 4), ldsf(hi + OFF_RED + 128 + lane * 4)),
                                   fmaxf(ldsf(hi + OFF_RED + 256 + lane * 4), ldsf(hi + OFF_RED + 384 + lane * 4)));
            const float m_new = fmaxf(m_run, ceilf(mt) + 24.f);
            if (wq == 0) { stsf(hi + OFF_MREF + (T == 4 ? 128 : 0) + lane * 4, m_new); stsf(hi + OFF_ALPHA + lane * 4, ex2(m_run - m_new)); }
            m_run = m_new;
#pragma unroll
            for (int i = 0; i < 2 * NJ; i++) mh[i] = __shfl_sync(~0u, m_new, 8 * (i >> 1) + 2 * t + (i & 1));
            if (T > 0) { wg0bar(); rescale(O); }
        };
        auto write_p = [&] {
          uint32_t pk[2 * NJ];
          float x[4 * NJ];
#pragma unroll
          for (int i = 0; i < 4 * NJ; i++) x[i] = S[i] - mh[2 * (i >> 2) + (i & 1)];
#pragma unroll
          for (int i = 0; i < 2 * NJ; i++) pk[i] = pack_bf16(ex2(x[2 * i]), ex2(x[2 * i + 1]));
#pragma unroll
          for (int hf = 0; hf < NJ / 2; hf++) stsm4t(ptl + (T & 1) * 4096 + hf * 2048, pk[4 * hf], pk[4 * hf + 1], pk[4 * hf + 2], pk[4 * hf + 3]);
          asm volatile("fence.proxy.async.shared::cta;" ::: "memory");
          if constexpr (NJ == 4) {
#pragma unroll
            for (int i = 0; i < 8; i++) x[i] = fmaxf(x[i], x[i + 8]);
          }
          return cbar_or(fmaxf(fmaxf(fmaxf(x[0], x[1]), fmaxf(x[2], x[3])), fmaxf(fmaxf(x[4], x[5]), fmaxf(x[6], x[7]))) > 32.f);
        };
        if constexpr (NJ == 4) {
          bool over = T == 0;
#pragma unroll 1
          do {
            if (over) update();
            over = write_p();
          } while (__builtin_expect(over, 0));
        } else {
#pragma unroll 1
          while (__builtin_expect(write_p(), 0)) update();
        }
      };
      uint32_t have = 0;
#pragma unroll
      for (int i = 0; i < 4; i++) x1l[i] = nullptr;
      px = pm = x2o = nullptr;
#pragma unroll 1
      for (int T = 0; T < 3; T++) {
        sfor<0, 8>([&](auto jc) {
          constexpr int jj = decltype(jc)::value;
          const uint32_t da = dlo(SB) + box_slot(8 * T + jj) * 512, db = dlo(OFF_R0) + jj * 256;
          mbar_wait(hi + BAR(BAR_FULL) + 64 * T + 8 * jj);
          wg_fence();
          wgmma_ss<0, jj != 0>(S32, da, db);
#pragma unroll
          for (int ks = 1; ks < 4; ks++) wgmma_ss<0, 1>(S32, da + ks * 2, db + ks * 2);
          wg_commit();
        });
        softmax(T, O32, S32);
        pv(T, 0, O32);
        have = landed(3);
        release(T, O32);
        if (T == 1) late_addr();
      }
      split_o();
#pragma unroll 1
      for (int T = 3;; T++) {
        sfor<0, 8>([&](auto jc) {
          constexpr int jj = decltype(jc)::value;
          const uint32_t da = dlo(SB) + (8 * T + jj - 23) * 512, db = dlo(OFF_R0) + jj * 256;
          if (!((have >> jj) & 1)) mbar_wait(hi + BAR(BAR_FULL) + 64 * T + 8 * jj);
          wg_fence();
          wgmma_ss<0, jj != 0>(S16, da, db);
#pragma unroll
          for (int ks = 1; ks < 4; ks++) wgmma_ss<0, 1>(S16, da + ks * 2, db + ks * 2);
          wg_commit();
          if (jj == 2 && T == 3) send_o();
        });
        softmax(T, O16, S16);
        if (T == 4) break;
        pv(3, 0, O16);
        have = landed(4);
        fetch_o();
        if (wq == 0) stsf(hi + OFF_MREF + 128 + lane * 4, mnew);
        mbar_wait(hi + BAR(BAR_XE));
        release(3, O16);
        merge_o();
        if (__builtin_expect(moved, 0)) {
          m_run = mnew;
#pragma unroll
          for (int i = 0; i < 4; i++) mh[i] = __shfl_sync(~0u, mnew, 8 * (i >> 1) + 2 * t + (i & 1));
        }
      }
      last_products(0);
    } else {
      float ls[2] = {0.f, 0.f};
      const int hr = 4 * wq + (lane >> 3);
      const uint32_t ptl = hi + OFF_PT + (tid & 127) * 16;
      auto sum8 = [](const uint4& v) { return ((bf_lo(v.x) + bf_hi(v.x)) + (bf_lo(v.y) + bf_hi(v.y))) + ((bf_lo(v.z) + bf_hi(v.z)) + (bf_lo(v.w) + bf_hi(v.w))); };
      auto row_sum = [](float l) { l += __shfl_xor_sync(~0u, l, 1); l += __shfl_xor_sync(~0u, l, 2); return l + __shfl_xor_sync(~0u, l, 4); };
      auto get_p = [&](auto& O) {
        if (__builtin_expect(cbar_or(false), 0)) {
          cbar_or(false);
          rescale(O);
          ls[0] *= ldsf(hi + OFF_ALPHA + hr * 4);
          if (sizeof(O[0]) == 64) ls[1] *= ldsf(hi + OFF_ALPHA + 64 + hr * 4);
        }
      };
#pragma unroll 1
      for (int T = 0; T < 3; T++) {
        get_p(O32);
        pv(T, 1, O32);
        ls[0] += sum8(lds4(ptl + (T & 1) * 4096));
        ls[1] += sum8(lds4(ptl + (T & 1) * 4096 + 2048));
        release(T, O32);
      }
      split_o();
      send_o();
      {
        const float l = row_sum(ls[1]);
        if (!(lane & 7))
          asm volatile("st.async.weak.shared::cluster.mbarrier::complete_tx::bytes.v2.b32 [%0], {%1,%2}, [%3];"
                       ::"r"(mate + OFF_MX + hr * 8), "r"(lds1(hi + OFF_MREF + 64 + hr * 4)), "r"(__float_as_uint(l)), "r"(mate + BAR(BAR_XE)) : "memory");
      }
      get_p(O16);
      pv(3, 1, O16);
      ls[0] += sum8(lds4(ptl + 4096));
      fetch_o();
      const float lx = ldsf(hi + OFF_MX + hr * 8 + 4) * __shfl_sync(~0u, bnew, hr);
      ls[0] = ls[0] * __shfl_sync(~0u, anew, hr) + ((lane & 7) ? 0.f : lx);
      release(3, O16);
      merge_o();
      late_addr();
      uint32_t* const mlo = hold(inbox((16 * rI + hr) * 4 + (lane & 2), 6, fb, 13, 512 + (cta >> 1) * 8 + (lane & 1) * 4));
      mbar_wait(hi + BAR(BAR_CLR));
      get_p(O16);
      {
        const uint32_t m = lds1(hi + OFF_MREF + 128 + hr * 4), l = nz(__float_as_uint(row_sum(ls[0] + sum8(lds4(ptl)))));
        if (!(lane & 4)) stg4_b128(mlo, make_uint4(m, l, m, l));
      }
      last_products(1);
    }
  }

  uint32_t aw[8][4];
  uint2 own;
  uint32_t x2m, x2b;
  asm("mapa.shared::cluster.u32 %0, %1, %2;" : "=r"(x2m) : "r"(hi + OFF_BS5 + 2048 + tid * 8), "r"(rI ^ 1));
  asm("mapa.shared::cluster.u32 %0, %1, %2;" : "=r"(x2b) : "r"(hi + BAR(BAR_X2)), "r"(rI ^ 1));
  {
    wait_until(ck1, X1_D0);
    uint2 ml[2];
    uint4 v[4];
#pragma unroll
    for (int i = 0; i < 4; i++) v[i] = ldg_2u64(px + (i >> 1) * 512 + (i & 1) * 32);
#pragma unroll
    for (int i = 0; i < 2; i++) ml[i] = ldg_u64(pm + i * 32);
    uint32_t sel[4][2] = {{0u, 0u}, {0u, 0u}, {0u, 0u}, {0u, 0u}};
    float Ls = 0.f;
    bool w_ok = false;
    const uint32_t bso = hold32(hi + OFF_BS4 + w * 320 + (16 * (t >> 1) + 8 * (g >> 2) + 4 * (g & 1) + 2 * (t & 1) + ((g >> 1) & 1)) * 8), bsi = hold32(hi + OFF_BS4 + g * 320 + t * 16);
    const uint32_t lso = hold32(hi + OFF_BS4 + w * 320 + 256 + t * 4), lsi = hold32(hi + OFF_BS4 + t * 640 + 256);
    const uint32_t wa = hold32(hi + OFF_WUV + wg * 8192 + (lane >> 4) * 4096 + (lane & 7) * 128 + (((2 * wq + ((lane >> 3) & 1)) ^ (lane & 7)) << 4));
    mbar_wait(hi + BAR(BAR_EMPTY + 3));
    mbar_wait(hi + BAR(BAR_FULL + U_WUV) + 8 * wg);
#pragma unroll
    for (int ks = 0; ks < 4; ks++) { ldsm4t(aw[ks], wa + ks * 1024); aw[4 + ks][0] = aw[4 + ks][1] = aw[4 + ks][2] = aw[4 + ks][3] = 0; }
    bool wv_ok = false;
    float e0[4], e1[4];
#pragma unroll 1
    while (true) {
      if (!wv_ok && mbar_test(hi + BAR(BAR_FULL + U_WUV + 2) + 8 * wg)) {
        wv_ok = true;
#pragma unroll
        for (int ks = 0; ks < 4; ks++) ldsm4t(aw[4 + ks], wa - (OFF_WUV - OFF_WUV2) + ks * 1024);
      }
#pragma unroll
      for (int i = 0; i < 4; i++) tie(v[i]);
      tie(ml[0]); tie(ml[1]);
      const bool ok = __all_sync(~0u, w_ok && min(min3(min3(v[0].y, v[0].w, v[1].y), v[1].w, v[2].y), min3(v[2].w, v[3].y, v[3].w)) != 0);
#pragma unroll
      for (int i = 0; i < 4; i++) e0[i] = e1[i] = 0.f;
      mma_v(e0, v[0], sel[0][0], sel[0][1]); mma_v(e1, v[2], sel[2][0], sel[2][1]);
      mma_v(e0, v[1], sel[1][0], sel[1][1]); mma_v(e1, v[3], sel[3][0], sel[3][1]);
      if (ok) break;
#pragma unroll
      for (int i = 0; i < 4; i++) if (v[i].y == 0 || v[i].w == 0) v[i] = ldg_2u64(px + (i >> 1) * 512 + (i & 1) * 32);
      if (!w_ok) {
        if (__all_sync(~0u, min(ml[0].y, ml[1].y) != 0)) {
          w_ok = true;
          float M = fmaxf(__uint_as_float(ml[0].x), __uint_as_float(ml[1].x));
          M = fmaxf(M, __shfl_xor_sync(~0u, M, 1)); M = fmaxf(M, __shfl_xor_sync(~0u, M, 2));
          const uint32_t wb[2] = {pack_bf16(ex2(__uint_as_float(ml[0].x) - M), 0.f), pack_bf16(ex2(__uint_as_float(ml[1].x) - M), 0.f)};
#pragma unroll
          for (int i = 0; i < 4; i++) { sel[i][0] = shl_clamp(wb[i >> 1], 16 * g - 64 * (i & 1)); sel[i][1] = shl_clamp(wb[i >> 1], 16 * g - 64 * (i & 1) - 32); }
          Ls = bf_lo(wb[0]) * __uint_as_float(ml[0].y) + bf_lo(wb[1]) * __uint_as_float(ml[1].y);
        } else {
#pragma unroll
          for (int i = 0; i < 2; i++) ml[i] = ldg_u64(pm + i * 32);
        }
      }
    }
    stsf(lso, Ls);
    sts2(bso, pack_bf16(e0[0] + e1[0], e0[1] + e1[1]), pack_bf16(e0[2] + e1[2], e0[3] + e1[3]));
    cbar();
    float o[4][4] = {{0.f, 0.f, 0.f, 0.f}, {0.f, 0.f, 0.f, 0.f}, {0.f, 0.f, 0.f, 0.f}, {0.f, 0.f, 0.f, 0.f}};
    uint4 b[4];
#pragma unroll
    for (int kk = 0; kk < 4; kk++) b[kk] = lds4(bsi + kk * 64);
    const float4 la = ldsf4(lsi), lb = ldsf4(lsi + 320);
    if (!wv_ok) {
      mbar_wait(hi + BAR(BAR_FULL + U_WUV + 2) + 8 * wg);
#pragma unroll
      for (int ks = 0; ks < 4; ks++) ldsm4t(aw[4 + ks], wa - (OFF_WUV - OFF_WUV2) + ks * 1024);
    }
#pragma unroll
    for (int kk = 0; kk < 4; kk++) { mma16816(o[(2 * kk) & 3], aw[2 * kk], b[kk].x, b[kk].y); mma16816(o[(2 * kk + 1) & 3], aw[2 * kk + 1], b[kk].z, b[kk].w); }
    const float ia = rcp((la.x + la.y) + (la.z + la.w)), ib = rcp((lb.x + lb.y) + (lb.z + lb.w));
    const uint32_t y0 = pack_bf16(((o[0][0] + o[1][0]) + (o[2][0] + o[3][0])) * ia, ((o[0][1] + o[1][1]) + (o[2][1] + o[3][1])) * ib);
    const uint32_t y1 = pack_bf16(((o[0][2] + o[1][2]) + (o[2][2] + o[3][2])) * ia, ((o[0][3] + o[1][3]) + (o[2][3] + o[3][3])) * ib);
    stg_u64(x2o, y0, y1);
    asm volatile("st.async.weak.shared::cluster.mbarrier::complete_tx::bytes.v2.b32 [%0], {%1,%2}, [%3];" ::"r"(x2m), "r"(y0), "r"(y1), "r"(x2b) : "memory");
    own = make_uint2(y0, y1);
  }
  const uint32_t ck2 = clk32();
  {
    uint32_t* const o = hold(inbox(4 * (8 * jI + w) + (g >> 1), 6, fb, 12, (g & 1) * 256 + hI * 8 + 2 * t));
    const uint32_t* const x2k = hold(inbox(4 * hI + 1 + (jI >> 1), 7, ~fb, 9 + (jI >> 1), tid * 2));
    const uint32_t bso = hold32(hi + OFF_BS5 + (16 * w + g) * 16 + t * 4), bsi = hold32(hi + OFF_BS5 + lane * 16);
    const uint32_t wa = hold32(hi + OFF_WO + wg * 8192 + (8 * (lane >> 4) + (lane & 7)) * 128 + (((2 * wq + ((lane >> 3) & 1)) ^ (lane & 7)) << 4));
    wait_until(ck2, D_X2);
    uint2 v[4];
    v[0] = ldg_u64(x2k); v[1] = ldg_u64(x2k + 512);
    mbar_wait_cluster(hi + BAR(BAR_X2));
    v[2] = lds2(hi + OFF_BS5 + 2048 + tid * 8); v[3] = own;
    v[2].y = nz(v[2].y); v[3].y = nz(v[3].y);
    int wo_n = 0;
    sum4_to_smem<2>(v, x2k, bso, [&] {
      if (wo_n == 0 && mbar_test(hi + BAR(BAR_FULL + U_WO) + 8 * wg)) {
        wo_n = 1;
#pragma unroll
        for (int ks = 0; ks < 4; ks++) ldsm4t(aw[ks], wa + ks * 2048);
      }
      if (wo_n == 1 && mbar_test(hi + BAR(BAR_FULL + U_WO + 2) + 8 * wg)) {
        wo_n = 2;
#pragma unroll
        for (int ks = 0; ks < 4; ks++) ldsm4t(aw[4 + ks], wa + 16384 + ks * 2048);
      }
    });
    cbar();
    float e[4][4] = {{0.f, 0.f, 0.f, 0.f}, {0.f, 0.f, 0.f, 0.f}, {0.f, 0.f, 0.f, 0.f}, {0.f, 0.f, 0.f, 0.f}};
    uint32_t b[4][4];
#pragma unroll
    for (int kk = 0; kk < 4; kk++) ldsm4t(b[kk], bsi + kk * 512);
    if (wo_n < 2) {
      if (wo_n == 0) {
        mbar_wait(hi + BAR(BAR_FULL + U_WO) + 8 * wg);
#pragma unroll
        for (int ks = 0; ks < 4; ks++) ldsm4t(aw[ks], wa + ks * 2048);
      }
      mbar_wait(hi + BAR(BAR_FULL + U_WO + 2) + 8 * wg);
#pragma unroll
      for (int ks = 0; ks < 4; ks++) ldsm4t(aw[4 + ks], wa + 16384 + ks * 2048);
    }
#pragma unroll
    for (int ks = 0; ks < 8; ks++) mma16816(e[ks & 3], aw[ks], b[ks >> 1][2 * (ks & 1)], b[ks >> 1][2 * (ks & 1) + 1]);
    stg_u64(o, pack_bf16((e[0][0] + e[1][0]) + (e[2][0] + e[3][0]), (e[0][1] + e[1][1]) + (e[2][1] + e[3][1])),
            pack_bf16((e[0][2] + e[1][2]) + (e[2][2] + e[3][2]), (e[0][3] + e[1][3]) + (e[2][3] + e[3][3])));
    if (lane == 0) mbar_arrive(hi + BAR(BAR_P5D));
  }
  const uint32_t ck3 = clk32();
  if (cta < NFF) {
    const int mi = lane >> 3, r = lane & 7;
    uint32_t a1[4][4], a2[4][4];
    uint32_t bc[8], bs[8];
    const uint32_t* const mbi = gs->MODB + (2 + wg) * 2048 + ((~((fb >> 14)) & 1) << 10) + 256 * wq + lane;
#pragma unroll
    for (int i = 0; i < 8; i++) { bs[i] = ldg_rlx1(mbi + i * 32); bc[i] = ldg_rlx1(mbi + 4096 + i * 32); }
    const int lp = (tid >> 2) & 31, kq = tid & 3;
    const int fo = (lp >> 2) + 8 * (kq >> 1), bo = 2 * (lp & 3) + (kq & 1);
    const uint32_t* xb = hold(gs->X3B + ((cta >> 1) & 1) * 4096 + wg * 2048 + (((fb >> 14) & 1) << 10) + (16 * wq + t) * 16 + 2 * g);
    uint32_t* ox[4];
#pragma unroll
    for (int mb = 0; mb < 4; mb++) ox[mb] = hold(inbox(16 * w + 4 * mb + (g >> 1), 4 + (cta >= 56), fb, 16 + 4 * mb, (cta >= 56 ? cta - 56 : cta) * 16 + (g & 1) * 8 + 2 * t));
    const uint32_t gi = hold32(hi + OFF_REDG + tid * 4);
    const uint32_t h1o = hold32(hi + OFF_H1 + fo * 16 + bo * 2), sti = hold32(hi + OFF_REDS + bo * 80), sto = hold32(hi + OFF_REDS + g * 80 + w * 8);
    const uint32_t a1a = hold32(hi + OFF_W1 + (64 * w + 8 * (mi >> 1) + r) * 64 + (((2 * rI + (mi & 1)) ^ (r >> 1)) << 4));
    bool w2ok = false;
    uint32_t a2a[4];
#pragma unroll
    for (int mb = 0; mb < 4; mb++) {
      a2a[mb] = hi + OFF_W2 + w * 2048 + (8 * (mi >> 1) + r) * 128 + (((2 * mb + (mi & 1)) ^ r) << 4);
      a2[mb][0] = a2[mb][1] = a2[mb][2] = a2[mb][3] = 0;
    }
#pragma unroll 1
    while (true) {
      uint32_t mn = 0xffffffffu;
#pragma unroll
      for (int i = 0; i < 8; i++) mn = min3(mn, bs[i], bc[i]);
      if (__all_sync(~0u, mn != 0)) break;
#pragma unroll
      for (int i = 0; i < 8; i++) { bs[i] = ldg_rlx1(mbi + i * 32); bc[i] = ldg_rlx1(mbi + 4096 + i * 32); }
    }
#pragma unroll
    for (int i = 0; i < 8; i++) { bs[i] = movm(bs[i]); bc[i] = hadd2(movm(bc[i]), ONE2); }
    mbar_wait(hi + BAR(BAR_FULL + U_W1) + 8 * wg);
#pragma unroll
    for (int ks = 0; ks < 4; ks++) ldsm4t(a1[ks], a1a + ks * 1024);
    {
      float u[2][4] = {{0.f, 0.f, 0.f, 0.f}, {0.f, 0.f, 0.f, 0.f}}, vv[2][4] = {{0.f, 0.f, 0.f, 0.f}, {0.f, 0.f, 0.f, 0.f}};
#pragma unroll
      for (int ks = 0; ks < 4; ks++) { mma16816(u[ks & 1], a1[ks], bc[2 * ks], bc[2 * ks + 1]); mma16816(vv[ks & 1], a1[ks], bs[2 * ks], bs[2 * ks + 1]); }
      sts4f(hi + OFF_REDU + tid * 16, u[0][0] + u[1][0], u[0][1] + u[1][1], u[0][2] + u[1][2], u[0][3] + u[1][3]);
      sts4f(hi + OFF_REDV + tid * 16, vv[0][0] + vv[1][0], vv[0][1] + vv[1][1], vv[0][2] + vv[1][2], vv[0][3] + vv[1][3]);
    }
    if (wg) asm volatile("bar.arrive 1, 256;" ::: "memory"); else cbar();
    float U = 0.f, V = 0.f;
    bool uv = wg;
    wait_until(ck3, D_X3B);
    float G[2][4], S[2][4];
    bool ok;
#pragma unroll 1
    do {
      uint2 x[4];
#pragma unroll
      for (int ks = 0; ks < 4; ks++) x[ks] = ldg_u64(xb + ks * 64);
      if (!uv) {
        uv = true;
        float a[8], b[8];
#pragma unroll
        for (int i = 0; i < 8; i++) { a[i] = ldsf(gi + (OFF_REDU - OFF_REDG) + i * 512); b[i] = ldsf(gi + (OFF_REDV - OFF_REDG) + i * 512); }
        U = ((a[0] + a[1]) + (a[2] + a[3])) + ((a[4] + a[5]) + (a[6] + a[7]));
        V = ((b[0] + b[1]) + (b[2] + b[3])) + ((b[4] + b[5]) + (b[6] + b[7]));
      }
      if (!w2ok && mbar_test(hi + BAR(BAR_FULL + U_W2) + 8 * wg)) {
        w2ok = true;
#pragma unroll
        for (int mb = 0; mb < 4; mb++) ldsm4t(a2[mb], a2a[mb]);
      }
#pragma unroll
      for (int ks = 0; ks < 4; ks++) tie(x[ks]);
      ok = __all_sync(~0u, min(min3(x[0].y, x[1].y, x[2].y), x[3].y) != 0);
#pragma unroll
      for (int i = 0; i < 4; i++) G[0][i] = G[1][i] = S[0][i] = S[1][i] = 0.f;
#pragma unroll
      for (int ks = 0; ks < 4; ks++) {
        const uint32_t s0[4] = {x[ks].x, ONE2, x[ks].y, ONE2};
        mma16816(S[ks & 1], s0, x[ks].x, x[ks].y);
        mma16816(G[ks & 1], a1[ks], hmul2(x[ks].x, bc[2 * ks]), hmul2(x[ks].y, bc[2 * ks + 1]));
      }
    } while (!ok);
    if ((g >> 1) == t) sts2f(sto, (g & 1) ? S[0][3] + S[1][3] : S[0][2] + S[1][2], (g & 1) ? S[0][1] + S[1][1] : S[0][0] + S[1][0]);
    sts4f(hi + OFF_REDG + tid * 16, G[0][0] + G[1][0], G[0][1] + G[1][1], G[0][2] + G[1][2], G[0][3] + G[1][3]);
    if (wg) asm volatile("bar.arrive 3, 256;" ::: "memory"); else asm volatile("bar.sync 3, 256;" ::: "memory");
    if (tid < 128) {
      float gv[8];
      float4 sv[4];
#pragma unroll
      for (int i = 0; i < 4; i++) sv[i] = ldsf4(sti + i * 16);
#pragma unroll
      for (int i = 0; i < 8; i++) gv[i] = ldsf(gi + i * 512);
      const float s1 = ((sv[0].x + sv[0].z) + (sv[1].x + sv[1].z)) + ((sv[2].x + sv[2].z) + (sv[3].x + sv[3].z));
      const float s2 = ((sv[0].y + sv[0].w) + (sv[1].y + sv[1].w)) + ((sv[2].y + sv[2].w) + (sv[3].y + sv[3].w));
      const float gs_ = ((gv[0] + gv[1]) + (gv[2] + gv[3])) + ((gv[4] + gv[5]) + (gv[6] + gv[7]));
      const float mu = s1 * (1.f / 512.f);
      const float rs = rsq(fmaxf(s2 * (1.f / 512.f) - mu * mu, 0.f) + 1e-5f);
      const float hv = fmaxf(rs * (gs_ - mu * U) + V, 0.f);
      asm volatile("st.shared.u16 [%0], %1;" ::"r"(h1o), "h"(__bfloat16_as_ushort(__float2bfloat16(hv))) : "memory");
    }
    if (!w2ok) {
      mbar_wait(hi + BAR(BAR_FULL + U_W2) + 8 * wg);
#pragma unroll
      for (int mb = 0; mb < 4; mb++) ldsm4t(a2[mb], a2a[mb]);
    }
    asm volatile("bar.sync 2, 256;" ::: "memory");
    uint32_t b0, b1;
    ldsm2t(b0, b1, hi + OFF_H1 + (lane & 15) * 16);
#pragma unroll
    for (int mb = 0; mb < 4; mb++) {
      float o[4] = {0.f, 0.f, 0.f, 0.f};
      mma16816(o, a2[mb], b0, b1);
      stg_u64(ox[mb], pack_bf16(o[0], o[1]), pack_bf16(o[2], o[3]));
    }
    if (lane == 0) mbar_arrive(hi + BAR(BAR_P7D));
  }
}

typedef CUresult (*EncodeTiledFn)(CUtensorMap*, CUtensorMapDataType, cuuint32_t, void*, const cuuint64_t*, const cuuint64_t*,
                                  const cuuint32_t*, const cuuint32_t*, CUtensorMapInterleave, CUtensorMapSwizzle,
                                  CUtensorMapL2promotion, CUtensorMapFloatOOBfill);

void make_map(EncodeTiledFn enc, CUtensorMap* m, const void* base, uint64_t cols, uint64_t rows, uint32_t bc, uint32_t br,
              CUtensorMapSwizzle sw, CUtensorMapL2promotion promo) {
  cuuint64_t dims[2] = {cols, rows};
  cuuint64_t strides[1] = {cols * 2};
  cuuint32_t box[2] = {bc, br};
  cuuint32_t es[2] = {1, 1};
  enc(m, CU_TENSOR_MAP_DATA_TYPE_BFLOAT16, 2, const_cast<void*>(base), dims, strides, box, es, CU_TENSOR_MAP_INTERLEAVE_NONE, sw, promo,
      CU_TENSOR_MAP_FLOAT_OOB_FILL_NONE);
}
void make_map3(EncodeTiledFn enc, CUtensorMap* m, const void* base, uint64_t rows, uint32_t br, uint32_t bb) {
  cuuint64_t dims[3] = {64, rows, 8};
  cuuint64_t strides[2] = {1024, 128};
  cuuint32_t box[3] = {64, br, bb};
  cuuint32_t es[3] = {1, 1, 1};
  enc(m, CU_TENSOR_MAP_DATA_TYPE_BFLOAT16, 3, const_cast<void*>(base), dims, strides, box, es, CU_TENSOR_MAP_INTERLEAVE_NONE,
      CU_TENSOR_MAP_SWIZZLE_128B, CU_TENSOR_MAP_L2_PROMOTION_NONE, CU_TENSOR_MAP_FLOAT_OOB_FILL_NONE);
}

}

extern "C" void kernel_launch(void* const* d_in, const int* in_sizes, int n_in, void* d_out, int out_size) {
  (void)in_sizes; (void)n_in; (void)out_size;
  static EncodeTiledFn enc = nullptr;
  static Scratch* scratch = nullptr;
  if (!enc) {
    void* sp = nullptr;
    cudaGetSymbolAddress(&sp, g_s);
    scratch = (Scratch*)(((uintptr_t)sp + 131071) & ~(uintptr_t)131071);
    void* fn = nullptr;
    cudaDriverEntryPointQueryResult q;
    cudaGetDriverEntryPoint("cuTensorMapEncodeTiled", &fn, cudaEnableDefault, &q);
    enc = (EncodeTiledFn)fn;
    cudaFuncSetAttribute(fused_decode_kernel, cudaFuncAttributeMaxDynamicSharedMemorySize, SMEM_BYTES);
  }
  Params P;
  make_map(enc, &P.ckv, d_in[1], 512, 8 * 4096, 64, 64, CU_TENSOR_MAP_SWIZZLE_128B, CU_TENSOR_MAP_L2_PROMOTION_NONE);
  make_map(enc, &P.wq, d_in[2], 4096, 512, 64, 64, CU_TENSOR_MAP_SWIZZLE_128B, CU_TENSOR_MAP_L2_PROMOTION_NONE);
  make_map(enc, &P.wuk, d_in[3], 4096, 512, 64, 64, CU_TENSOR_MAP_SWIZZLE_128B, CU_TENSOR_MAP_L2_PROMOTION_NONE);
  {
    cuuint64_t dims[5] = {4096, 2, 8, 4, 8};
    cuuint64_t strides[4] = {8 * 8192, 8192, 16 * 8192, 64 * 8192};
    cuuint32_t box[5] = {64, 2, 8, 2, 2};
    cuuint32_t es[5] = {1, 1, 1, 1, 1};
    enc(&P.wuv, CU_TENSOR_MAP_DATA_TYPE_BFLOAT16, 5, d_in[4], dims, strides, box, es, CU_TENSOR_MAP_INTERLEAVE_NONE, CU_TENSOR_MAP_SWIZZLE_128B,
        CU_TENSOR_MAP_L2_PROMOTION_NONE, CU_TENSOR_MAP_FLOAT_OOB_FILL_NONE);
  }
  make_map(enc, &P.wo, d_in[5], 512, 4096, 64, 64, CU_TENSOR_MAP_SWIZZLE_128B, CU_TENSOR_MAP_L2_PROMOTION_NONE);
  make_map(enc, &P.w1, d_in[7], 1792, 512, 2 * FCH, 128, CU_TENSOR_MAP_SWIZZLE_64B, CU_TENSOR_MAP_L2_PROMOTION_NONE);
  make_map3(enc, &P.w2, d_in[8], 1792, FCH, 4);
  make_map(enc, &P.wma, d_in[10], 3072, 512, 64, 128, CU_TENSOR_MAP_SWIZZLE_128B, CU_TENSOR_MAP_L2_PROMOTION_NONE);
  make_map(enc, &P.wmod, d_in[10], 3072, 512, 32, 128, CU_TENSOR_MAP_SWIZZLE_64B, CU_TENSOR_MAP_L2_PROMOTION_NONE);
  fused_decode_kernel<<<NCTA, NTHREADS, SMEM_BYTES>>>((__nv_bfloat16*)d_out, scratch, (const uint8_t*)d_in[2], (const uint8_t*)d_in[0],
                                                      (const uint8_t*)d_in[9], P);
}
```
